```python
import torch

def _softmax(x, axis=-1):
    return torch.softmax(x, dim=axis)
def _gelu(x):
    return torch.nn.functional.gelu(x, approximate="tanh")
def _silu(x):
    return torch.nn.functional.silu(x)
def _sigmoid(x):
    return torch.sigmoid(x)
def _layernorm(x, axis=-1, eps=1e-5):
    m = x.mean(dim=axis, keepdim=True)
    v = x.var(dim=axis, keepdim=True, unbiased=False)
    return (x - m) / torch.sqrt(v + eps)
def _scatter_add(tgt, idx, src, axis=0):
    return tgt.clone().index_add_(axis, idx, src)
def _segment_sum(src, seg, n):
    out = torch.zeros((n,) + src.shape[1:], dtype=src.dtype)
    return out.index_add_(0, seg, src)
def _pad(x, pw):
    flat = tuple(v for pair in reversed(pw) for v in pair)
    return torch.nn.functional.pad(x, flat)

kernel_name = 'interleave_layers__sliding_local_dilated__dense_activation_squared_relu__prompt'

def setup_inputs():

    _w = (lambda a: (lambda t: t.to(torch.bfloat16) if t.is_floating_point() else t)(torch.as_tensor(a)))
    def _A_setup():
        B, S, D = 1, 2048, 1024
        return {
            "x": _w((lambda *s: torch.randn(*s, dtype=torch.bfloat16) * 0.05)(B, S, D)),
            "wqkv": _w((lambda *s: torch.randn(*s, dtype=torch.bfloat16) * 0.05)(D, 3 * D)),
            "wo": _w((lambda *s: torch.randn(*s, dtype=torch.bfloat16) * 0.05)(D, D)),
        }
    _A_in = _A_setup()

    def _B_setup():
        B, S, D, F = 1, 2048, 1024, 3584
        return {
            "x": _w((lambda *s: torch.randn(*s, dtype=torch.bfloat16) * 0.05)(B, S, D)),
            "w1": _w((lambda *s: torch.randn(*s, dtype=torch.bfloat16) * 0.05)(D, F)),
            "b1": _w((lambda *s: torch.randn(*s, dtype=torch.bfloat16) * 0.2)(F)),
            "w2": _w((lambda *s: torch.randn(*s, dtype=torch.bfloat16) * 0.05)(F, D)),
            "b2": _w((lambda *s: torch.randn(*s, dtype=torch.bfloat16) * 1.6)(D)),
        }
    _B_in = _B_setup()

    return {
        "A_x": _A_in["x"],
        "A_wqkv": _A_in["wqkv"],
        "A_wo": _A_in["wo"],
        "B_x": _B_in["x"],
        "B_w1": _B_in["w1"],
        "B_b1": _B_in["b1"],
        "B_w2": _B_in["w2"],
        "B_b2": _B_in["b2"],
    }

def reference(A_x, A_wqkv, A_wo, B_x, B_w1, B_b1, B_w2, B_b2):
    def _A_ref(x, wqkv, wo):
        B, S, D = x.shape
        H = 32; Dh = D // H
        W, dil = 8, 2
        qkv = (lambda x, *d: x.permute(*d))((x @ wqkv).reshape(B, S, 3, H, Dh), 2, 0, 3, 1, 4)
        q, k, v = qkv[0], qkv[1], qkv[2]
        scale = Dh ** -0.5
        pos = torch.arange(S)
        off = torch.arange(W) * dil
        idx = pos[:, None] - off[None, :]
        mask = idx >= 0
        idx_c = torch.where(mask, idx, 0).reshape(-1)
        kg = k[:, :, idx_c, :].reshape(B, H, S, W, Dh)
        vg = v[:, :, idx_c, :].reshape(B, H, S, W, Dh)
        logits = torch.einsum("bhsd,bhswd->bhsw", q, kg) * scale
        logits = torch.where(mask[None, None, :, :], logits, -1e9)
        attn = _softmax(logits, axis=-1)
        o = torch.einsum("bhsw,bhswd->bhsd", attn, vg)
        return (lambda x, *d: x.permute(*d))(o, 0, 2, 1, 3).reshape(B, S, D) @ wo

    def _B_ref(x, w1, b1, w2, b2):
        h = torch.einsum("bsd,df->bsf", x, w1) + b1
        zero = torch.zeros_like(h)
        r = torch.where(h > zero, h, zero)
        h = r * r
        out = torch.einsum("bsf,fd->bsd", h, w2) + b2
        return out

    x = A_x
    x = x + _A_ref(_layernorm(x, axis=-1), A_wqkv, A_wo)
    x = x + _B_ref(_layernorm(x, axis=-1), B_w1, B_b1, B_w2, B_b2)
    x = x + _A_ref(_layernorm(x, axis=-1), A_wqkv, A_wo)
    x = x + _B_ref(_layernorm(x, axis=-1), B_w1, B_b1, B_w2, B_b2)
    return x
```

```cpp
#include <cuda_runtime.h>
#include <cuda_bf16.h>
#include <cuda.h>
#include <stdint.h>

namespace {

constexpr int S_ = 2048, D_ = 1024, F_ = 3584;
constexpr int NST = 5;
constexpr int A_BYTES = 16384, ST_BYTES = 40960;
constexpr int OFF_STG = NST * ST_BYTES;
constexpr int OFF_CSQ = OFF_STG + 16384;
constexpr int OFF_UP  = OFF_CSQ + 1536;
constexpr int OFF_B2  = OFF_UP + 3584;
constexpr int OFF_RST = OFF_B2 + 512;
constexpr int OFF_BAR = OFF_RST + 1024;
constexpr int OFF_EPO = OFF_BAR + 128;
constexpr int SMEM_BYTES = OFF_EPO + 16 + 1024;
constexpr int KB_LAYER = 6 * 16 + 56;

constexpr int FK_TILE = 0;
constexpr int FK_STAT = 14;
constexpr int FK_HALO = 18;
constexpr int FK_CS   = 22;
constexpr int NFK = 23;

struct Params {
  CUtensorMap ld_x, ld_act, ld_h, st_act, st_h, st_out, w_qkv, w_o, w_1a, w_1b, w_2;
  const __nv_bfloat16 *x, *wqkv, *wo, *w1, *b1, *w2, *b2;
};

__device__ __align__(1024) __nv_bfloat16 g_act[3 * S_ * D_];
__device__ __align__(1024) __nv_bfloat16 g_h[S_ * F_];
__device__ __align__(128) float2 g_stats[4 * S_ * 8];
__device__ __align__(128) float g_cs[2 * (3 * D_ + F_)];
__device__ __align__(128) uint4 g_halo[4 * 16 * 8 * 256];
__device__ __align__(128) unsigned g_flags[NFK * 16 * 32];
__device__ unsigned g_epoch[128];
#define TL(t, e)
#define TLW(t, e)

template<int N> __device__ __forceinline__ void wgmma_ss(float (&d)[N/2], uint64_t da, uint64_t db, int sd);
template<> __device__ __forceinline__ void wgmma_ss<128>(float (&d)[64], uint64_t da, uint64_t db, int sd) {
  asm volatile("{\n.reg .pred p;\nsetp.ne.b32 p, %66, 0;\n"
    "wgmma.mma_async.sync.aligned.m64n128k16.f32.bf16.bf16 {%0, %1, %2, %3, %4, %5, %6, %7, %8, %9, %10, %11, %12, %13, %14, %15, %16, %17, %18, %19, %20, %21, %22, %23, %24, %25, %26, %27, %28, %29, %30, %31, %32, %33, %34, %35, %36, %37, %38, %39, %40, %41, %42, %43, %44, %45, %46, %47, %48, %49, %50, %51, %52, %53, %54, %55, %56, %57, %58, %59, %60, %61, %62, %63}, %64, %65, p, 1, 1, 0, 1;\n}\n"
    : "+f"(d[0]), "+f"(d[1]), "+f"(d[2]), "+f"(d[3]), "+f"(d[4]), "+f"(d[5]), "+f"(d[6]), "+f"(d[7]), "+f"(d[8]), "+f"(d[9]), "+f"(d[10]), "+f"(d[11]), "+f"(d[12]), "+f"(d[13]), "+f"(d[14]), "+f"(d[15]), "+f"(d[16]), "+f"(d[17]), "+f"(d[18]), "+f"(d[19]), "+f"(d[20]), "+f"(d[21]), "+f"(d[22]), "+f"(d[23]), "+f"(d[24]), "+f"(d[25]), "+f"(d[26]), "+f"(d[27]), "+f"(d[28]), "+f"(d[29]), "+f"(d[30]), "+f"(d[31]), "+f"(d[32]), "+f"(d[33]), "+f"(d[34]), "+f"(d[35]), "+f"(d[36]), "+f"(d[37]), "+f"(d[38]), "+f"(d[39]), "+f"(d[40]), "+f"(d[41]), "+f"(d[42]), "+f"(d[43]), "+f"(d[44]), "+f"(d[45]), "+f"(d[46]), "+f"(d[47]), "+f"(d[48]), "+f"(d[49]), "+f"(d[50]), "+f"(d[51]), "+f"(d[52]), "+f"(d[53]), "+f"(d[54]), "+f"(d[55]), "+f"(d[56]), "+f"(d[57]), "+f"(d[58]), "+f"(d[59]), "+f"(d[60]), "+f"(d[61]), "+f"(d[62]), "+f"(d[63])
    : "l"(da), "l"(db), "r"(sd));
}

template<> __device__ __forceinline__ void wgmma_ss<192>(float (&d)[96], uint64_t da, uint64_t db, int sd) {
  asm volatile("{\n.reg .pred p;\nsetp.ne.b32 p, %98, 0;\n"
    "wgmma.mma_async.sync.aligned.m64n192k16.f32.bf16.bf16 {%0, %1, %2, %3, %4, %5, %6, %7, %8, %9, %10, %11, %12, %13, %14, %15, %16, %17, %18, %19, %20, %21, %22, %23, %24, %25, %26, %27, %28, %29, %30, %31, %32, %33, %34, %35, %36, %37, %38, %39, %40, %41, %42, %43, %44, %45, %46, %47, %48, %49, %50, %51, %52, %53, %54, %55, %56, %57, %58, %59, %60, %61, %62, %63, %64, %65, %66, %67, %68, %69, %70, %71, %72, %73, %74, %75, %76, %77, %78, %79, %80, %81, %82, %83, %84, %85, %86, %87, %88, %89, %90, %91, %92, %93, %94, %95}, %96, %97, p, 1, 1, 0, 1;\n}\n"
    : "+f"(d[0]), "+f"(d[1]), "+f"(d[2]), "+f"(d[3]), "+f"(d[4]), "+f"(d[5]), "+f"(d[6]), "+f"(d[7]), "+f"(d[8]), "+f"(d[9]), "+f"(d[10]), "+f"(d[11]), "+f"(d[12]), "+f"(d[13]), "+f"(d[14]), "+f"(d[15]), "+f"(d[16]), "+f"(d[17]), "+f"(d[18]), "+f"(d[19]), "+f"(d[20]), "+f"(d[21]), "+f"(d[22]), "+f"(d[23]), "+f"(d[24]), "+f"(d[25]), "+f"(d[26]), "+f"(d[27]), "+f"(d[28]), "+f"(d[29]), "+f"(d[30]), "+f"(d[31]), "+f"(d[32]), "+f"(d[33]), "+f"(d[34]), "+f"(d[35]), "+f"(d[36]), "+f"(d[37]), "+f"(d[38]), "+f"(d[39]), "+f"(d[40]), "+f"(d[41]), "+f"(d[42]), "+f"(d[43]), "+f"(d[44]), "+f"(d[45]), "+f"(d[46]), "+f"(d[47]), "+f"(d[48]), "+f"(d[49]), "+f"(d[50]), "+f"(d[51]), "+f"(d[52]), "+f"(d[53]), "+f"(d[54]), "+f"(d[55]), "+f"(d[56]), "+f"(d[57]), "+f"(d[58]), "+f"(d[59]), "+f"(d[60]), "+f"(d[61]), "+f"(d[62]), "+f"(d[63]), "+f"(d[64]), "+f"(d[65]), "+f"(d[66]), "+f"(d[67]), "+f"(d[68]), "+f"(d[69]), "+f"(d[70]), "+f"(d[71]), "+f"(d[72]), "+f"(d[73]), "+f"(d[74]), "+f"(d[75]), "+f"(d[76]), "+f"(d[77]), "+f"(d[78]), "+f"(d[79]), "+f"(d[80]), "+f"(d[81]), "+f"(d[82]), "+f"(d[83]), "+f"(d[84]), "+f"(d[85]), "+f"(d[86]), "+f"(d[87]), "+f"(d[88]), "+f"(d[89]), "+f"(d[90]), "+f"(d[91]), "+f"(d[92]), "+f"(d[93]), "+f"(d[94]), "+f"(d[95])
    : "l"(da), "l"(db), "r"(sd));
}

__device__ __forceinline__ uint32_t smem_u32(const void* p) { return (uint32_t)__cvta_generic_to_shared(p); }
__device__ __forceinline__ void mbar_init(uint32_t bar, uint32_t cnt) { asm volatile("mbarrier.init.shared::cta.b64 [%0], %1;" :: "r"(bar), "r"(cnt)); }
__device__ __forceinline__ void mbar_expect_tx(uint32_t bar, uint32_t bytes) { asm volatile("mbarrier.arrive.expect_tx.shared::cta.b64 _, [%0], %1;" :: "r"(bar), "r"(bytes) : "memory"); }
__device__ __forceinline__ void mbar_arrive(uint32_t bar) { asm volatile("mbarrier.arrive.shared::cta.b64 _, [%0];" :: "r"(bar) : "memory"); }
__device__ __forceinline__ void mbar_wait(uint32_t bar, uint32_t parity) {
  asm volatile(
    "{\n.reg .pred p;\n.reg .u32 n;\n"
    "mbarrier.try_wait.parity.shared::cta.b64 p, [%0], %1;\n"
    "@p bra.uni WAIT_DONE;\n"
    "mov.u32 n, 0;\n"
    "WAIT_LOOP:\n"
    "mbarrier.try_wait.parity.shared::cta.b64 p, [%0], %1;\n"
    "@p bra.uni WAIT_DONE;\n"
    "add.u32 n, n, 1;\n"
    "setp.lt.u32 p, n, 0x4000000;\n"
    "@p bra.uni WAIT_LOOP;\n"
    "trap;\n"
    "WAIT_DONE:\n}" :: "r"(bar), "r"(parity) : "memory");
}
__device__ __forceinline__ void tma_ld2(uint32_t dst, const CUtensorMap* m, uint32_t bar, int c0, int c1) {
  asm volatile("cp.async.bulk.tensor.2d.shared::cluster.global.mbarrier::complete_tx::bytes [%0], [%1, {%3, %4}], [%2];"
    :: "r"(dst), "l"(m), "r"(bar), "r"(c0), "r"(c1) : "memory");
}
__device__ __forceinline__ void tma_ld3(uint32_t dst, const CUtensorMap* m, uint32_t bar, int c0, int c1, int c2) {
  asm volatile("cp.async.bulk.tensor.3d.shared::cluster.global.mbarrier::complete_tx::bytes [%0], [%1, {%3, %4, %5}], [%2];"
    :: "r"(dst), "l"(m), "r"(bar), "r"(c0), "r"(c1), "r"(c2) : "memory");
}
__device__ __forceinline__ void tma_st2(const CUtensorMap* m, uint32_t src, int c0, int c1) {
  asm volatile("cp.async.bulk.tensor.2d.global.shared::cta.bulk_group [%0, {%2, %3}], [%1];"
    :: "l"(m), "r"(src), "r"(c0), "r"(c1) : "memory");
}
__device__ __forceinline__ void bulk_commit() { asm volatile("cp.async.bulk.commit_group;" ::: "memory"); }
__device__ __forceinline__ void bulk_wait_all() { asm volatile("cp.async.bulk.wait_group 0;" ::: "memory"); }
__device__ __forceinline__ void bulk_wait_read() { asm volatile("cp.async.bulk.wait_group.read 0;" ::: "memory"); }
__device__ __forceinline__ void fence_async_smem() { asm volatile("fence.proxy.async.shared::cta;" ::: "memory"); }
__device__ __forceinline__ void fence_async_all() { asm volatile("fence.proxy.async;" ::: "memory"); }
__device__ __forceinline__ void wgmma_fence() { asm volatile("wgmma.fence.sync.aligned;" ::: "memory"); }
__device__ __forceinline__ void wgmma_commit() { asm volatile("wgmma.commit_group.sync.aligned;" ::: "memory"); }
template<int N> __device__ __forceinline__ void wgmma_wait() { asm volatile("wgmma.wait_group.sync.aligned %0;" :: "n"(N) : "memory"); }
__device__ __forceinline__ void bar_sync(int id, int n) { asm volatile("bar.sync %0, %1;" :: "r"(id), "r"(n) : "memory"); }
__device__ __forceinline__ unsigned ld_acquire(const unsigned* p) { unsigned v; asm volatile("ld.acquire.gpu.global.u32 %0, [%1];" : "=r"(v) : "l"(p) : "memory"); return v; }
__device__ __forceinline__ void red_release(unsigned* p) { asm volatile("red.release.gpu.global.add.u32 [%0], 1;" :: "l"(p) : "memory"); }
__device__ __forceinline__ uint32_t pack_bf16(float lo, float hi) { uint32_t r; asm("cvt.rn.bf16x2.f32 %0, %1, %2;" : "=r"(r) : "f"(hi), "f"(lo)); return r; }
__device__ __forceinline__ float bf_lo(uint32_t u) { return __uint_as_float(u << 16); }
__device__ __forceinline__ float bf_hi(uint32_t u) { return __uint_as_float(u & 0xffff0000u); }
__device__ __forceinline__ void stmatrix4(uint32_t addr, uint32_t r0, uint32_t r1, uint32_t r2, uint32_t r3) {
  asm volatile("stmatrix.sync.aligned.m8n8.x4.shared.b16 [%0], {%1, %2, %3, %4};" :: "r"(addr), "r"(r0), "r"(r1), "r"(r2), "r"(r3) : "memory");
}
__device__ __forceinline__ uint32_t movmatrix(uint32_t a) { uint32_t d; asm volatile("movmatrix.sync.aligned.m8n8.trans.b16 %0, %1;" : "=r"(d) : "r"(a)); return d; }
__device__ __forceinline__ void mma16816(float (&c)[4], uint32_t a0, uint32_t a1, uint32_t a2, uint32_t a3, uint32_t b0, uint32_t b1) {
  asm volatile("mma.sync.aligned.m16n8k16.row.col.f32.bf16.bf16.f32 {%0,%1,%2,%3}, {%4,%5,%6,%7}, {%8,%9}, {%0,%1,%2,%3};"
    : "+f"(c[0]), "+f"(c[1]), "+f"(c[2]), "+f"(c[3]) : "r"(a0), "r"(a1), "r"(a2), "r"(a3), "r"(b0), "r"(b1));
}
__device__ __forceinline__ void sts128(uint32_t a, uint32_t x, uint32_t y, uint32_t z, uint32_t w) { asm volatile("st.shared.v4.b32 [%0], {%1,%2,%3,%4};" :: "r"(a), "r"(x), "r"(y), "r"(z), "r"(w) : "memory"); }
__device__ __forceinline__ uint4 lds128(uint32_t a) { uint4 v; asm volatile("ld.shared.v4.b32 {%0,%1,%2,%3}, [%4];" : "=r"(v.x), "=r"(v.y), "=r"(v.z), "=r"(v.w) : "r"(a) : "memory"); return v; }
__device__ __forceinline__ float2 lds64f(uint32_t a) { float2 v; asm volatile("ld.shared.v2.f32 {%0,%1}, [%2];" : "=f"(v.x), "=f"(v.y) : "r"(a) : "memory"); return v; }
__device__ __forceinline__ float4 lds128f(uint32_t a) { float4 v; asm volatile("ld.shared.v4.f32 {%0,%1,%2,%3}, [%4];" : "=f"(v.x), "=f"(v.y), "=f"(v.z), "=f"(v.w) : "r"(a) : "memory"); return v; }
__device__ __forceinline__ void sts32f(uint32_t a, float v) { asm volatile("st.shared.f32 [%0], %1;" :: "r"(a), "f"(v) : "memory"); }
__device__ __forceinline__ void sts64f(uint32_t a, float x, float y) { asm volatile("st.shared.v2.f32 [%0], {%1,%2};" :: "r"(a), "f"(x), "f"(y) : "memory"); }
__device__ __forceinline__ float lds32f(uint32_t a) { float v; asm volatile("ld.shared.f32 %0, [%1];" : "=f"(v) : "r"(a) : "memory"); return v; }
template<int R> __device__ __forceinline__ void reg_alloc() { asm volatile("setmaxnreg.inc.sync.aligned.u32 %0;" :: "n"(R)); }
template<int R> __device__ __forceinline__ void reg_dealloc() { asm volatile("setmaxnreg.dec.sync.aligned.u32 %0;" :: "n"(R)); }

__device__ __forceinline__ unsigned* flag_ptr(int kind, int m) { return g_flags + (kind * 16 + m) * 32; }

__device__ __forceinline__ void warp_wait_flags(const unsigned* p, int n, unsigned target, int lane) {
  for (unsigned it = 0;; it++) {
    unsigned v = lane < n ? ld_acquire(p + lane) : target;
    if (__all_sync(0xffffffffu, (int)(v - target) >= 0)) break;
    if (it > 0x1000000u) __trap();
  }
  __syncwarp();
}

__device__ __forceinline__ int kb_of(int step, bool own_first, int j) {
  if (!own_first) return step;
  if (step < 2) return 2 * j + step;
  return (step - 2 < 2 * j) ? step - 2 : step;
}

struct Ctx {
  uint32_t sb;
  int m, j, wg, w, lane;
  unsigned epoch;
};

template<int BN, bool ZERO>
__device__ __forceinline__ void mainloop(const Ctx& c, float (&acc)[2][BN / 2], int t, int nkb) {
  int g0 = (t >= 7 ? KB_LAYER + (t - 7) * 16 : t * 16);
  int s = g0 % NST;
  uint32_t ph = (g0 / NST) & 1;
  const uint32_t full0 = c.sb + OFF_BAR, empty0 = full0 + 8 * NST;
  if (ZERO) {
#pragma unroll
    for (int i = 0; i < BN / 2; i++) { acc[0][i] = 0.f; acc[1][i] = 0.f; }
  }
  TL(t, 0);
  if (t > 0) bar_sync(1, 256);
  TL(t, 1);
  int prev = 0;
  for (int kb = 0; kb < nkb; kb++) {
    mbar_wait(full0 + 8 * s, ph);
    const uint32_t a = c.sb + s * ST_BYTES;
    const uint64_t da = (uint64_t)((a >> 4) | (1u << 16)) | ((uint64_t)(128u | (1u << 30)) << 32);
    const uint64_t db = (uint64_t)(((a + A_BYTES) >> 4) | (512u << 16)) | ((uint64_t)(64u | (1u << 30)) << 32);
    wgmma_fence();
#pragma unroll
    for (int k = 0; k < 4; k++) {
#pragma unroll
      for (int i = 0; i < 2; i++)
        wgmma_ss<BN>(acc[i], da + (i * 64 + k * 2), db + k * 128, 1);
    }
    wgmma_commit();
    if (kb == nkb - 1 && t < 13) bar_sync(1, 256);
    wgmma_wait<1>();
    if (kb > 0 && c.lane == 0) mbar_arrive(empty0 + 8 * prev);
    prev = s;
    if (++s == NST) { s = 0; ph ^= 1; }
  }
  wgmma_wait<0>();
  if (c.lane == 0) mbar_arrive(empty0 + 8 * prev);
  TL(t, 3);
}

__device__ __forceinline__ void load_row_stats(const Ctx& c, int ln) {
  warp_wait_flags(flag_ptr(FK_STAT + ln, c.m), 8, 4 * (c.epoch + 1), c.lane);
  const float4* p = reinterpret_cast<const float4*>(g_stats + ((size_t)ln * S_ + c.m * 128 + c.w * 32 + c.lane) * 8);
  float4 v0 = __ldcg(p), v1 = __ldcg(p + 1), v2 = __ldcg(p + 2), v3 = __ldcg(p + 3);
  float s = ((v0.x + v0.z) + (v1.x + v1.z)) + ((v2.x + v2.z) + (v3.x + v3.z));
  float q = ((v0.y + v0.w) + (v1.y + v1.w)) + ((v2.y + v2.w) + (v3.y + v3.w));
  float mean = s * (1.0f / D_);
  float var = fmaxf(q * (1.0f / D_) - mean * mean, 0.0f);
  sts64f(c.sb + OFF_RST + (c.w * 32 + c.lane) * 8, mean, rsqrtf(var + 1e-5f));
  __syncwarp();
}

__device__ __forceinline__ void attn16(const uint32_t (&qa)[4], const uint32_t (&qb)[4],
    const uint32_t (&k0a)[4], const uint32_t (&k0b)[4], const uint32_t (&k1a)[4], const uint32_t (&k1b)[4],
    const uint32_t (&v0a)[4], const uint32_t (&v0b)[4], const uint32_t (&v1a)[4], const uint32_t (&v1b)[4],
    uint32_t (&oa)[4], uint32_t (&ob)[4], int lane, bool nohalo) {
  float s0[4] = {0, 0, 0, 0}, s1[4] = {0, 0, 0, 0}, s2[4] = {0, 0, 0, 0}, s3[4] = {0, 0, 0, 0};
#pragma unroll
  for (int t = 0; t < 2; t++) {
    mma16816(s0, qa[2 * t], qb[2 * t], qa[2 * t + 1], qb[2 * t + 1], k0a[2 * t], k0a[2 * t + 1]);
    mma16816(s1, qa[2 * t], qb[2 * t], qa[2 * t + 1], qb[2 * t + 1], k0b[2 * t], k0b[2 * t + 1]);
    mma16816(s2, qa[2 * t], qb[2 * t], qa[2 * t + 1], qb[2 * t + 1], k1a[2 * t], k1a[2 * t + 1]);
    mma16816(s3, qa[2 * t], qb[2 * t], qa[2 * t + 1], qb[2 * t + 1], k1b[2 * t], k1b[2 * t + 1]);
  }
  const int g = lane >> 2, cc = lane & 3;
  const bool odd = g & 1, far = cc > (g >> 1);
  float m0 = odd ? s1[1] : s1[0];
  float a0 = far ? (odd ? s0[1] : s0[0]) : (odd ? s2[1] : s2[0]);
  float m1 = odd ? s2[3] : s2[2];
  float a1 = far ? (odd ? s1[3] : s1[2]) : (odd ? s3[3] : s3[2]);
  const float sc = 0.17677669529663687f * 1.4426950408889634f;
  m0 *= sc; a0 *= sc; m1 *= sc; a1 *= sc;
  if (nohalo) { const float neg = -1e9f * 1.4426950408889634f; m0 = neg; if (far) { a0 = neg; a1 = neg; } }
  float x0 = fmaxf(m0, a0), x1 = fmaxf(m1, a1);
  x0 = fmaxf(x0, __shfl_xor_sync(0xffffffffu, x0, 1)); x1 = fmaxf(x1, __shfl_xor_sync(0xffffffffu, x1, 1));
  x0 = fmaxf(x0, __shfl_xor_sync(0xffffffffu, x0, 2)); x1 = fmaxf(x1, __shfl_xor_sync(0xffffffffu, x1, 2));
  m0 = exp2f(m0 - x0); a0 = exp2f(a0 - x0); m1 = exp2f(m1 - x1); a1 = exp2f(a1 - x1);
  float t0 = m0 + a0, t1 = m1 + a1;
  t0 += __shfl_xor_sync(0xffffffffu, t0, 1); t1 += __shfl_xor_sync(0xffffffffu, t1, 1);
  t0 += __shfl_xor_sync(0xffffffffu, t0, 2); t1 += __shfl_xor_sync(0xffffffffu, t1, 2);
  t0 = __frcp_rn(t0); t1 = __frcp_rn(t1);
  const int sh = odd ? 16 : 0;
  const uint32_t pm0 = pack_bf16(m0 * t0, 0.f) << sh, pa0 = pack_bf16(a0 * t0, 0.f) << sh;
  const uint32_t pm1 = pack_bf16(m1 * t1, 0.f) << sh, pa1 = pack_bf16(a1 * t1, 0.f) << sh;
  const uint32_t f0 = far ? pa0 : 0u, n0 = far ? 0u : pa0, f1 = far ? pa1 : 0u, n1 = far ? 0u : pa1;
#pragma unroll
  for (int dt = 0; dt < 4; dt++) {
    float o[4] = {0, 0, 0, 0};
    mma16816(o, f0, 0u, pm0, f1, v0a[dt], v0b[dt]);
    mma16816(o, n0, pm1, 0u, n1, v1a[dt], v1b[dt]);
    oa[dt] = pack_bf16(o[0], o[1]);
    ob[dt] = pack_bf16(o[2], o[3]);
  }
}

__device__ __forceinline__ void tile_qkv(const Ctx& c, const Params& p, int t) {
  const int layer = t >= 7, q = t - layer * 7;
  float acc[2][96];
  mainloop<192, true>(c, acc, t, 16);
  const int lane = c.lane, w = c.w, g = lane >> 2, cc = lane & 3;
  if (q == 0) {
    load_row_stats(c, layer * 2);
    if (layer == 0) {
      warp_wait_flags(flag_ptr(FK_CS, 0), 1, 96 * (c.epoch + 1), lane);
#pragma unroll
      for (int r = 0; r < 3; r++) {
        int i = r * 128 + w * 32 + lane;
        int qq = i / 192, rem = i - qq * 192;
        int col = (rem >> 6) * D_ + (c.j + 8 * qq) * 64 + (rem & 63);
        sts32f(c.sb + OFF_CSQ + i * 4, __ldcg(g_cs + col) + __ldcg(g_cs + (3 * D_ + F_) + col));
      }
      bar_sync(2 + c.wg, 128);
    }
  }
  float2 rs[4];
#pragma unroll
  for (int r = 0; r < 4; r++) rs[r] = lds64f(c.sb + OFF_RST + (w * 32 + 8 * r + g) * 8);
  uint32_t P[3][2][4][4];
  const uint32_t csb = c.sb + OFF_CSQ + q * 768 + cc * 8;
#pragma unroll
  for (int nn = 0; nn < 24; nn++) {
    const int nt = (nn + 8) % 24;
    const float2 cs = lds64f(csb + nt * 32);
#pragma unroll
    for (int r = 0; r < 4; r++) {
      const int i = r & 1, h = r >> 1;
      float v0 = fmaf(-rs[r].x, cs.x, acc[i][4 * nt + 2 * h]) * rs[r].y;
      float v1 = fmaf(-rs[r].x, cs.y, acc[i][4 * nt + 2 * h + 1]) * rs[r].y;
      uint32_t u = pack_bf16(v0, v1);
      if (nt >= 16) u = movmatrix(u);
      P[nt >> 3][(nt >> 2) & 1][r][nt & 3] = u;
    }
    if (nn == 15) {
      if (w < 3) {
        const uint32_t dst = c.sb + OFF_STG + (w + 1) * 4096 + lane * 16;
#pragma unroll
        for (int z = 0; z < 8; z++) { const uint32_t* u = P[1 + (z >> 2)][(z >> 1) & 1][2 + (z & 1)]; sts128(dst + z * 512, u[0], u[1], u[2], u[3]); }
      } else if (c.m < 15) {
        uint4* dst = g_halo + (((layer * 2 + q) * 16 + c.m) * 8 + c.j) * 256 + lane;
#pragma unroll
        for (int z = 0; z < 8; z++) { const uint32_t* u = P[1 + (z >> 2)][(z >> 1) & 1][2 + (z & 1)]; __stcg(dst + z * 32, make_uint4(u[0], u[1], u[2], u[3])); }
        __syncwarp();
        if (lane == 0) red_release(flag_ptr(FK_HALO + layer * 2 + q, c.m) + c.j);
      }
    }
  }
  uint32_t O[2][4][4];
#pragma unroll
  for (int hh = 0; hh < 2; hh++)
    attn16(P[0][hh][2], P[0][hh][3], P[1][hh][0], P[1][hh][1], P[1][hh][2], P[1][hh][3],
           P[2][hh][0], P[2][hh][1], P[2][hh][2], P[2][hh][3], O[hh][2], O[hh][3], lane, false);
  bar_sync(2 + c.wg, 128);
  uint32_t H[2][2][2][4];
  const bool nohalo = (w == 0 && c.m == 0);
  if (w > 0) {
    const uint32_t src = c.sb + OFF_STG + w * 4096 + lane * 16;
#pragma unroll
    for (int z = 0; z < 8; z++) { uint4 v = lds128(src + z * 512); uint32_t* u = H[z >> 2][(z >> 1) & 1][z & 1]; u[0] = v.x; u[1] = v.y; u[2] = v.z; u[3] = v.w; }
  } else if (!nohalo) {
    warp_wait_flags(flag_ptr(FK_HALO + layer * 2 + q, c.m - 1) + c.j, 1, c.epoch + 1, lane);
    const uint4* src = g_halo + (((layer * 2 + q) * 16 + c.m - 1) * 8 + c.j) * 256 + lane;
#pragma unroll
    for (int z = 0; z < 8; z++) { uint4 v = __ldcg(src + z * 32); uint32_t* u = H[z >> 2][(z >> 1) & 1][z & 1]; u[0] = v.x; u[1] = v.y; u[2] = v.z; u[3] = v.w; }
  } else {
#pragma unroll
    for (int z = 0; z < 8; z++) { uint32_t* u = H[z >> 2][(z >> 1) & 1][z & 1]; u[0] = u[1] = u[2] = u[3] = 0u; }
  }
#pragma unroll
  for (int hh = 0; hh < 2; hh++)
    attn16(P[0][hh][0], P[0][hh][1], H[0][hh][0], H[0][hh][1], P[1][hh][0], P[1][hh][1],
           H[1][hh][0], H[1][hh][1], P[2][hh][0], P[2][hh][1], O[hh][0], O[hh][1], lane, nohalo);
  __syncwarp();
  const uint32_t stg = c.sb + OFF_STG + w * 4096;
#pragma unroll
  for (int nt = 0; nt < 8; nt++)
    stmatrix4(stg + lane * 128 + ((nt ^ (lane & 7)) << 4), O[nt >> 2][0][nt & 3], O[nt >> 2][1][nt & 3], O[nt >> 2][2][nt & 3], O[nt >> 2][3][nt & 3]);
  fence_async_smem();
  __syncwarp();
  TL(t, 4);
  if (lane == 0) {
    tma_st2(&p.st_act, stg, (c.j + 8 * q) * 64, 2 * S_ + c.m * 128 + w * 32);
    bulk_commit();
    bulk_wait_all();
    red_release(flag_ptr(FK_TILE + t, c.m) + c.j);
  }
  __syncwarp();
  TL(t, 5);
  if (t == 0) {
    warp_wait_flags(flag_ptr(FK_CS, 1), 1, 112 * (c.epoch + 1), lane);
    for (int i = w * 32 + lane; i < 448; i += 128) {
      int col = i < 192 ? c.j * 192 + i : (i < 320 ? 1536 + c.j * 128 + (i - 192) : 2560 + c.j * 128 + (i - 320));
      uint32_t a = c.sb + OFF_UP + (i >> 1) * 16 + (i & 1) * 4;
      sts32f(a, __ldcg(g_cs + 3 * D_ + col) + __ldcg(g_cs + (3 * D_ + F_) + 3 * D_ + col));
      sts32f(a + 8, __bfloat162float(p.b1[col]));
    }
    sts32f(c.sb + OFF_B2 + (w * 32 + lane) * 4, __bfloat162float(p.b2[c.j * 128 + w * 32 + lane]));
  }
}

template<int BN>
__device__ __forceinline__ void tile_up(const Ctx& c, const Params& p, int t) {
  const int layer = t >= 7, type = t - layer * 7;
  float acc[2][BN / 2];
  mainloop<BN, true>(c, acc, t, 16);
  const int lane = c.lane, w = c.w, g = lane >> 2, cc = lane & 3;
  if (BN == 192) load_row_stats(c, layer * 2 + 1);
  float2 rs[4];
#pragma unroll
  for (int r = 0; r < 4; r++) rs[r] = lds64f(c.sb + OFF_RST + (w * 32 + 8 * r + g) * 8);
  const int loc0 = BN == 192 ? 0 : (type == 4 ? 192 : 320);
  const int col0 = BN == 192 ? c.j * 192 : (type == 4 ? 1536 : 2560) + c.j * 128;
  const uint32_t cb = c.sb + OFF_UP + loc0 * 8 + cc * 16;
  const uint32_t stg = c.sb + OFF_STG + w * 4096;
#pragma unroll
  for (int ch = 0; ch < BN / 64; ch++) {
    uint32_t P[8][4];
#pragma unroll
    for (int n8 = 0; n8 < 8; n8++) {
      const int nt = ch * 8 + n8;
      const float4 cv = lds128f(cb + nt * 64);
#pragma unroll
      for (int r = 0; r < 4; r++) {
        const int i = r & 1, h = r >> 1;
        float v0 = fmaxf(fmaf(fmaf(-rs[r].x, cv.x, acc[i][4 * nt + 2 * h]), rs[r].y, cv.z), 0.f);
        float v1 = fmaxf(fmaf(fmaf(-rs[r].x, cv.y, acc[i][4 * nt + 2 * h + 1]), rs[r].y, cv.w), 0.f);
        P[n8][r] = pack_bf16(v0 * v0, v1 * v1);
      }
    }
    if (ch > 0) { if (lane == 0) bulk_wait_read(); __syncwarp(); }
#pragma unroll
    for (int n8 = 0; n8 < 8; n8++)
      stmatrix4(stg + lane * 128 + ((n8 ^ (lane & 7)) << 4), P[n8][0], P[n8][1], P[n8][2], P[n8][3]);
    fence_async_smem();
    __syncwarp();
    if (lane == 0) { tma_st2(&p.st_h, stg, col0 + ch * 64, c.m * 128 + w * 32); bulk_commit(); }
  }
  TL(t, 4);
  if (lane == 0) { bulk_wait_all(); red_release(flag_ptr(FK_TILE + t, c.m) + c.j); }
  __syncwarp();
  TL(t, 5);
}

__device__ __forceinline__ void tile_res(const Ctx& c, const Params& p, int t) {
  const int layer = t >= 7, type = t - layer * 7;
  const bool isD = type == 6;
  const int lane = c.lane, w = c.w, g = lane >> 2, cc = lane & 3;
  float acc[2][64];
  {
    const __nv_bfloat16* src = isD ? g_act : (layer ? g_act + S_ * D_ : p.x);
    const uint32_t* r0 = reinterpret_cast<const uint32_t*>(src + (size_t)(c.m * 128 + w * 32 + g) * D_ + c.j * 128 + cc * 2);
    uint32_t u[4][16];
#pragma unroll
    for (int r = 0; r < 4; r++)
#pragma unroll
      for (int nt = 0; nt < 16; nt++) u[r][nt] = __ldcg(r0 + r * 8 * (D_ / 2) + nt * 4);
#pragma unroll
    for (int nt = 0; nt < 16; nt++) {
      float2 b = make_float2(0.f, 0.f);
      if (isD) b = lds64f(c.sb + OFF_B2 + nt * 32 + cc * 8);
#pragma unroll
      for (int r = 0; r < 4; r++) {
        acc[r & 1][4 * nt + 2 * (r >> 1)] = bf_lo(u[r][nt]) + b.x;
        acc[r & 1][4 * nt + 2 * (r >> 1) + 1] = bf_hi(u[r][nt]) + b.y;
      }
    }
  }
  const int nkb = isD ? 56 : 16;
  mainloop<128, false>(c, acc, t, nkb);
  const int g1 = (layer ? KB_LAYER : 0) + type * 16 + nkb;
  const int s0 = g1 % NST, s1 = (g1 + 1) % NST;
  const uint32_t d0 = c.sb + s0 * ST_BYTES + w * 4096, d1 = c.sb + s1 * ST_BYTES + w * 4096;
  uint32_t P[16][4];
#pragma unroll
  for (int nt = 0; nt < 16; nt++) {
#pragma unroll
    for (int r = 0; r < 4; r++) P[nt][r] = pack_bf16(acc[r & 1][4 * nt + 2 * (r >> 1)], acc[r & 1][4 * nt + 2 * (r >> 1) + 1]);
    stmatrix4((nt < 8 ? d0 : d1) + lane * 128 + (((nt & 7) ^ (lane & 7)) << 4), P[nt][0], P[nt][1], P[nt][2], P[nt][3]);
  }
  fence_async_smem();
  __syncwarp();
  if (lane == 0) {
    const CUtensorMap* mp = t == 13 ? &p.st_out : &p.st_act;
    const int row = (t == 6 ? S_ : 0) + c.m * 128 + w * 32;
    tma_st2(mp, d0, c.j * 128, row);
    tma_st2(mp, d1, c.j * 128 + 64, row);
    bulk_commit();
  }
  if (t == 13) { if (lane == 0) bulk_wait_all(); TL(t, 5); return; }
  bar_sync(2 + c.wg, 128);
  if (w == 0 && lane == 0) { mbar_arrive(c.sb + OFF_BAR + 8 * s0); mbar_arrive(c.sb + OFF_BAR + 8 * s1); }
  TL(t, 4);
  float sm[4], sq[4];
#pragma unroll
  for (int r = 0; r < 4; r++) {
    float a = 0.f, b = 0.f;
#pragma unroll
    for (int nt = 0; nt < 16; nt++) { float x = bf_lo(P[nt][r]), y = bf_hi(P[nt][r]); a += x + y; b = fmaf(x, x, fmaf(y, y, b)); }
    a += __shfl_xor_sync(0xffffffffu, a, 1); b += __shfl_xor_sync(0xffffffffu, b, 1);
    a += __shfl_xor_sync(0xffffffffu, a, 2); b += __shfl_xor_sync(0xffffffffu, b, 2);
    sm[r] = a; sq[r] = b;
  }
  if (lane == 0) { bulk_wait_all(); red_release(flag_ptr(FK_TILE + t, c.m) + c.j); }
  TL(t, 5);
  const int ln = layer * 2 + (isD ? 2 : 1);
  const float a = cc == 0 ? sm[0] : cc == 1 ? sm[1] : cc == 2 ? sm[2] : sm[3];
  const float b = cc == 0 ? sq[0] : cc == 1 ? sq[1] : cc == 2 ? sq[2] : sq[3];
  __stcg(g_stats + ((size_t)ln * S_ + c.m * 128 + w * 32 + 8 * cc + g) * 8 + c.j, make_float2(a, b));
  __syncwarp();
  if (lane == 0) red_release(flag_ptr(FK_STAT + ln, c.m) + c.j);
}

__device__ __forceinline__ void colsum_piece(const Ctx& c, const __nv_bfloat16* W, int ldw, int piece, float* out, unsigned* flag) {
  const int tid = c.w * 32 + c.lane;
  const int chunk = piece >> 1, half = piece & 1;
  const uint4* src = reinterpret_cast<const uint4*>(W + (size_t)(half * 512 + (tid >> 3)) * ldw + chunk * 64 + (tid & 7) * 8);
  float a[8] = {0, 0, 0, 0, 0, 0, 0, 0};
  uint4 v[32];
#pragma unroll
  for (int i = 0; i < 32; i++) v[i] = __ldg(src + (size_t)i * 16 * (ldw / 8));
#pragma unroll
  for (int i = 0; i < 32; i++) {
    a[0] += bf_lo(v[i].x); a[1] += bf_hi(v[i].x); a[2] += bf_lo(v[i].y); a[3] += bf_hi(v[i].y);
    a[4] += bf_lo(v[i].z); a[5] += bf_hi(v[i].z); a[6] += bf_lo(v[i].w); a[7] += bf_hi(v[i].w);
  }
#pragma unroll
  for (int e = 0; e < 8; e++) { a[e] += __shfl_xor_sync(0xffffffffu, a[e], 8); a[e] += __shfl_xor_sync(0xffffffffu, a[e], 16); }
  const uint32_t red = c.sb + OFF_UP;
  if (c.lane < 8) {
#pragma unroll
    for (int e = 0; e < 8; e++) sts32f(red + (c.w * 64 + c.lane * 8 + e) * 4, a[e]);
  }
  bar_sync(2 + c.wg, 128);
  if (c.w == 0) {
#pragma unroll
    for (int r = 0; r < 2; r++) {
      const int col = r * 32 + c.lane;
      float s = (lds32f(red + col * 4) + lds32f(red + (64 + col) * 4)) + (lds32f(red + (128 + col) * 4) + lds32f(red + (192 + col) * 4));
      __stcg(out + half * (3 * D_ + F_) + chunk * 64 + col, s);
    }
    __syncwarp();
    if (c.lane == 0) red_release(flag);
  }
  bar_sync(2 + c.wg, 128);
}

__device__ __forceinline__ void prologue(const Ctx& c, const Params& p) {
  const int row0 = c.m * 128 + c.j * 16 + c.w * 4;
  uint4 v[4][4];
#pragma unroll
  for (int r = 0; r < 4; r++)
#pragma unroll
    for (int i = 0; i < 4; i++) v[r][i] = __ldg(reinterpret_cast<const uint4*>(p.x + (size_t)(row0 + r) * D_) + i * 32 + c.lane);
#pragma unroll
  for (int r = 0; r < 4; r++) {
    float a = 0.f, b = 0.f;
#pragma unroll
    for (int i = 0; i < 4; i++) {
      const uint32_t u[4] = {v[r][i].x, v[r][i].y, v[r][i].z, v[r][i].w};
#pragma unroll
      for (int e = 0; e < 4; e++) { float x = bf_lo(u[e]), y = bf_hi(u[e]); a += x + y; b = fmaf(x, x, fmaf(y, y, b)); }
    }
#pragma unroll
    for (int o = 1; o < 32; o <<= 1) { a += __shfl_xor_sync(0xffffffffu, a, o); b += __shfl_xor_sync(0xffffffffu, b, o); }
    if (c.lane < 8) __stcg(g_stats + (size_t)(row0 + r) * 8 + c.lane, c.lane == 0 ? make_float2(a, b) : make_float2(0.f, 0.f));
  }
  __syncwarp();
  if (c.lane == 0) red_release(flag_ptr(FK_STAT, c.m) + c.j);
  const int b = c.m * 8 + c.j;
  if (b < 96) colsum_piece(c, p.wqkv, 3 * D_, b, g_cs, flag_ptr(FK_CS, 0));
  if (b >= 16) colsum_piece(c, p.w1, F_, b - 16, g_cs + 3 * D_, flag_ptr(FK_CS, 1));
}

__global__ void __launch_bounds__(384, 1) fused_kernel(const __grid_constant__ Params p) {
  extern __shared__ uint8_t smem_raw[];
  Ctx c;
  c.sb = (smem_u32(smem_raw) + 1023) & ~1023u;
  const int tid = threadIdx.x;
  c.wg = tid >> 7; c.w = (tid >> 5) & 3; c.lane = tid & 31;
  c.m = blockIdx.x >> 3; c.j = blockIdx.x & 7;
  const uint32_t full0 = c.sb + OFF_BAR, empty0 = full0 + 8 * NST;
  c.epoch = __ldcg(g_epoch + blockIdx.x);
  if (tid == 0) {
    for (int s = 0; s < NST; s++) { mbar_init(full0 + 8 * s, 2); mbar_init(empty0 + 8 * s, 4); }
    asm volatile("fence.mbarrier_init.release.cluster;" ::: "memory");
  }
  __syncthreads();
  if (c.wg == 2) {
    reg_dealloc<40>();
    if (c.w == 0) {
      const unsigned target = 4 * (c.epoch + 1);
      int s = 0; uint32_t ph = 1;
      for (int t = 0; t < 14; t++) {
        const int layer = t >= 7, type = t - layer * 7;
        const CUtensorMap* mp = type == 6 ? &p.ld_h : (t < 2 ? &p.ld_x : &p.ld_act);
        const int row0 = c.m * 128 + (type == 2 ? 2 * S_ : (type < 2 && layer ? S_ : 0));
        const int nkb = type == 6 ? 56 : 16;
        const bool own = type == 3 || t == 7;
        int cur = -1; unsigned ready = 0;
        for (int step = 0; step < nkb; step++) {
          const int kb = kb_of(step, own, c.j);
          int kind = -1; unsigned need = 0;
          if (own) { if (step >= 2) { kind = t - 1; need = (1u << (kb >> 1)) | (step >= NST ? 1u << c.j : 0u); } }
          else if (type == 2) { kind = t - 2 + (kb >> 3); need = 1u << (kb & 7); }
          else if (type == 6) {
            if (kb < 24) { kind = t - 3; need = 1u << (kb / 3); }
            else { kind = t - 2 + (kb >= 40); need = 1u << (((kb - 24) >> 1) & 7); }
          }
          if (kind != cur) { cur = kind; ready = 0; }
          if ((ready & need) != need) {
            const unsigned* fp = flag_ptr(FK_TILE + kind, c.m);
            for (unsigned it = 0;; it++) {
              unsigned v = c.lane < 8 ? ld_acquire(fp + c.lane) : 0u;
              ready = __ballot_sync(0xffffffffu, c.lane < 8 && (int)(v - target) >= 0);
              if ((ready & need) == need) break;
              if (it > 0x1000000u) __trap();
            }
            __syncwarp();
            fence_async_all();
          }
          mbar_wait(empty0 + 8 * s, ph);
          if (c.lane == 0 && !(own && step < 2)) {
            mbar_expect_tx(full0 + 8 * s, A_BYTES);
            tma_ld2(c.sb + s * ST_BYTES, mp, full0 + 8 * s, kb * 64, row0);
          }
          if (++s == NST) { s = 0; ph ^= 1; }
        }
      }
    } else if (c.w == 1 && c.lane == 0) {
      int s = 0; uint32_t ph = 1;
      for (int t = 0; t < 14; t++) {
        const int layer = t >= 7, type = t - layer * 7;
        const CUtensorMap* mp = type < 2 ? &p.w_qkv : type == 2 ? &p.w_o : type == 3 ? &p.w_1a : type < 6 ? &p.w_1b : &p.w_2;
        const int c0 = type < 2 ? (c.j + 8 * type) * 64 : 0;
        const int c2 = type < 2 ? 0 : type == 3 ? 3 * c.j : type == 4 ? 24 + 2 * c.j : type == 5 ? 40 + 2 * c.j : 2 * c.j;
        const uint32_t bytes = (type < 2 || type == 3) ? 24576 : 16384;
        const int nkb = type == 6 ? 56 : 16;
        const bool own = type == 3 || t == 7;
        for (int step = 0; step < nkb; step++) {
          const int kb = kb_of(step, own, c.j);
          mbar_wait(empty0 + 8 * s, ph);
          mbar_expect_tx(full0 + 8 * s, bytes);
          tma_ld3(c.sb + s * ST_BYTES + A_BYTES, mp, full0 + 8 * s, c0, kb * 64, c2);
          if (++s == NST) { s = 0; ph ^= 1; }
        }
      }
    } else if (c.w == 2 && c.lane == 0) {
      g_epoch[blockIdx.x] = c.epoch + 1;
    }
  } else {
    reg_alloc<232>();
    if (c.wg == 1) prologue(c, p);
    for (int t = c.wg; t < 14; t += 2) {
      const int type = t >= 7 ? t - 7 : t;
      if (type < 2) tile_qkv(c, p, t);
      else if (type == 3) tile_up<192>(c, p, t);
      else if (type == 4 || type == 5) tile_up<128>(c, p, t);
      else tile_res(c, p, t);
    }
  }
}

typedef CUresult (*EncodeFn)(CUtensorMap*, CUtensorMapDataType, cuuint32_t, void*, const cuuint64_t*, const cuuint64_t*,
                             const cuuint32_t*, const cuuint32_t*, CUtensorMapInterleave, CUtensorMapSwizzle,
                             CUtensorMapL2promotion, CUtensorMapFloatOOBfill);

void make_map(EncodeFn fn, CUtensorMap* m, const void* ptr, int rank, const cuuint64_t* dims, const cuuint64_t* strides, const cuuint32_t* box) {
  const cuuint32_t es[3] = {1, 1, 1};
  fn(m, CU_TENSOR_MAP_DATA_TYPE_BFLOAT16, rank, const_cast<void*>(ptr), dims, strides, box, es, CU_TENSOR_MAP_INTERLEAVE_NONE,
     CU_TENSOR_MAP_SWIZZLE_128B, CU_TENSOR_MAP_L2_PROMOTION_L2_128B, CU_TENSOR_MAP_FLOAT_OOB_FILL_NONE);
}
void map2d(EncodeFn fn, CUtensorMap* m, const void* ptr, int cols, int rows, int box_rows) {
  const cuuint64_t dims[2] = {(cuuint64_t)cols, (cuuint64_t)rows}, st[1] = {(cuuint64_t)cols * 2};
  const cuuint32_t box[2] = {64, (cuuint32_t)box_rows};
  make_map(fn, m, ptr, 2, dims, st, box);
}
void map_w(EncodeFn fn, CUtensorMap* m, const void* ptr, int K, int N, int inner, int nch) {
  const cuuint64_t dims[3] = {(cuuint64_t)inner, (cuuint64_t)K, (cuuint64_t)(N / inner)}, st[2] = {(cuuint64_t)N * 2, (cuuint64_t)inner * 2};
  const cuuint32_t box[3] = {64, 64, (cuuint32_t)nch};
  make_map(fn, m, ptr, 3, dims, st, box);
}

}

extern "C" void kernel_launch(void* const* d_in, const int* in_sizes, int n_in, void* d_out, int out_size) {
  (void)in_sizes; (void)n_in; (void)out_size;
  Params p;
  p.x = (const __nv_bfloat16*)d_in[0]; p.wqkv = (const __nv_bfloat16*)d_in[1]; p.wo = (const __nv_bfloat16*)d_in[2];
  p.w1 = (const __nv_bfloat16*)d_in[4]; p.b1 = (const __nv_bfloat16*)d_in[5];
  p.w2 = (const __nv_bfloat16*)d_in[6]; p.b2 = (const __nv_bfloat16*)d_in[7];
  void* fnp = nullptr; cudaDriverEntryPointQueryResult qr;
  cudaGetDriverEntryPoint("cuTensorMapEncodeTiled", &fnp, cudaEnableDefault, &qr);
  EncodeFn fn = (EncodeFn)fnp;
  void *act, *h;
  cudaGetSymbolAddress(&act, g_act); cudaGetSymbolAddress(&h, g_h);
  map2d(fn, &p.ld_x, p.x, D_, S_, 128);
  map2d(fn, &p.ld_act, act, D_, 3 * S_, 128);
  map2d(fn, &p.ld_h, h, F_, S_, 128);
  map2d(fn, &p.st_act, act, D_, 3 * S_, 32);
  map2d(fn, &p.st_h, h, F_, S_, 32);
  map2d(fn, &p.st_out, d_out, D_, S_, 32);
  map_w(fn, &p.w_qkv, p.wqkv, D_, 3 * D_, D_, 3);
  map_w(fn, &p.w_o, p.wo, D_, D_, 64, 2);
  map_w(fn, &p.w_1a, p.w1, D_, F_, 64, 3);
  map_w(fn, &p.w_1b, p.w1, D_, F_, 64, 2);
  map_w(fn, &p.w_2, p.w2, F_, D_, 64, 2);
  cudaFuncSetAttribute(fused_kernel, cudaFuncAttributeMaxDynamicSharedMemorySize, SMEM_BYTES);
  fused_kernel<<<128, 384, SMEM_BYTES>>>(p);
}
```

```cpp
#include <cuda_runtime.h>
#include <cuda_bf16.h>
#include <cuda.h>
#include <stdint.h>

namespace {

constexpr int S_ = 2048, D_ = 1024, F_ = 3584;
constexpr int NST = 5;
constexpr int A_BYTES = 16384, ST_BYTES = 40960;
constexpr int OFF_STG = NST * ST_BYTES;
constexpr int OFF_CSQ = OFF_STG + 16384;
constexpr int OFF_UP  = OFF_CSQ + 1536;
constexpr int OFF_B2  = OFF_UP + 3584;
constexpr int OFF_RST = OFF_B2 + 512;
constexpr int OFF_BAR = OFF_RST + 1024;
constexpr int OFF_EPO = OFF_BAR + 128;
constexpr int SMEM_BYTES = OFF_EPO + 16 + 1024;
constexpr int KB_LAYER = 6 * 16 + 56;

constexpr int FK_TILE = 0;
constexpr int FK_STAT = 14;
constexpr int FK_HALO = 18;
constexpr int FK_CS   = 22;
constexpr int NFK = 23;

struct Params {
  CUtensorMap ld_x, ld_act, ld_h, st_act, st_h, st_out, w_qkv, w_o, w_1a, w_1b, w_2;
  const __nv_bfloat16 *x, *wqkv, *wo, *w1, *b1, *w2, *b2;
};

__device__ __align__(1024) __nv_bfloat16 g_act[3 * S_ * D_];
__device__ __align__(1024) __nv_bfloat16 g_h[S_ * F_];
__device__ __align__(128) float2 g_stats[4 * S_ * 8];
__device__ __align__(128) float g_cs[2 * (3 * D_ + F_)];
__device__ __align__(128) uint4 g_halo[4 * 16 * 8 * 256];
__device__ __align__(128) unsigned g_flags[NFK * 16 * 32];
__device__ unsigned g_epoch[128];
#define TL(t, e)
#define TLW(t, e)

template<int N> __device__ __forceinline__ void wgmma_ss(float (&d)[N/2], uint64_t da, uint64_t db, int sd);
template<> __device__ __forceinline__ void wgmma_ss<128>(float (&d)[64], uint64_t da, uint64_t db, int sd) {
  asm volatile("{\n.reg .pred p;\nsetp.ne.b32 p, %66, 0;\n"
    "wgmma.mma_async.sync.aligned.m64n128k16.f32.bf16.bf16 {%0, %1, %2, %3, %4, %5, %6, %7, %8, %9, %10, %11, %12, %13, %14, %15, %16, %17, %18, %19, %20, %21, %22, %23, %24, %25, %26, %27, %28, %29, %30, %31, %32, %33, %34, %35, %36, %37, %38, %39, %40, %41, %42, %43, %44, %45, %46, %47, %48, %49, %50, %51, %52, %53, %54, %55, %56, %57, %58, %59, %60, %61, %62, %63}, %64, %65, p, 1, 1, 0, 1;\n}\n"
    : "+f"(d[0]), "+f"(d[1]), "+f"(d[2]), "+f"(d[3]), "+f"(d[4]), "+f"(d[5]), "+f"(d[6]), "+f"(d[7]), "+f"(d[8]), "+f"(d[9]), "+f"(d[10]), "+f"(d[11]), "+f"(d[12]), "+f"(d[13]), "+f"(d[14]), "+f"(d[15]), "+f"(d[16]), "+f"(d[17]), "+f"(d[18]), "+f"(d[19]), "+f"(d[20]), "+f"(d[21]), "+f"(d[22]), "+f"(d[23]), "+f"(d[24]), "+f"(d[25]), "+f"(d[26]), "+f"(d[27]), "+f"(d[28]), "+f"(d[29]), "+f"(d[30]), "+f"(d[31]), "+f"(d[32]), "+f"(d[33]), "+f"(d[34]), "+f"(d[35]), "+f"(d[36]), "+f"(d[37]), "+f"(d[38]), "+f"(d[39]), "+f"(d[40]), "+f"(d[41]), "+f"(d[42]), "+f"(d[43]), "+f"(d[44]), "+f"(d[45]), "+f"(d[46]), "+f"(d[47]), "+f"(d[48]), "+f"(d[49]), "+f"(d[50]), "+f"(d[51]), "+f"(d[52]), "+f"(d[53]), "+f"(d[54]), "+f"(d[55]), "+f"(d[56]), "+f"(d[57]), "+f"(d[58]), "+f"(d[59]), "+f"(d[60]), "+f"(d[61]), "+f"(d[62]), "+f"(d[63])
    : "l"(da), "l"(db), "r"(sd));
}

template<> __device__ __forceinline__ void wgmma_ss<192>(float (&d)[96], uint64_t da, uint64_t db, int sd) {
  asm volatile("{\n.reg .pred p;\nsetp.ne.b32 p, %98, 0;\n"
    "wgmma.mma_async.sync.aligned.m64n192k16.f32.bf16.bf16 {%0, %1, %2, %3, %4, %5, %6, %7, %8, %9, %10, %11, %12, %13, %14, %15, %16, %17, %18, %19, %20, %21, %22, %23, %24, %25, %26, %27, %28, %29, %30, %31, %32, %33, %34, %35, %36, %37, %38, %39, %40, %41, %42, %43, %44, %45, %46, %47, %48, %49, %50, %51, %52, %53, %54, %55, %56, %57, %58, %59, %60, %61, %62, %63, %64, %65, %66, %67, %68, %69, %70, %71, %72, %73, %74, %75, %76, %77, %78, %79, %80, %81, %82, %83, %84, %85, %86, %87, %88, %89, %90, %91, %92, %93, %94, %95}, %96, %97, p, 1, 1, 0, 1;\n}\n"
    : "+f"(d[0]), "+f"(d[1]), "+f"(d[2]), "+f"(d[3]), "+f"(d[4]), "+f"(d[5]), "+f"(d[6]), "+f"(d[7]), "+f"(d[8]), "+f"(d[9]), "+f"(d[10]), "+f"(d[11]), "+f"(d[12]), "+f"(d[13]), "+f"(d[14]), "+f"(d[15]), "+f"(d[16]), "+f"(d[17]), "+f"(d[18]), "+f"(d[19]), "+f"(d[20]), "+f"(d[21]), "+f"(d[22]), "+f"(d[23]), "+f"(d[24]), "+f"(d[25]), "+f"(d[26]), "+f"(d[27]), "+f"(d[28]), "+f"(d[29]), "+f"(d[30]), "+f"(d[31]), "+f"(d[32]), "+f"(d[33]), "+f"(d[34]), "+f"(d[35]), "+f"(d[36]), "+f"(d[37]), "+f"(d[38]), "+f"(d[39]), "+f"(d[40]), "+f"(d[41]), "+f"(d[42]), "+f"(d[43]), "+f"(d[44]), "+f"(d[45]), "+f"(d[46]), "+f"(d[47]), "+f"(d[48]), "+f"(d[49]), "+f"(d[50]), "+f"(d[51]), "+f"(d[52]), "+f"(d[53]), "+f"(d[54]), "+f"(d[55]), "+f"(d[56]), "+f"(d[57]), "+f"(d[58]), "+f"(d[59]), "+f"(d[60]), "+f"(d[61]), "+f"(d[62]), "+f"(d[63]), "+f"(d[64]), "+f"(d[65]), "+f"(d[66]), "+f"(d[67]), "+f"(d[68]), "+f"(d[69]), "+f"(d[70]), "+f"(d[71]), "+f"(d[72]), "+f"(d[73]), "+f"(d[74]), "+f"(d[75]), "+f"(d[76]), "+f"(d[77]), "+f"(d[78]), "+f"(d[79]), "+f"(d[80]), "+f"(d[81]), "+f"(d[82]), "+f"(d[83]), "+f"(d[84]), "+f"(d[85]), "+f"(d[86]), "+f"(d[87]), "+f"(d[88]), "+f"(d[89]), "+f"(d[90]), "+f"(d[91]), "+f"(d[92]), "+f"(d[93]), "+f"(d[94]), "+f"(d[95])
    : "l"(da), "l"(db), "r"(sd));
}

__device__ __forceinline__ uint32_t smem_u32(const void* p) { return (uint32_t)__cvta_generic_to_shared(p); }
__device__ __forceinline__ void mbar_init(uint32_t bar, uint32_t cnt) { asm volatile("mbarrier.init.shared::cta.b64 [%0], %1;" :: "r"(bar), "r"(cnt)); }
__device__ __forceinline__ void mbar_expect_tx(uint32_t bar, uint32_t bytes) { asm volatile("mbarrier.arrive.expect_tx.shared::cta.b64 _, [%0], %1;" :: "r"(bar), "r"(bytes) : "memory"); }
__device__ __forceinline__ void mbar_arrive(uint32_t bar) { asm volatile("mbarrier.arrive.shared::cta.b64 _, [%0];" :: "r"(bar) : "memory"); }
__device__ __forceinline__ void mbar_wait(uint32_t bar, uint32_t parity) {
  asm volatile(
    "{\n.reg .pred p;\n.reg .u32 n;\n"
    "mbarrier.try_wait.parity.shared::cta.b64 p, [%0], %1;\n"
    "@p bra.uni WAIT_DONE;\n"
    "mov.u32 n, 0;\n"
    "WAIT_LOOP:\n"
    "mbarrier.try_wait.parity.shared::cta.b64 p, [%0], %1;\n"
    "@p bra.uni WAIT_DONE;\n"
    "add.u32 n, n, 1;\n"
    "setp.lt.u32 p, n, 0x4000000;\n"
    "@p bra.uni WAIT_LOOP;\n"
    "trap;\n"
    "WAIT_DONE:\n}" :: "r"(bar), "r"(parity) : "memory");
}
__device__ __forceinline__ void tma_ld2(uint32_t dst, const CUtensorMap* m, uint32_t bar, int c0, int c1) {
  asm volatile("cp.async.bulk.tensor.2d.shared::cluster.global.mbarrier::complete_tx::bytes [%0], [%1, {%3, %4}], [%2];"
    :: "r"(dst), "l"(m), "r"(bar), "r"(c0), "r"(c1) : "memory");
}
__device__ __forceinline__ void tma_ld3(uint32_t dst, const CUtensorMap* m, uint32_t bar, int c0, int c1, int c2) {
  asm volatile("cp.async.bulk.tensor.3d.shared::cluster.global.mbarrier::complete_tx::bytes [%0], [%1, {%3, %4, %5}], [%2];"
    :: "r"(dst), "l"(m), "r"(bar), "r"(c0), "r"(c1), "r"(c2) : "memory");
}
__device__ __forceinline__ void tma_st2(const CUtensorMap* m, uint32_t src, int c0, int c1) {
  asm volatile("cp.async.bulk.tensor.2d.global.shared::cta.bulk_group [%0, {%2, %3}], [%1];"
    :: "l"(m), "r"(src), "r"(c0), "r"(c1) : "memory");
}
__device__ __forceinline__ void bulk_commit() { asm volatile("cp.async.bulk.commit_group;" ::: "memory"); }
__device__ __forceinline__ void bulk_wait_all() { asm volatile("cp.async.bulk.wait_group 0;" ::: "memory"); }
__device__ __forceinline__ void bulk_wait_read() { asm volatile("cp.async.bulk.wait_group.read 0;" ::: "memory"); }
__device__ __forceinline__ void fence_async_smem() { asm volatile("fence.proxy.async.shared::cta;" ::: "memory"); }
__device__ __forceinline__ void fence_async_all() { asm volatile("fence.proxy.async;" ::: "memory"); }
__device__ __forceinline__ void wgmma_fence() { asm volatile("wgmma.fence.sync.aligned;" ::: "memory"); }
__device__ __forceinline__ void wgmma_commit() { asm volatile("wgmma.commit_group.sync.aligned;" ::: "memory"); }
template<int N> __device__ __forceinline__ void wgmma_wait() { asm volatile("wgmma.wait_group.sync.aligned %0;" :: "n"(N) : "memory"); }
__device__ __forceinline__ void bar_sync(int id, int n) { asm volatile("bar.sync %0, %1;" :: "r"(id), "r"(n) : "memory"); }
__device__ __forceinline__ unsigned ld_acquire(const unsigned* p) { unsigned v; asm volatile("ld.acquire.gpu.global.u32 %0, [%1];" : "=r"(v) : "l"(p) : "memory"); return v; }
__device__ __forceinline__ void red_release(unsigned* p) { asm volatile("red.release.gpu.global.add.u32 [%0], 1;" :: "l"(p) : "memory"); }
__device__ __forceinline__ uint32_t pack_bf16(float lo, float hi) { uint32_t r; asm("cvt.rn.bf16x2.f32 %0, %1, %2;" : "=r"(r) : "f"(hi), "f"(lo)); return r; }
__device__ __forceinline__ float bf_lo(uint32_t u) { return __uint_as_float(u << 16); }
__device__ __forceinline__ float bf_hi(uint32_t u) { return __uint_as_float(u & 0xffff0000u); }
__device__ __forceinline__ void stmatrix4(uint32_t addr, uint32_t r0, uint32_t r1, uint32_t r2, uint32_t r3) {
  asm volatile("stmatrix.sync.aligned.m8n8.x4.shared.b16 [%0], {%1, %2, %3, %4};" :: "r"(addr), "r"(r0), "r"(r1), "r"(r2), "r"(r3) : "memory");
}
__device__ __forceinline__ uint32_t movmatrix(uint32_t a) { uint32_t d; asm volatile("movmatrix.sync.aligned.m8n8.trans.b16 %0, %1;" : "=r"(d) : "r"(a)); return d; }
__device__ __forceinline__ void mma16816(float (&c)[4], uint32_t a0, uint32_t a1, uint32_t a2, uint32_t a3, uint32_t b0, uint32_t b1) {
  asm volatile("mma.sync.aligned.m16n8k16.row.col.f32.bf16.bf16.f32 {%0,%1,%2,%3}, {%4,%5,%6,%7}, {%8,%9}, {%0,%1,%2,%3};"
    : "+f"(c[0]), "+f"(c[1]), "+f"(c[2]), "+f"(c[3]) : "r"(a0), "r"(a1), "r"(a2), "r"(a3), "r"(b0), "r"(b1));
}
__device__ __forceinline__ void sts128(uint32_t a, uint32_t x, uint32_t y, uint32_t z, uint32_t w) { asm volatile("st.shared.v4.b32 [%0], {%1,%2,%3,%4};" :: "r"(a), "r"(x), "r"(y), "r"(z), "r"(w) : "memory"); }
__device__ __forceinline__ uint4 lds128(uint32_t a) { uint4 v; asm volatile("ld.shared.v4.b32 {%0,%1,%2,%3}, [%4];" : "=r"(v.x), "=r"(v.y), "=r"(v.z), "=r"(v.w) : "r"(a) : "memory"); return v; }
__device__ __forceinline__ float2 lds64f(uint32_t a) { float2 v; asm volatile("ld.shared.v2.f32 {%0,%1}, [%2];" : "=f"(v.x), "=f"(v.y) : "r"(a) : "memory"); return v; }
__device__ __forceinline__ float4 lds128f(uint32_t a) { float4 v; asm volatile("ld.shared.v4.f32 {%0,%1,%2,%3}, [%4];" : "=f"(v.x), "=f"(v.y), "=f"(v.z), "=f"(v.w) : "r"(a) : "memory"); return v; }
__device__ __forceinline__ void sts32f(uint32_t a, float v) { asm volatile("st.shared.f32 [%0], %1;" :: "r"(a), "f"(v) : "memory"); }
__device__ __forceinline__ void sts64f(uint32_t a, float x, float y) { asm volatile("st.shared.v2.f32 [%0], {%1,%2};" :: "r"(a), "f"(x), "f"(y) : "memory"); }
__device__ __forceinline__ float lds32f(uint32_t a) { float v; asm volatile("ld.shared.f32 %0, [%1];" : "=f"(v) : "r"(a) : "memory"); return v; }
template<int R> __device__ __forceinline__ void reg_alloc() { asm volatile("setmaxnreg.inc.sync.aligned.u32 %0;" :: "n"(R)); }
template<int R> __device__ __forceinline__ void reg_dealloc() { asm volatile("setmaxnreg.dec.sync.aligned.u32 %0;" :: "n"(R)); }

__device__ __forceinline__ unsigned* flag_ptr(int kind, int m) { return g_flags + (kind * 16 + m) * 32; }

__device__ __forceinline__ void warp_wait_flags(const unsigned* p, int n, unsigned target, int lane) {
  for (unsigned it = 0;; it++) {
    unsigned v = lane < n ? ld_acquire(p + lane) : target;
    if (__all_sync(0xffffffffu, (int)(v - target) >= 0)) break;
    if (it > 0x1000000u) __trap();
  }
  __syncwarp();
}

__device__ __forceinline__ int kb_of(int step, bool own_first, int j) {
  if (!own_first) return step;
  if (step < 2) return 2 * j + step;
  return (step - 2 < 2 * j) ? step - 2 : step;
}

struct Ctx {
  uint32_t sb;
  int m, j, wg, w, lane;
  unsigned epoch;
};

template<int BN, bool ZERO>
__device__ __forceinline__ void mainloop(const Ctx& c, float (&acc)[2][BN / 2], int t, int nkb) {
  int g0 = (t >= 7 ? KB_LAYER + (t - 7) * 16 : t * 16);
  int s = g0 % NST;
  uint32_t ph = (g0 / NST) & 1;
  const uint32_t full0 = c.sb + OFF_BAR, empty0 = full0 + 8 * NST;
  if (ZERO) {
#pragma unroll
    for (int i = 0; i < BN / 2; i++) { acc[0][i] = 0.f; acc[1][i] = 0.f; }
  }
  TL(t, 0);
  if (t > 0) bar_sync(1, 256);
  TL(t, 1);
  int prev = 0;
  for (int kb = 0; kb < nkb; kb++) {
    mbar_wait(full0 + 8 * s, ph);
    const uint32_t a = c.sb + s * ST_BYTES;
    const uint64_t da = (uint64_t)((a >> 4) | (1u << 16)) | ((uint64_t)(128u | (1u << 30)) << 32);
    const uint64_t db = (uint64_t)(((a + A_BYTES) >> 4) | (512u << 16)) | ((uint64_t)(64u | (1u << 30)) << 32);
    wgmma_fence();
#pragma unroll
    for (int k = 0; k < 4; k++) {
#pragma unroll
      for (int i = 0; i < 2; i++)
        wgmma_ss<BN>(acc[i], da + (i * 64 + k * 2), db + k * 128, 1);
    }
    wgmma_commit();
    if (kb == nkb - 1 && t < 13) bar_sync(1, 256);
    wgmma_wait<1>();
    if (kb > 0 && c.lane == 0) mbar_arrive(empty0 + 8 * prev);
    prev = s;
    if (++s == NST) { s = 0; ph ^= 1; }
  }
  wgmma_wait<0>();
  if (c.lane == 0) mbar_arrive(empty0 + 8 * prev);
  TL(t, 3);
}

__device__ __forceinline__ void load_row_stats(const Ctx& c, int ln) {
  warp_wait_flags(flag_ptr(FK_STAT + ln, c.m), 8, 4 * (c.epoch + 1), c.lane);
  const float4* p = reinterpret_cast<const float4*>(g_stats + ((size_t)ln * S_ + c.m * 128 + c.w * 32 + c.lane) * 8);
  float4 v0 = __ldcg(p), v1 = __ldcg(p + 1), v2 = __ldcg(p + 2), v3 = __ldcg(p + 3);
  float s = ((v0.x + v0.z) + (v1.x + v1.z)) + ((v2.x + v2.z) + (v3.x + v3.z));
  float q = ((v0.y + v0.w) + (v1.y + v1.w)) + ((v2.y + v2.w) + (v3.y + v3.w));
  float mean = s * (1.0f / D_);
  float var = fmaxf(q * (1.0f / D_) - mean * mean, 0.0f);
  sts64f(c.sb + OFF_RST + (c.w * 32 + c.lane) * 8, mean, rsqrtf(var + 1e-5f));
  __syncwarp();
}

__device__ __forceinline__ void attn16(const uint32_t (&qa)[4], const uint32_t (&qb)[4],
    const uint32_t (&k0a)[4], const uint32_t (&k0b)[4], const uint32_t (&k1a)[4], const uint32_t (&k1b)[4],
    const uint32_t (&v0a)[4], const uint32_t (&v0b)[4], const uint32_t (&v1a)[4], const uint32_t (&v1b)[4],
    uint32_t (&oa)[4], uint32_t (&ob)[4], int lane, bool nohalo) {
  float s0[4] = {0, 0, 0, 0}, s1[4] = {0, 0, 0, 0}, s2[4] = {0, 0, 0, 0}, s3[4] = {0, 0, 0, 0};
#pragma unroll
  for (int t = 0; t < 2; t++) {
    mma16816(s0, qa[2 * t], qb[2 * t], qa[2 * t + 1], qb[2 * t + 1], k0a[2 * t], k0a[2 * t + 1]);
    mma16816(s1, qa[2 * t], qb[2 * t], qa[2 * t + 1], qb[2 * t + 1], k0b[2 * t], k0b[2 * t + 1]);
    mma16816(s2, qa[2 * t], qb[2 * t], qa[2 * t + 1], qb[2 * t + 1], k1a[2 * t], k1a[2 * t + 1]);
    mma16816(s3, qa[2 * t], qb[2 * t], qa[2 * t + 1], qb[2 * t + 1], k1b[2 * t], k1b[2 * t + 1]);
  }
  const int g = lane >> 2, cc = lane & 3;
  const bool odd = g & 1, far = cc > (g >> 1);
  float m0 = odd ? s1[1] : s1[0];
  float a0 = far ? (odd ? s0[1] : s0[0]) : (odd ? s2[1] : s2[0]);
  float m1 = odd ? s2[3] : s2[2];
  float a1 = far ? (odd ? s1[3] : s1[2]) : (odd ? s3[3] : s3[2]);
  const float sc = 0.17677669529663687f * 1.4426950408889634f;
  m0 *= sc; a0 *= sc; m1 *= sc; a1 *= sc;
  if (nohalo) { const float neg = -1e9f * 1.4426950408889634f; m0 = neg; if (far) { a0 = neg; a1 = neg; } }
  float x0 = fmaxf(m0, a0), x1 = fmaxf(m1, a1);
  x0 = fmaxf(x0, __shfl_xor_sync(0xffffffffu, x0, 1)); x1 = fmaxf(x1, __shfl_xor_sync(0xffffffffu, x1, 1));
  x0 = fmaxf(x0, __shfl_xor_sync(0xffffffffu, x0, 2)); x1 = fmaxf(x1, __shfl_xor_sync(0xffffffffu, x1, 2));
  m0 = exp2f(m0 - x0); a0 = exp2f(a0 - x0); m1 = exp2f(m1 - x1); a1 = exp2f(a1 - x1);
  float t0 = m0 + a0, t1 = m1 + a1;
  t0 += __shfl_xor_sync(0xffffffffu, t0, 1); t1 += __shfl_xor_sync(0xffffffffu, t1, 1);
  t0 += __shfl_xor_sync(0xffffffffu, t0, 2); t1 += __shfl_xor_sync(0xffffffffu, t1, 2);
  t0 = __frcp_rn(t0); t1 = __frcp_rn(t1);
  const int sh = odd ? 16 : 0;
  const uint32_t pm0 = pack_bf16(m0 * t0, 0.f) << sh, pa0 = pack_bf16(a0 * t0, 0.f) << sh;
  const uint32_t pm1 = pack_bf16(m1 * t1, 0.f) << sh, pa1 = pack_bf16(a1 * t1, 0.f) << sh;
  const uint32_t f0 = far ? pa0 : 0u, n0 = far ? 0u : pa0, f1 = far ? pa1 : 0u, n1 = far ? 0u : pa1;
#pragma unroll
  for (int dt = 0; dt < 4; dt++) {
    float o[4] = {0, 0, 0, 0};
    mma16816(o, f0, 0u, pm0, f1, v0a[dt], v0b[dt]);
    mma16816(o, n0, pm1, 0u, n1, v1a[dt], v1b[dt]);
    oa[dt] = pack_bf16(o[0], o[1]);
    ob[dt] = pack_bf16(o[2], o[3]);
  }
}

__device__ __forceinline__ void tile_qkv(const Ctx& c, const Params& p, int t) {
  const int layer = t >= 7, q = t - layer * 7;
  float acc[2][96];
  mainloop<192, true>(c, acc, t, 16);
  const int lane = c.lane, w = c.w, g = lane >> 2, cc = lane & 3;
  if (q == 0) {
    load_row_stats(c, layer * 2);
    if (layer == 0) {
      warp_wait_flags(flag_ptr(FK_CS, 0), 1, 96 * (c.epoch + 1), lane);
#pragma unroll
      for (int r = 0; r < 3; r++) {
        int i = r * 128 + w * 32 + lane;
        int qq = i / 192, rem = i - qq * 192;
        int col = (rem >> 6) * D_ + (c.j + 8 * qq) * 64 + (rem & 63);
        sts32f(c.sb + OFF_CSQ + i * 4, __ldcg(g_cs + col) + __ldcg(g_cs + (3 * D_ + F_) + col));
      }
      bar_sync(2 + c.wg, 128);
    }
  }
  float2 rs[4];
#pragma unroll
  for (int r = 0; r < 4; r++) rs[r] = lds64f(c.sb + OFF_RST + (w * 32 + 8 * r + g) * 8);
  uint32_t P[3][2][4][4];
  const uint32_t csb = c.sb + OFF_CSQ + q * 768 + cc * 8;
#pragma unroll
  for (int nn = 0; nn < 24; nn++) {
    const int nt = (nn + 8) % 24;
    const float2 cs = lds64f(csb + nt * 32);
#pragma unroll
    for (int r = 0; r < 4; r++) {
      const int i = r & 1, h = r >> 1;
      float v0 = fmaf(-rs[r].x, cs.x, acc[i][4 * nt + 2 * h]) * rs[r].y;
      float v1 = fmaf(-rs[r].x, cs.y, acc[i][4 * nt + 2 * h + 1]) * rs[r].y;
      uint32_t u = pack_bf16(v0, v1);
      if (nt >= 16) u = movmatrix(u);
      P[nt >> 3][(nt >> 2) & 1][r][nt & 3] = u;
    }
    if (nn == 15) {
      if (w < 3) {
        const uint32_t dst = c.sb + OFF_STG + (w + 1) * 4096 + lane * 16;
#pragma unroll
        for (int z = 0; z < 8; z++) { const uint32_t* u = P[1 + (z >> 2)][(z >> 1) & 1][2 + (z & 1)]; sts128(dst + z * 512, u[0], u[1], u[2], u[3]); }
      } else if (c.m < 15) {
        uint4* dst = g_halo + (((layer * 2 + q) * 16 + c.m) * 8 + c.j) * 256 + lane;
#pragma unroll
        for (int z = 0; z < 8; z++) { const uint32_t* u = P[1 + (z >> 2)][(z >> 1) & 1][2 + (z & 1)]; __stcg(dst + z * 32, make_uint4(u[0], u[1], u[2], u[3])); }
        __syncwarp();
        if (lane == 0) red_release(flag_ptr(FK_HALO + layer * 2 + q, c.m) + c.j);
      }
    }
  }
  uint32_t O[2][4][4];
#pragma unroll
  for (int hh = 0; hh < 2; hh++)
    attn16(P[0][hh][2], P[0][hh][3], P[1][hh][0], P[1][hh][1], P[1][hh][2], P[1][hh][3],
           P[2][hh][0], P[2][hh][1], P[2][hh][2], P[2][hh][3], O[hh][2], O[hh][3], lane, false);
  bar_sync(2 + c.wg, 128);
  uint32_t H[2][2][2][4];
  const bool nohalo = (w == 0 && c.m == 0);
  if (w > 0) {
    const uint32_t src = c.sb + OFF_STG + w * 4096 + lane * 16;
#pragma unroll
    for (int z = 0; z < 8; z++) { uint4 v = lds128(src + z * 512); uint32_t* u = H[z >> 2][(z >> 1) & 1][z & 1]; u[0] = v.x; u[1] = v.y; u[2] = v.z; u[3] = v.w; }
  } else if (!nohalo) {
    warp_wait_flags(flag_ptr(FK_HALO + layer * 2 + q, c.m - 1) + c.j, 1, c.epoch + 1, lane);
    const uint4* src = g_halo + (((layer * 2 + q) * 16 + c.m - 1) * 8 + c.j) * 256 + lane;
#pragma unroll
    for (int z = 0; z < 8; z++) { uint4 v = __ldcg(src + z * 32); uint32_t* u = H[z >> 2][(z >> 1) & 1][z & 1]; u[0] = v.x; u[1] = v.y; u[2] = v.z; u[3] = v.w; }
  } else {
#pragma unroll
    for (int z = 0; z < 8; z++) { uint32_t* u = H[z >> 2][(z >> 1) & 1][z & 1]; u[0] = u[1] = u[2] = u[3] = 0u; }
  }
#pragma unroll
  for (int hh = 0; hh < 2; hh++)
    attn16(P[0][hh][0], P[0][hh][1], H[0][hh][0], H[0][hh][1], P[1][hh][0], P[1][hh][1],
           H[1][hh][0], H[1][hh][1], P[2][hh][0], P[2][hh][1], O[hh][0], O[hh][1], lane, nohalo);
  __syncwarp();
  const uint32_t stg = c.sb + OFF_STG + w * 4096;
#pragma unroll
  for (int nt = 0; nt < 8; nt++)
    stmatrix4(stg + lane * 128 + ((nt ^ (lane & 7)) << 4), O[nt >> 2][0][nt & 3], O[nt >> 2][1][nt & 3], O[nt >> 2][2][nt & 3], O[nt >> 2][3][nt & 3]);
  fence_async_smem();
  __syncwarp();
  TL(t, 4);
  if (lane == 0) {
    tma_st2(&p.st_act, stg, (c.j + 8 * q) * 64, 2 * S_ + c.m * 128 + w * 32);
    bulk_commit();
    bulk_wait_all();
    red_release(flag_ptr(FK_TILE + t, c.m) + c.j);
  }
  __syncwarp();
  TL(t, 5);
  if (t == 0) {
    warp_wait_flags(flag_ptr(FK_CS, 1), 1, 112 * (c.epoch + 1), lane);
    for (int i = w * 32 + lane; i < 448; i += 128) {
      int col = i < 192 ? c.j * 192 + i : (i < 320 ? 1536 + c.j * 128 + (i - 192) : 2560 + c.j * 128 + (i - 320));
      uint32_t a = c.sb + OFF_UP + (i >> 1) * 16 + (i & 1) * 4;
      sts32f(a, __ldcg(g_cs + 3 * D_ + col) + __ldcg(g_cs + (3 * D_ + F_) + 3 * D_ + col));
      sts32f(a + 8, __bfloat162float(p.b1[col]));
    }
    sts32f(c.sb + OFF_B2 + (w * 32 + lane) * 4, __bfloat162float(p.b2[c.j * 128 + w * 32 + lane]));
  }
}

template<int BN>
__device__ __forceinline__ void tile_up(const Ctx& c, const Params& p, int t) {
  const int layer = t >= 7, type = t - layer * 7;
  float acc[2][BN / 2];
  mainloop<BN, true>(c, acc, t, 16);
  const int lane = c.lane, w = c.w, g = lane >> 2, cc = lane & 3;
  if (BN == 192) load_row_stats(c, layer * 2 + 1);
  float2 rs[4];
#pragma unroll
  for (int r = 0; r < 4; r++) rs[r] = lds64f(c.sb + OFF_RST + (w * 32 + 8 * r + g) * 8);
  const int loc0 = BN == 192 ? 0 : (type == 4 ? 192 : 320);
  const int col0 = BN == 192 ? c.j * 192 : (type == 4 ? 1536 : 2560) + c.j * 128;
  const uint32_t cb = c.sb + OFF_UP + loc0 * 8 + cc * 16;
  const uint32_t stg = c.sb + OFF_STG + w * 4096;
#pragma unroll
  for (int ch = 0; ch < BN / 64; ch++) {
    uint32_t P[8][4];
#pragma unroll
    for (int n8 = 0; n8 < 8; n8++) {
      const int nt = ch * 8 + n8;
      const float4 cv = lds128f(cb + nt * 64);
#pragma unroll
      for (int r = 0; r < 4; r++) {
        const int i = r & 1, h = r >> 1;
        float v0 = fmaxf(fmaf(fmaf(-rs[r].x, cv.x, acc[i][4 * nt + 2 * h]), rs[r].y, cv.z), 0.f);
        float v1 = fmaxf(fmaf(fmaf(-rs[r].x, cv.y, acc[i][4 * nt + 2 * h + 1]), rs[r].y, cv.w), 0.f);
        P[n8][r] = pack_bf16(v0 * v0, v1 * v1);
      }
    }
    if (ch > 0) { if (lane == 0) bulk_wait_read(); __syncwarp(); }
#pragma unroll
    for (int n8 = 0; n8 < 8; n8++)
      stmatrix4(stg + lane * 128 + ((n8 ^ (lane & 7)) << 4), P[n8][0], P[n8][1], P[n8][2], P[n8][3]);
    fence_async_smem();
    __syncwarp();
    if (lane == 0) { tma_st2(&p.st_h, stg, col0 + ch * 64, c.m * 128 + w * 32); bulk_commit(); }
  }
  TL(t, 4);
  if (lane == 0) { bulk_wait_all(); red_release(flag_ptr(FK_TILE + t, c.m) + c.j); }
  __syncwarp();
  TL(t, 5);
}

__device__ __forceinline__ void tile_res(const Ctx& c, const Params& p, int t) {
  const int layer = t >= 7, type = t - layer * 7;
  const bool isD = type == 6;
  const int lane = c.lane, w = c.w, g = lane >> 2, cc = lane & 3;
  float acc[2][64];
  {
    const __nv_bfloat16* src = isD ? g_act : (layer ? g_act + S_ * D_ : p.x);
    const uint32_t* r0 = reinterpret_cast<const uint32_t*>(src + (size_t)(c.m * 128 + w * 32 + g) * D_ + c.j * 128 + cc * 2);
    uint32_t u[4][16];
#pragma unroll
    for (int r = 0; r < 4; r++)
#pragma unroll
      for (int nt = 0; nt < 16; nt++) u[r][nt] = __ldcg(r0 + r * 8 * (D_ / 2) + nt * 4);
#pragma unroll
    for (int nt = 0; nt < 16; nt++) {
      float2 b = make_float2(0.f, 0.f);
      if (isD) b = lds64f(c.sb + OFF_B2 + nt * 32 + cc * 8);
#pragma unroll
      for (int r = 0; r < 4; r++) {
        acc[r & 1][4 * nt + 2 * (r >> 1)] = bf_lo(u[r][nt]) + b.x;
        acc[r & 1][4 * nt + 2 * (r >> 1) + 1] = bf_hi(u[r][nt]) + b.y;
      }
    }
  }
  const int nkb = isD ? 56 : 16;
  mainloop<128, false>(c, acc, t, nkb);
  const int g1 = (layer ? KB_LAYER : 0) + type * 16 + nkb;
  const int s0 = g1 % NST, s1 = (g1 + 1) % NST;
  const uint32_t d0 = c.sb + s0 * ST_BYTES + w * 4096, d1 = c.sb + s1 * ST_BYTES + w * 4096;
  uint32_t P[16][4];
#pragma unroll
  for (int nt = 0; nt < 16; nt++) {
#pragma unroll
    for (int r = 0; r < 4; r++) P[nt][r] = pack_bf16(acc[r & 1][4 * nt + 2 * (r >> 1)], acc[r & 1][4 * nt + 2 * (r >> 1) + 1]);
    stmatrix4((nt < 8 ? d0 : d1) + lane * 128 + (((nt & 7) ^ (lane & 7)) << 4), P[nt][0], P[nt][1], P[nt][2], P[nt][3]);
  }
  fence_async_smem();
  __syncwarp();
  if (lane == 0) {
    const CUtensorMap* mp = t == 13 ? &p.st_out : &p.st_act;
    const int row = (t == 6 ? S_ : 0) + c.m * 128 + w * 32;
    tma_st2(mp, d0, c.j * 128, row);
    tma_st2(mp, d1, c.j * 128 + 64, row);
    bulk_commit();
  }
  if (t == 13) {
    if (lane == 0) bulk_wait_all();
    TL(t, 5);
    return;
  }
  bar_sync(2 + c.wg, 128);
  if (w == 0 && lane == 0) { mbar_arrive(c.sb + OFF_BAR + 8 * s0); mbar_arrive(c.sb + OFF_BAR + 8 * s1); }
  TL(t, 4);
  float sm[4], sq[4];
#pragma unroll
  for (int r = 0; r < 4; r++) {
    float a = 0.f, b = 0.f;
#pragma unroll
    for (int nt = 0; nt < 16; nt++) { float x = bf_lo(P[nt][r]), y = bf_hi(P[nt][r]); a += x + y; b = fmaf(x, x, fmaf(y, y, b)); }
    a += __shfl_xor_sync(0xffffffffu, a, 1); b += __shfl_xor_sync(0xffffffffu, b, 1);
    a += __shfl_xor_sync(0xffffffffu, a, 2); b += __shfl_xor_sync(0xffffffffu, b, 2);
    sm[r] = a; sq[r] = b;
  }
  if (lane == 0) { bulk_wait_all(); red_release(flag_ptr(FK_TILE + t, c.m) + c.j); }
  TL(t, 5);
  const int ln = layer * 2 + (isD ? 2 : 1);
  const float a = cc == 0 ? sm[0] : cc == 1 ? sm[1] : cc == 2 ? sm[2] : sm[3];
  const float b = cc == 0 ? sq[0] : cc == 1 ? sq[1] : cc == 2 ? sq[2] : sq[3];
  __stcg(g_stats + ((size_t)ln * S_ + c.m * 128 + w * 32 + 8 * cc + g) * 8 + c.j, make_float2(a, b));
  __syncwarp();
  if (lane == 0) red_release(flag_ptr(FK_STAT + ln, c.m) + c.j);
}

__device__ __forceinline__ void colsum_piece(const Ctx& c, const __nv_bfloat16* W, int ldw, int piece, float* out, unsigned* flag) {
  const int tid = c.w * 32 + c.lane;
  const int chunk = piece >> 1, half = piece & 1;
  const uint4* src = reinterpret_cast<const uint4*>(W + (size_t)(half * 512 + (tid >> 3)) * ldw + chunk * 64 + (tid & 7) * 8);
  float a[8] = {0, 0, 0, 0, 0, 0, 0, 0};
  uint4 v[32];
#pragma unroll
  for (int i = 0; i < 32; i++) v[i] = __ldg(src + (size_t)i * 16 * (ldw / 8));
#pragma unroll
  for (int i = 0; i < 32; i++) {
    a[0] += bf_lo(v[i].x); a[1] += bf_hi(v[i].x); a[2] += bf_lo(v[i].y); a[3] += bf_hi(v[i].y);
    a[4] += bf_lo(v[i].z); a[5] += bf_hi(v[i].z); a[6] += bf_lo(v[i].w); a[7] += bf_hi(v[i].w);
  }
#pragma unroll
  for (int e = 0; e < 8; e++) { a[e] += __shfl_xor_sync(0xffffffffu, a[e], 8); a[e] += __shfl_xor_sync(0xffffffffu, a[e], 16); }
  const uint32_t red = c.sb + OFF_UP;
  if (c.lane < 8) {
#pragma unroll
    for (int e = 0; e < 8; e++) sts32f(red + (c.w * 64 + c.lane * 8 + e) * 4, a[e]);
  }
  bar_sync(2 + c.wg, 128);
  if (c.w == 0) {
#pragma unroll
    for (int r = 0; r < 2; r++) {
      const int col = r * 32 + c.lane;
      float s = (lds32f(red + col * 4) + lds32f(red + (64 + col) * 4)) + (lds32f(red + (128 + col) * 4) + lds32f(red + (192 + col) * 4));
      __stcg(out + half * (3 * D_ + F_) + chunk * 64 + col, s);
    }
    __syncwarp();
    if (c.lane == 0) red_release(flag);
  }
  bar_sync(2 + c.wg, 128);
}

__device__ __forceinline__ void prologue(const Ctx& c, const Params& p) {
  const int row0 = c.m * 128 + c.j * 16 + c.w * 4;
  uint4 v[4][4];
#pragma unroll
  for (int r = 0; r < 4; r++)
#pragma unroll
    for (int i = 0; i < 4; i++) v[r][i] = __ldg(reinterpret_cast<const uint4*>(p.x + (size_t)(row0 + r) * D_) + i * 32 + c.lane);
#pragma unroll
  for (int r = 0; r < 4; r++) {
    float a = 0.f, b = 0.f;
#pragma unroll
    for (int i = 0; i < 4; i++) {
      const uint32_t u[4] = {v[r][i].x, v[r][i].y, v[r][i].z, v[r][i].w};
#pragma unroll
      for (int e = 0; e < 4; e++) { float x = bf_lo(u[e]), y = bf_hi(u[e]); a += x + y; b = fmaf(x, x, fmaf(y, y, b)); }
    }
#pragma unroll
    for (int o = 1; o < 32; o <<= 1) { a += __shfl_xor_sync(0xffffffffu, a, o); b += __shfl_xor_sync(0xffffffffu, b, o); }
    if (c.lane < 8) __stcg(g_stats + (size_t)(row0 + r) * 8 + c.lane, c.lane == 0 ? make_float2(a, b) : make_float2(0.f, 0.f));
  }
  __syncwarp();
  if (c.lane == 0) red_release(flag_ptr(FK_STAT, c.m) + c.j);
  const int b = c.m * 8 + c.j;
  if (b < 96) colsum_piece(c, p.wqkv, 3 * D_, b, g_cs, flag_ptr(FK_CS, 0));
  if (b >= 16) colsum_piece(c, p.w1, F_, b - 16, g_cs + 3 * D_, flag_ptr(FK_CS, 1));
}

__global__ void __launch_bounds__(384, 1) fused_kernel(const __grid_constant__ Params p) {
  extern __shared__ uint8_t smem_raw[];
  Ctx c;
  c.sb = (smem_u32(smem_raw) + 1023) & ~1023u;
  const int tid = threadIdx.x;
  c.wg = __shfl_sync(0xffffffffu, tid >> 7, 0); c.w = __shfl_sync(0xffffffffu, (tid >> 5) & 3, 0); c.lane = tid & 31;
  c.m = blockIdx.x >> 3; c.j = blockIdx.x & 7;
  const uint32_t full0 = c.sb + OFF_BAR, empty0 = full0 + 8 * NST;
  c.epoch = __ldcg(g_epoch + blockIdx.x);
  if (tid == 0) {
    for (int s = 0; s < NST; s++) { mbar_init(full0 + 8 * s, 2); mbar_init(empty0 + 8 * s, 4); }
    asm volatile("fence.mbarrier_init.release.cluster;" ::: "memory");
  }
  __syncthreads();
  if (c.wg == 2) {
    reg_dealloc<40>();
    if (c.w == 0) {
      const unsigned target = 4 * (c.epoch + 1);
      int s = 0; uint32_t ph = 1;
      for (int t = 0; t < 14; t++) {
        const int layer = t >= 7, type = t - layer * 7;
        const CUtensorMap* mp = type == 6 ? &p.ld_h : (t < 2 ? &p.ld_x : &p.ld_act);
        const int row0 = c.m * 128 + (type == 2 ? 2 * S_ : (type < 2 && layer ? S_ : 0));
        const int nkb = type == 6 ? 56 : 16;
        const bool own = type == 3 || t == 7;
        int cur = -1; unsigned ready = 0;
        for (int step = 0; step < nkb; step++) {
          const int kb = kb_of(step, own, c.j);
          int kind = -1; unsigned need = 0;
          if (own) { if (step >= 2) { kind = t - 1; need = (1u << (kb >> 1)) | (step >= NST ? 1u << c.j : 0u); } }
          else if (type == 2) { kind = t - 2 + (kb >> 3); need = 1u << (kb & 7); }
          else if (type == 6) {
            if (kb < 24) { kind = t - 3; need = 1u << (kb / 3); }
            else { kind = t - 2 + (kb >= 40); need = 1u << (((kb - 24) >> 1) & 7); }
          }
          if (kind != cur) { cur = kind; ready = 0; }
          if ((ready & need) != need) {
            const unsigned* fp = flag_ptr(FK_TILE + kind, c.m);
            for (unsigned it = 0;; it++) {
              unsigned v = c.lane < 8 ? ld_acquire(fp + c.lane) : 0u;
              ready = __ballot_sync(0xffffffffu, c.lane < 8 && (int)(v - target) >= 0);
              if ((ready & need) == need) break;
              if (it > 0x1000000u) __trap();
            }
            __syncwarp();
            fence_async_all();
          }
          mbar_wait(empty0 + 8 * s, ph);
          if (c.lane == 0 && !(own && step < 2)) {
            mbar_expect_tx(full0 + 8 * s, A_BYTES);
            tma_ld2(c.sb + s * ST_BYTES, mp, full0 + 8 * s, kb * 64, row0);
          }
          if (++s == NST) { s = 0; ph ^= 1; }
        }
      }
    } else if (c.w == 1 && c.lane == 0) {
      int s = 0; uint32_t ph = 1;
      for (int t = 0; t < 14; t++) {
        const int layer = t >= 7, type = t - layer * 7;
        const CUtensorMap* mp = type < 2 ? &p.w_qkv : type == 2 ? &p.w_o : type == 3 ? &p.w_1a : type < 6 ? &p.w_1b : &p.w_2;
        const int c0 = type < 2 ? (c.j + 8 * type) * 64 : 0;
        const int c2 = type < 2 ? 0 : type == 3 ? 3 * c.j : type == 4 ? 24 + 2 * c.j : type == 5 ? 40 + 2 * c.j : 2 * c.j;
        const uint32_t bytes = (type < 2 || type == 3) ? 24576 : 16384;
        const int nkb = type == 6 ? 56 : 16;
        const bool own = type == 3 || t == 7;
        for (int step = 0; step < nkb; step++) {
          const int kb = kb_of(step, own, c.j);
          mbar_wait(empty0 + 8 * s, ph);
          mbar_expect_tx(full0 + 8 * s, bytes);
          tma_ld3(c.sb + s * ST_BYTES + A_BYTES, mp, full0 + 8 * s, c0, kb * 64, c2);
          if (++s == NST) { s = 0; ph ^= 1; }
        }
      }
    } else if (c.w == 2 && c.lane == 0) {
      g_epoch[blockIdx.x] = c.epoch + 1;
    }
  } else {
    reg_alloc<232>();
    if (c.wg == 1) prologue(c, p);
    for (int t = c.wg; t < 14; t += 2) {
      const int type = t >= 7 ? t - 7 : t;
      if (type < 2) tile_qkv(c, p, t);
      else if (type == 3) tile_up<192>(c, p, t);
      else if (type == 4 || type == 5) tile_up<128>(c, p, t);
      else tile_res(c, p, t);
    }
  }
}

typedef CUresult (*EncodeFn)(CUtensorMap*, CUtensorMapDataType, cuuint32_t, void*, const cuuint64_t*, const cuuint64_t*,
                             const cuuint32_t*, const cuuint32_t*, CUtensorMapInterleave, CUtensorMapSwizzle,
                             CUtensorMapL2promotion, CUtensorMapFloatOOBfill);

void make_map(EncodeFn fn, CUtensorMap* m, const void* ptr, int rank, const cuuint64_t* dims, const cuuint64_t* strides, const cuuint32_t* box) {
  const cuuint32_t es[3] = {1, 1, 1};
  fn(m, CU_TENSOR_MAP_DATA_TYPE_BFLOAT16, rank, const_cast<void*>(ptr), dims, strides, box, es, CU_TENSOR_MAP_INTERLEAVE_NONE,
     CU_TENSOR_MAP_SWIZZLE_128B, CU_TENSOR_MAP_L2_PROMOTION_L2_128B, CU_TENSOR_MAP_FLOAT_OOB_FILL_NONE);
}
void map2d(EncodeFn fn, CUtensorMap* m, const void* ptr, int cols, int rows, int box_rows) {
  const cuuint64_t dims[2] = {(cuuint64_t)cols, (cuuint64_t)rows}, st[1] = {(cuuint64_t)cols * 2};
  const cuuint32_t box[2] = {64, (cuuint32_t)box_rows};
  make_map(fn, m, ptr, 2, dims, st, box);
}
void map_w(EncodeFn fn, CUtensorMap* m, const void* ptr, int K, int N, int inner, int nch) {
  const cuuint64_t dims[3] = {(cuuint64_t)inner, (cuuint64_t)K, (cuuint64_t)(N / inner)}, st[2] = {(cuuint64_t)N * 2, (cuuint64_t)inner * 2};
  const cuuint32_t box[3] = {64, 64, (cuuint32_t)nch};
  make_map(fn, m, ptr, 3, dims, st, box);
}

}

extern "C" void kernel_launch(void* const* d_in, const int* in_sizes, int n_in, void* d_out, int out_size) {
  (void)in_sizes; (void)n_in; (void)out_size;
  Params p;
  p.x = (const __nv_bfloat16*)d_in[0]; p.wqkv = (const __nv_bfloat16*)d_in[1]; p.wo = (const __nv_bfloat16*)d_in[2];
  p.w1 = (const __nv_bfloat16*)d_in[4]; p.b1 = (const __nv_bfloat16*)d_in[5];
  p.w2 = (const __nv_bfloat16*)d_in[6]; p.b2 = (const __nv_bfloat16*)d_in[7];
  void* fnp = nullptr; cudaDriverEntryPointQueryResult qr;
  cudaGetDriverEntryPoint("cuTensorMapEncodeTiled", &fnp, cudaEnableDefault, &qr);
  EncodeFn fn = (EncodeFn)fnp;
  void *act, *h;
  cudaGetSymbolAddress(&act, g_act); cudaGetSymbolAddress(&h, g_h);
  map2d(fn, &p.ld_x, p.x, D_, S_, 128);
  map2d(fn, &p.ld_act, act, D_, 3 * S_, 128);
  map2d(fn, &p.ld_h, h, F_, S_, 128);
  map2d(fn, &p.st_act, act, D_, 3 * S_, 32);
  map2d(fn, &p.st_h, h, F_, S_, 32);
  map2d(fn, &p.st_out, d_out, D_, S_, 32);
  map_w(fn, &p.w_qkv, p.wqkv, D_, 3 * D_, D_, 3);
  map_w(fn, &p.w_o, p.wo, D_, D_, 64, 2);
  map_w(fn, &p.w_1a, p.w1, D_, F_, 64, 3);
  map_w(fn, &p.w_1b, p.w1, D_, F_, 64, 2);
  map_w(fn, &p.w_2, p.w2, F_, D_, 64, 2);
  cudaFuncSetAttribute(fused_kernel, cudaFuncAttributeMaxDynamicSharedMemorySize, SMEM_BYTES);
  fused_kernel<<<128, 384, SMEM_BYTES>>>(p);
}
```

```cpp
#include <cuda_runtime.h>
#include <cuda_bf16.h>
#include <cuda.h>
#include <stdint.h>

namespace {

constexpr int S_ = 2048, D_ = 1024, F_ = 3584;
constexpr int A_BYTES = 16384;
constexpr int OFF_X   = 163840;
constexpr int OFF_STG = OFF_X + 32768;
constexpr int OFF_CSQ = OFF_STG + 16384;
constexpr int OFF_UP  = OFF_CSQ + 1536;
constexpr int OFF_B2  = OFF_UP + 3584;
constexpr int OFF_RST = OFF_B2 + 512;
constexpr int OFF_RED = OFF_RST + 1024;
constexpr int OFF_FULL = OFF_RED + 1024;
constexpr int OFF_EMPTY = OFF_FULL + 64;
constexpr int OFF_XBAR = OFF_EMPTY + 64;
constexpr int OFF_ZERO = OFF_XBAR + 16;
constexpr int SMEM_BYTES = OFF_ZERO + 16 + 1024;
constexpr int KB_LAYER = 6 * 16 + 56;
constexpr int NCS = 3 * D_ + F_;
constexpr unsigned SPIN_LIMIT = 1u << 20;
constexpr int PAUSE1 = 7, PAUSE2 = 9;
enum { BAR_START = 1, BAR_EPI = 3, BAR_WG = 5, BAR_P0 = 7, BAR_P1 = 8, BAR_RES = 9 };

struct Params {
  CUtensorMap ld_x, ld_act, ld_h, st_act, st_h, st_out, w_qkv, w_o, w_1a, w_1b, w_2;
  const __nv_bfloat16 *wqkv, *wo, *w1, *b1, *w2, *b2;
};

__device__ __align__(1024) __nv_bfloat16 g_act[3 * S_ * D_];
__device__ __align__(1024) __nv_bfloat16 g_h[S_ * F_];
__device__ __align__(128) uint4 g_stats[4 * S_ * 8];
__device__ __align__(128) uint2 g_cs[2 * NCS];
__device__ __align__(128) uint4 g_halo[4 * 128 * 11 * 32];
__device__ __align__(128) unsigned g_flags[14 * 16 * 32];
__device__ unsigned g_epoch[128];
#define TL(t, e)

template<int N> __device__ __forceinline__ void wgmma_ss(float (&d)[96], uint64_t da, uint64_t db);
template<> __device__ __forceinline__ void wgmma_ss<128>(float (&d)[96], uint64_t da, uint64_t db) {
  asm volatile("{\n.reg .pred p;\nsetp.ne.b32 p, 1, 0;\nwgmma.mma_async.sync.aligned.m64n128k16.f32.bf16.bf16 {%0, %1, %2, %3, %4, %5, %6, %7, %8, %9, %10, %11, %12, %13, %14, %15, %16, %17, %18, %19, %20, %21, %22, %23, %24, %25, %26, %27, %28, %29, %30, %31, %32, %33, %34, %35, %36, %37, %38, %39, %40, %41, %42, %43, %44, %45, %46, %47, %48, %49, %50, %51, %52, %53, %54, %55, %56, %57, %58, %59, %60, %61, %62, %63}, %64, %65, p, 1, 1, 0, 1;\n}"
    : "+f"(d[0]), "+f"(d[1]), "+f"(d[2]), "+f"(d[3]), "+f"(d[4]), "+f"(d[5]), "+f"(d[6]), "+f"(d[7]), "+f"(d[8]), "+f"(d[9]), "+f"(d[10]), "+f"(d[11]), "+f"(d[12]), "+f"(d[13]), "+f"(d[14]), "+f"(d[15]), "+f"(d[16]), "+f"(d[17]), "+f"(d[18]), "+f"(d[19]), "+f"(d[20]), "+f"(d[21]), "+f"(d[22]), "+f"(d[23]), "+f"(d[24]), "+f"(d[25]), "+f"(d[26]), "+f"(d[27]), "+f"(d[28]), "+f"(d[29]), "+f"(d[30]), "+f"(d[31]), "+f"(d[32]), "+f"(d[33]), "+f"(d[34]), "+f"(d[35]), "+f"(d[36]), "+f"(d[37]), "+f"(d[38]), "+f"(d[39]), "+f"(d[40]), "+f"(d[41]), "+f"(d[42]), "+f"(d[43]), "+f"(d[44]), "+f"(d[45]), "+f"(d[46]), "+f"(d[47]), "+f"(d[48]), "+f"(d[49]), "+f"(d[50]), "+f"(d[51]), "+f"(d[52]), "+f"(d[53]), "+f"(d[54]), "+f"(d[55]), "+f"(d[56]), "+f"(d[57]), "+f"(d[58]), "+f"(d[59]), "+f"(d[60]), "+f"(d[61]), "+f"(d[62]), "+f"(d[63])
    : "l"(da), "l"(db));
}
template<> __device__ __forceinline__ void wgmma_ss<192>(float (&d)[96], uint64_t da, uint64_t db) {
  asm volatile("{\n.reg .pred p;\nsetp.ne.b32 p, 1, 0;\nwgmma.mma_async.sync.aligned.m64n192k16.f32.bf16.bf16 {%0, %1, %2, %3, %4, %5, %6, %7, %8, %9, %10, %11, %12, %13, %14, %15, %16, %17, %18, %19, %20, %21, %22, %23, %24, %25, %26, %27, %28, %29, %30, %31, %32, %33, %34, %35, %36, %37, %38, %39, %40, %41, %42, %43, %44, %45, %46, %47, %48, %49, %50, %51, %52, %53, %54, %55, %56, %57, %58, %59, %60, %61, %62, %63, %64, %65, %66, %67, %68, %69, %70, %71, %72, %73, %74, %75, %76, %77, %78, %79, %80, %81, %82, %83, %84, %85, %86, %87, %88, %89, %90, %91, %92, %93, %94, %95}, %96, %97, p, 1, 1, 0, 1;\n}"
    : "+f"(d[0]), "+f"(d[1]), "+f"(d[2]), "+f"(d[3]), "+f"(d[4]), "+f"(d[5]), "+f"(d[6]), "+f"(d[7]), "+f"(d[8]), "+f"(d[9]), "+f"(d[10]), "+f"(d[11]), "+f"(d[12]), "+f"(d[13]), "+f"(d[14]), "+f"(d[15]), "+f"(d[16]), "+f"(d[17]), "+f"(d[18]), "+f"(d[19]), "+f"(d[20]), "+f"(d[21]), "+f"(d[22]), "+f"(d[23]), "+f"(d[24]), "+f"(d[25]), "+f"(d[26]), "+f"(d[27]), "+f"(d[28]), "+f"(d[29]), "+f"(d[30]), "+f"(d[31]), "+f"(d[32]), "+f"(d[33]), "+f"(d[34]), "+f"(d[35]), "+f"(d[36]), "+f"(d[37]), "+f"(d[38]), "+f"(d[39]), "+f"(d[40]), "+f"(d[41]), "+f"(d[42]), "+f"(d[43]), "+f"(d[44]), "+f"(d[45]), "+f"(d[46]), "+f"(d[47]), "+f"(d[48]), "+f"(d[49]), "+f"(d[50]), "+f"(d[51]), "+f"(d[52]), "+f"(d[53]), "+f"(d[54]), "+f"(d[55]), "+f"(d[56]), "+f"(d[57]), "+f"(d[58]), "+f"(d[59]), "+f"(d[60]), "+f"(d[61]), "+f"(d[62]), "+f"(d[63]), "+f"(d[64]), "+f"(d[65]), "+f"(d[66]), "+f"(d[67]), "+f"(d[68]), "+f"(d[69]), "+f"(d[70]), "+f"(d[71]), "+f"(d[72]), "+f"(d[73]), "+f"(d[74]), "+f"(d[75]), "+f"(d[76]), "+f"(d[77]), "+f"(d[78]), "+f"(d[79]), "+f"(d[80]), "+f"(d[81]), "+f"(d[82]), "+f"(d[83]), "+f"(d[84]), "+f"(d[85]), "+f"(d[86]), "+f"(d[87]), "+f"(d[88]), "+f"(d[89]), "+f"(d[90]), "+f"(d[91]), "+f"(d[92]), "+f"(d[93]), "+f"(d[94]), "+f"(d[95])
    : "l"(da), "l"(db));
}

__device__ __forceinline__ uint32_t smem_u32(const void* p) { return (uint32_t)__cvta_generic_to_shared(p); }
__device__ __forceinline__ void mbar_init(uint32_t bar, uint32_t cnt) { asm volatile("mbarrier.init.shared::cta.b64 [%0], %1;" :: "r"(bar), "r"(cnt)); }
__device__ __forceinline__ void mbar_arrive_cluster(uint32_t bar) { asm volatile("mbarrier.arrive.shared::cluster.b64 _, [%0];" :: "r"(bar) : "memory"); }
__device__ __forceinline__ void mbar_wait(uint32_t bar, uint32_t parity) {
  asm volatile(
    "{\n.reg .pred p;\n.reg .u32 n;\n"
    "mbarrier.try_wait.parity.shared::cta.b64 p, [%0], %1;\n"
    "@p bra.uni WAIT_DONE;\n"
    "mov.u32 n, 0;\n"
    "WAIT_LOOP:\n"
    "mbarrier.try_wait.parity.shared::cta.b64 p, [%0], %1;\n"
    "@p bra.uni WAIT_DONE;\n"
    "add.u32 n, n, 1;\n"
    "setp.lt.u32 p, n, 0x100000;\n"
    "@p bra.uni WAIT_LOOP;\n"
    "trap;\n"
    "WAIT_DONE:\n}" :: "r"(bar), "r"(parity) : "memory");
}
#define ELECT "{\n.reg .pred p;\nelect.sync _|p, 0xffffffff;\n"
__device__ __forceinline__ void mbar_arrive_e(uint32_t bar) { asm volatile(ELECT "@p mbarrier.arrive.shared::cta.b64 _, [%0];\n}" :: "r"(bar) : "memory"); }
__device__ __forceinline__ void mbar_expect_e(uint32_t bar, uint32_t bytes) { asm volatile(ELECT "@p mbarrier.arrive.expect_tx.shared::cta.b64 _, [%0], %1;\n}" :: "r"(bar), "r"(bytes) : "memory"); }
__device__ __forceinline__ void tma_ld4_e(uint32_t dst, const CUtensorMap* m, uint32_t bar, int c0, int c3) {
  asm volatile(ELECT "@p cp.async.bulk.tensor.4d.shared::cluster.global.mbarrier::complete_tx::bytes [%0], [%1, {%3, %5, %5, %4}], [%2];\n}"
    :: "r"(dst), "l"(m), "r"(bar), "r"(c0), "r"(c3), "r"(0) : "memory");
}
__device__ __forceinline__ void tma_ld4_mc_e(uint32_t dst, const CUtensorMap* m, uint32_t bar, int c0, int c3) {
  asm volatile(ELECT "@p cp.async.bulk.tensor.4d.shared::cluster.global.mbarrier::complete_tx::bytes.multicast::cluster [%0], [%1, {%3, %5, %5, %4}], [%2], %6;\n}"
    :: "r"(dst), "l"(m), "r"(bar), "r"(c0), "r"(c3), "r"(0), "h"((uint16_t)3) : "memory");
}
__device__ __forceinline__ void tma_ld3_e(uint32_t dst, const CUtensorMap* m, uint32_t bar, int c0, int c1, int c2) {
  asm volatile(ELECT "@p cp.async.bulk.tensor.3d.shared::cluster.global.mbarrier::complete_tx::bytes [%0], [%1, {%3, %4, %5}], [%2];\n}"
    :: "r"(dst), "l"(m), "r"(bar), "r"(c0), "r"(c1), "r"(c2) : "memory");
}
__device__ __forceinline__ void tma_st4_e(const CUtensorMap* m, uint32_t src, int c0, int c3) {
  asm volatile(ELECT "@p cp.async.bulk.tensor.4d.global.shared::cta.bulk_group [%0, {%2, %4, %4, %3}], [%1];\n@p cp.async.bulk.commit_group;\n}"
    :: "l"(m), "r"(src), "r"(c0), "r"(c3), "r"(0) : "memory");
}
__device__ __forceinline__ void dsmem_copy_e(uint32_t dst, uint32_t src, uint32_t bar) {
  asm volatile(ELECT "@p cp.async.bulk.shared::cluster.shared::cta.mbarrier::complete_tx::bytes [%0], [%1], 4096, [%2];\n}"
    :: "r"(dst), "r"(src), "r"(bar) : "memory");
}
__device__ __forceinline__ void bulk_wait_read_e() { asm volatile(ELECT "@p cp.async.bulk.wait_group.read 0;\n}" ::: "memory"); __syncwarp(); }
__device__ __forceinline__ void publish_e(unsigned* flag) {
  asm volatile(ELECT "@p cp.async.bulk.wait_group 0;\n@p red.release.gpu.global.add.u32 [%0], 1;\n}" :: "l"(flag) : "memory");
  __syncwarp();
}
__device__ __forceinline__ void fence_async_smem() { asm volatile("fence.proxy.async.shared::cta;" ::: "memory"); }
__device__ __forceinline__ void wgmma_fence() { asm volatile("wgmma.fence.sync.aligned;" ::: "memory"); }
__device__ __forceinline__ void wgmma_commit() { asm volatile("wgmma.commit_group.sync.aligned;" ::: "memory"); }
template<int N> __device__ __forceinline__ void wgmma_wait() { asm volatile("wgmma.wait_group.sync.aligned %0;" :: "n"(N) : "memory"); }
__device__ __forceinline__ void bar_sync(int id, int n) { asm volatile("bar.sync %0, %1;" :: "r"(id), "r"(n) : "memory"); }
__device__ __forceinline__ void bar_arrive(int id, int n) { asm volatile("bar.arrive %0, %1;" :: "r"(id), "r"(n) : "memory"); }
__device__ __forceinline__ void bar_arrive_after(int id, uint32_t dep) {
  asm volatile("{\n.reg .u32 n;\nor.b32 n, %1, 256;\nmin.u32 n, n, 256;\nbar.arrive %0, n;\n}" :: "r"(id), "r"(dep) : "memory");
}
__device__ __forceinline__ void bar_sync_after(int id, uint32_t dep) {
  asm volatile("{\n.reg .u32 n;\nor.b32 n, %1, 256;\nmin.u32 n, n, 256;\nbar.sync %0, n;\n}" :: "r"(id), "r"(dep) : "memory");
}
__device__ __forceinline__ uint32_t mapa(uint32_t a, uint32_t r) { uint32_t d; asm("mapa.shared::cluster.u32 %0, %1, %2;" : "=r"(d) : "r"(a), "r"(r)); return d; }
__device__ __forceinline__ void st_tag128(uint4* p, uint32_t a, uint32_t b, uint32_t c, uint32_t tag) {
  asm volatile("{\n.reg .b64 lo, hi;\n.reg .b128 v;\nmov.b64 lo, {%1, %2};\nmov.b64 hi, {%3, %4};\nmov.b128 v, {lo, hi};\nst.relaxed.gpu.global.b128 [%0], v;\n}"
    :: "l"(p), "r"(a), "r"(b), "r"(c), "r"(tag) : "memory");
}
__device__ __forceinline__ uint4 ld_tag128(const uint4* p) {
  uint4 v;
  asm volatile("{\n.reg .b64 lo, hi;\n.reg .b128 v;\nld.relaxed.gpu.global.b128 v, [%4];\nmov.b128 {lo, hi}, v;\nmov.b64 {%0, %1}, lo;\nmov.b64 {%2, %3}, hi;\n}"
    : "=r"(v.x), "=r"(v.y), "=r"(v.z), "=r"(v.w) : "l"(p) : "memory");
  return v;
}
__device__ __forceinline__ void st_tag64(uint2* p, float a, uint32_t tag) {
  asm volatile("{\n.reg .b64 v;\nmov.b64 v, {%1, %2};\nst.relaxed.gpu.global.b64 [%0], v;\n}" :: "l"(p), "r"(__float_as_uint(a)), "r"(tag) : "memory");
}
__device__ __forceinline__ uint2 ld_tag64(const uint2* p) {
  uint2 v;
  asm volatile("{\n.reg .b64 v;\nld.relaxed.gpu.global.b64 v, [%2];\nmov.b64 {%0, %1}, v;\n}" : "=r"(v.x), "=r"(v.y) : "l"(p) : "memory");
  return v;
}
__device__ __forceinline__ uint32_t pack_bf16(float lo, float hi) { uint32_t r; asm("cvt.rn.bf16x2.f32 %0, %1, %2;" : "=r"(r) : "f"(hi), "f"(lo)); return r; }
__device__ __forceinline__ uint32_t relu_sq_bf16(float lo, float hi) {
  uint32_t r; asm("{\n.reg .b32 t;\ncvt.rn.relu.bf16x2.f32 t, %1, %2;\nmul.rn.bf16x2 %0, t, t;\n}" : "=r"(r) : "f"(hi), "f"(lo)); return r;
}
__device__ __forceinline__ float bf_lo(uint32_t u) { return __uint_as_float(u << 16); }
__device__ __forceinline__ float bf_hi(uint32_t u) { return __uint_as_float(u & 0xffff0000u); }
__device__ __forceinline__ void stmatrix4(uint32_t addr, uint32_t r0, uint32_t r1, uint32_t r2, uint32_t r3) {
  asm volatile("stmatrix.sync.aligned.m8n8.x4.shared.b16 [%0], {%1, %2, %3, %4};" :: "r"(addr), "r"(r0), "r"(r1), "r"(r2), "r"(r3) : "memory");
}
__device__ __forceinline__ void ldmatrix4(uint32_t addr, uint32_t (&r)[4]) {
  asm volatile("ldmatrix.sync.aligned.m8n8.x4.shared.b16 {%0, %1, %2, %3}, [%4];" : "=r"(r[0]), "=r"(r[1]), "=r"(r[2]), "=r"(r[3]) : "r"(addr) : "memory");
}
__device__ __forceinline__ uint32_t movmatrix(uint32_t a) { uint32_t d; asm volatile("movmatrix.sync.aligned.m8n8.trans.b16 %0, %1;" : "=r"(d) : "r"(a)); return d; }
__device__ __forceinline__ void mma16816_z(float (&c)[4], uint32_t a0, uint32_t a1, uint32_t a2, uint32_t a3, uint32_t b0, uint32_t b1, const float4& z) {
  asm volatile("mma.sync.aligned.m16n8k16.row.col.f32.bf16.bf16.f32 {%0,%1,%2,%3}, {%4,%5,%6,%7}, {%8,%9}, {%10,%11,%12,%13};"
    : "=f"(c[0]), "=f"(c[1]), "=f"(c[2]), "=f"(c[3]) : "r"(a0), "r"(a1), "r"(a2), "r"(a3), "r"(b0), "r"(b1), "f"(z.x), "f"(z.y), "f"(z.z), "f"(z.w));
}
__device__ __forceinline__ void mma1688_z(float (&c)[4], uint32_t a0, uint32_t a1, uint32_t b0, const float4& z) {
  asm volatile("mma.sync.aligned.m16n8k8.row.col.f32.bf16.bf16.f32 {%0,%1,%2,%3}, {%4,%5}, {%6}, {%7,%8,%9,%10};"
    : "=f"(c[0]), "=f"(c[1]), "=f"(c[2]), "=f"(c[3]) : "r"(a0), "r"(a1), "r"(b0), "f"(z.x), "f"(z.y), "f"(z.z), "f"(z.w));
}
__device__ __forceinline__ float ex2(float x) { float y; asm("ex2.approx.ftz.f32 %0, %1;" : "=f"(y) : "f"(x)); return y; }
__device__ __forceinline__ float rcp(float x) { float y; asm("rcp.approx.ftz.f32 %0, %1;" : "=f"(y) : "f"(x)); return y; }
__device__ __forceinline__ void mma16816(float (&c)[4], uint32_t a0, uint32_t a1, uint32_t a2, uint32_t a3, uint32_t b0, uint32_t b1) {
  asm volatile("mma.sync.aligned.m16n8k16.row.col.f32.bf16.bf16.f32 {%0,%1,%2,%3}, {%4,%5,%6,%7}, {%8,%9}, {%0,%1,%2,%3};"
    : "+f"(c[0]), "+f"(c[1]), "+f"(c[2]), "+f"(c[3]) : "r"(a0), "r"(a1), "r"(a2), "r"(a3), "r"(b0), "r"(b1));
}
__device__ __forceinline__ void mma1688(float (&c)[4], uint32_t a0, uint32_t a1, uint32_t b0) {
  asm volatile("mma.sync.aligned.m16n8k8.row.col.f32.bf16.bf16.f32 {%0,%1,%2,%3}, {%4,%5}, {%6}, {%0,%1,%2,%3};"
    : "+f"(c[0]), "+f"(c[1]), "+f"(c[2]), "+f"(c[3]) : "r"(a0), "r"(a1), "r"(b0));
}
__device__ __forceinline__ void sts128(uint32_t a, uint32_t x, uint32_t y, uint32_t z, uint32_t w) { asm volatile("st.shared.v4.b32 [%0], {%1,%2,%3,%4};" :: "r"(a), "r"(x), "r"(y), "r"(z), "r"(w) : "memory"); }
__device__ __forceinline__ uint4 lds128(uint32_t a) { uint4 v; asm volatile("ld.shared.v4.b32 {%0,%1,%2,%3}, [%4];" : "=r"(v.x), "=r"(v.y), "=r"(v.z), "=r"(v.w) : "r"(a) : "memory"); return v; }
__device__ __forceinline__ float2 lds64f(uint32_t a) { float2 v; asm volatile("ld.shared.v2.f32 {%0,%1}, [%2];" : "=f"(v.x), "=f"(v.y) : "r"(a) : "memory"); return v; }
__device__ __forceinline__ float4 lds128f(uint32_t a) { float4 v; asm volatile("ld.shared.v4.f32 {%0,%1,%2,%3}, [%4];" : "=f"(v.x), "=f"(v.y), "=f"(v.z), "=f"(v.w) : "r"(a) : "memory"); return v; }
__device__ __forceinline__ void sts32f(uint32_t a, float v) { asm volatile("st.shared.f32 [%0], %1;" :: "r"(a), "f"(v) : "memory"); }
__device__ __forceinline__ void sts64f(uint32_t a, float x, float y) { asm volatile("st.shared.v2.f32 [%0], {%1,%2};" :: "r"(a), "f"(x), "f"(y) : "memory"); }
__device__ __forceinline__ float lds32f(uint32_t a) { float v; asm volatile("ld.shared.f32 %0, [%1];" : "=f"(v) : "r"(a) : "memory"); return v; }
template<int R> __device__ __forceinline__ void reg_alloc() { asm volatile("setmaxnreg.inc.sync.aligned.u32 %0;" :: "n"(R)); }
template<int R> __device__ __forceinline__ void reg_dealloc() { asm volatile("setmaxnreg.dec.sync.aligned.u32 %0;" :: "n"(R)); }

struct Ctx {
  uint32_t sb;
  int m, j, b, rank, wg, w, lane;
  unsigned tag;
};

__device__ __forceinline__ int first_stage(int type) { return (0x2100433 >> (4 * type)) & 7; }

template<int BN>
__device__ __forceinline__ void mainloop(const Ctx& c, float (&acc)[2][96], int t, int type, int g, int nkb) {
  constexpr int NS = BN == 192 ? 4 : 5, STR = BN == 192 ? 40960 : 32768;
  int st = first_stage(type);
  const bool own = BN == 192 && (type == 3 || t == 7);
  const uint32_t rel = mapa(c.sb + OFF_EMPTY, c.lane & 1);
  const uint32_t sb = c.sb & 0x3ffffu;
  TL(t, 0);
  if (t > 0) bar_sync(BAR_START + c.wg, 256);
  TL(t, 1);
#pragma unroll 1
  for (int kb = 0; kb < nkb; kb++, g++) {
    mbar_wait(c.sb + OFF_FULL + 8 * (g & 7), (g >> 3) & 1);
    const uint32_t s = sb + st * STR;
    const uint32_t a = (own && kb < 2) ? sb + OFF_X + kb * A_BYTES : s;
    const uint64_t da = (uint64_t)((a >> 4) | (1u << 16)) | ((uint64_t)(128u | (1u << 30)) << 32);
    const uint64_t db = (uint64_t)(((s + A_BYTES) >> 4) | (512u << 16)) | ((uint64_t)(64u | (1u << 30)) << 32);
    wgmma_fence();
    wgmma_ss<BN>(acc[0], da, db);
    wgmma_ss<BN>(acc[1], da + 64, db);
    wgmma_commit();
    wgmma_wait<1>();
    if (kb > 0 && c.lane < 2) mbar_arrive_cluster(rel + 8 * ((g - 1) & 7));
    wgmma_fence();
#pragma unroll
    for (int k = 1; k < 4; k++) {
      if (k == 3 && kb == nkb - 1 && t < 13 && type != 1) bar_arrive(BAR_START + (c.wg ^ 1), 256);
      wgmma_ss<BN>(acc[0], da + k * 2, db + k * 128);
      wgmma_ss<BN>(acc[1], da + (64 + k * 2), db + k * 128);
    }
    wgmma_commit();
    if (BN == 192 && type == 1 && (kb == PAUSE1 || kb == PAUSE2)) { bar_sync(BAR_P0, 256); bar_sync(BAR_P1, 256); }
    if (++st == NS) st = 0;
  }
  wgmma_wait<0>();
  if (c.lane < 2) mbar_arrive_cluster(rel + 8 * ((g - 1) & 7));
  TL(t, 3);
}

__device__ __forceinline__ void load_row_stats(const Ctx& c, int ln) {
  const uint4* p = g_stats + ((size_t)ln * S_ + c.m * 128 + c.w * 32 + c.lane) * 8;
  float s, q;
  for (unsigned it = 0;; it++) {
    uint4 v[8];
#pragma unroll
    for (int i = 0; i < 8; i++) v[i] = ld_tag128(p + i);
    bool ok = true;
    s = 0.f; q = 0.f;
#pragma unroll
    for (int i = 0; i < 8; i++) { ok = ok && v[i].w == c.tag; s += __uint_as_float(v[i].x); q += __uint_as_float(v[i].y); }
    if (__all_sync(0xffffffffu, ok) || it > SPIN_LIMIT) break;
  }
  const float mean = s * (1.0f / D_);
  const float var = fmaxf(q * (1.0f / D_) - mean * mean, 0.0f);
  sts64f(c.sb + OFF_RST + (c.w * 32 + c.lane) * 8, rsqrtf(var + 1e-5f), -mean);
  __syncwarp();
}

__device__ __forceinline__ void epi_qkv(const Ctx& c, const Params& p, float (&acc)[2][96], int t, int q) {
  const int lane = c.lane, w = c.w, g = lane >> 2, cc = lane & 3;
  const int layer = t >= 7;
  float rs[4], nm[4], mu[4];
#pragma unroll
  for (int r = 0; r < 4; r++) { const float2 v = lds64f(c.sb + OFF_RST + (w * 32 + 8 * r + g) * 8); rs[r] = v.x; mu[r] = v.y; nm[r] = v.x * v.y; }
  uint32_t P[3][2][4][4];
  const uint32_t csb = c.sb + OFF_CSQ + q * 768 + cc * 8;
  const uint32_t stg = c.sb + OFF_STG + w * 4096;
  uint4* const halo = g_halo + ((layer * 2 + q) * 128 + c.b) * 352 + lane;
#pragma unroll
  for (int i = 1; i >= 0; i--) {
#pragma unroll
    for (int nt = 8; nt < 24; nt++) {
      const float2 cs = lds64f(csb + nt * 32);
#pragma unroll
      for (int h = 0; h < 2; h++) {
        const int r = 2 * h + i;
        uint32_t u = pack_bf16(fmaf(acc[i][4 * nt + 2 * h], rs[r], cs.x * nm[r]), fmaf(acc[i][4 * nt + 2 * h + 1], rs[r], cs.y * nm[r]));
        if (nt >= 16) u = movmatrix(u);
        P[nt >> 3][(nt >> 2) & 1][r][nt & 3] = u;
      }
    }
    if (i == 1) {
#define HW(n) P[1 + (((n) >> 4) & 1)][((n) >> 3) & 1][(((n) >> 2) & 1) * 2 + 1][(n) & 3]
      if (w < 3) {
#pragma unroll
        for (int z = 0; z < 8; z++) sts128(stg + 4096 + lane * 16 + z * 512, HW(4 * z), HW(4 * z + 1), HW(4 * z + 2), HW(4 * z + 3));
      } else if (c.m < 15) {
#pragma unroll
        for (int z = 0; z < 11; z++) st_tag128(halo + z * 32, HW(3 * z), HW(3 * z + 1), HW(3 * z + 2), c.tag);
      }
#undef HW
    }
  }
#pragma unroll
  for (int nt = 0; nt < 8; nt++) {
    const float2 cs = lds64f(csb + nt * 32);
#pragma unroll
    for (int r = 0; r < 4; r++)
      P[0][nt >> 2][r][nt & 3] = pack_bf16(fmaf(cs.x, mu[r], acc[r & 1][4 * nt + 2 * (r >> 1)]), fmaf(cs.y, mu[r], acc[r & 1][4 * nt + 2 * (r >> 1) + 1]));
  }
  bar_sync(BAR_WG + c.wg, 128);
  const bool nohalo = (w == 0 && c.m == 0);
  if (w == 0) {
    uint32_t G[33];
#pragma unroll
    for (int z = 0; z < 33; z++) G[z] = 0u;
    for (unsigned it = 0; !nohalo; it++) {
      bool ok = true;
#pragma unroll
      for (int z = 0; z < 11; z++) { const uint4 v = ld_tag128(halo - 8 * 352 + z * 32); G[3 * z] = v.x; G[3 * z + 1] = v.y; G[3 * z + 2] = v.z; ok = ok && v.w == c.tag; }
      if (__all_sync(0xffffffffu, ok) || it > SPIN_LIMIT) break;
    }
#pragma unroll
    for (int z = 0; z < 8; z++) sts128(stg + lane * 16 + z * 512, G[4 * z], G[4 * z + 1], G[4 * z + 2], G[4 * z + 3]);
  }
  uint32_t H[32];
#pragma unroll
  for (int z = 0; z < 8; z++) { const uint4 v = lds128(stg + lane * 16 + z * 512); H[4 * z] = v.x; H[4 * z + 1] = v.y; H[4 * z + 2] = v.z; H[4 * z + 3] = v.w; }
  TL(t, 4);
  float S[4][3][4];
  if (q == 0) bar_sync(BAR_P0, 256);
  float4 zero = lds128f(c.sb + OFF_ZERO);
#pragma unroll
  for (int k = 0; k < 2; k++)
#pragma unroll
    for (int z = 0; z < 4; z++) {
      const uint32_t* qa = P[0][z >> 1][2 * (z & 1)]; const uint32_t* qb = P[0][z >> 1][2 * (z & 1) + 1];
      const uint32_t* kk[3] = {H + 4 * z, P[1][z >> 1][2 * (z & 1)], P[1][z >> 1][2 * (z & 1) + 1]};
#pragma unroll
      for (int n = 0; n < 3; n++) {
        if (k == 0) mma16816_z(S[z][n], qa[0], qb[0], qa[1], qb[1], kk[n][0], kk[n][1], zero);
        else mma16816(S[z][n], qa[2], qb[2], qa[3], qb[3], kk[n][2], kk[n][3]);
      }
    }
  if (q == 0) {
    uint32_t dep = 0;
#pragma unroll
    for (int z = 0; z < 12; z++) dep |= __float_as_uint(S[z / 3][z % 3][0]);
    bar_arrive_after(BAR_P1, dep);
  }
  const bool far0 = 2 * cc > g, far1 = 2 * cc + 1 > g;
  const uint32_t fmask = (far0 ? 0xffffu : 0u) | (far1 ? 0xffff0000u : 0u);
  uint32_t pf[4][2], pn[4][2];
#pragma unroll
  for (int z = 0; z < 4; z++)
#pragma unroll
    for (int i = 0; i < 2; i++) {
      const float sc = rs[2 * (z & 1) + i] * (0.17677669529663687f * 1.4426950408889634f);
      float l0 = (far0 ? S[z][i][2 * i] : S[z][i + 1][2 * i]) * sc;
      float l1 = (far1 ? S[z][i][2 * i + 1] : S[z][i + 1][2 * i + 1]) * sc;
      if (i == 0 && nohalo) { const float neg = -1e9f * 1.4426950408889634f; if (far0) l0 = neg; if (far1) l1 = neg; }
      float mx = fmaxf(l0, l1);
      mx = fmaxf(mx, __shfl_xor_sync(0xffffffffu, mx, 1));
      mx = fmaxf(mx, __shfl_xor_sync(0xffffffffu, mx, 2));
      l0 = ex2(l0 - mx); l1 = ex2(l1 - mx);
      float sum = l0 + l1;
      sum += __shfl_xor_sync(0xffffffffu, sum, 1);
      sum += __shfl_xor_sync(0xffffffffu, sum, 2);
      sum = rcp(sum);
      const uint32_t u = pack_bf16(l0 * sum, l1 * sum);
      pf[z][i] = u & fmask; pn[z][i] = u & ~fmask;
    }
  float O[4][4][4];
  if (q == 0) bar_sync_after(BAR_P0, (pn[0][0] | pn[0][1] | pn[1][0]) | (pn[1][1] | pn[2][0] | pn[2][1]) | (pn[3][0] | pn[3][1]));
  zero = lds128f(c.sb + OFF_ZERO);
#pragma unroll
  for (int z = 0; z < 4; z++)
#pragma unroll
    for (int dt = 0; dt < 4; dt++) mma1688_z(O[z][dt], pn[z][0], pf[z][1], P[2][z >> 1][2 * (z & 1)][dt], zero);
#pragma unroll
  for (int z = 0; z < 4; z++)
#pragma unroll
    for (int dt = 0; dt < 4; dt++) mma1688(O[z][dt], pf[z][0], 0u, H[16 + 4 * z + dt]);
#pragma unroll
  for (int z = 0; z < 4; z++)
#pragma unroll
    for (int dt = 0; dt < 4; dt++) mma1688(O[z][dt], 0u, pn[z][1], P[2][z >> 1][2 * (z & 1) + 1][dt]);
  {
    uint32_t dep = 0;
#pragma unroll
    for (int z = 0; z < 16; z++) dep |= __float_as_uint(O[z >> 2][z & 3][2]);
    bar_arrive_after(q == 0 ? BAR_P1 : BAR_START + (c.wg ^ 1), dep);
  }
  TL(t, 5);
#pragma unroll
  for (int nt = 0; nt < 8; nt++) {
    const float* e = O[2 * (nt >> 2)][nt & 3]; const float* o = O[2 * (nt >> 2) + 1][nt & 3];
    stmatrix4(stg + lane * 128 + ((nt ^ (lane & 7)) << 4), pack_bf16(e[0], e[1]), pack_bf16(e[2], e[3]), pack_bf16(o[0], o[1]), pack_bf16(o[2], o[3]));
  }
  fence_async_smem();
  __syncwarp();
  tma_st4_e(&p.st_act, stg, (c.j + 8 * q) * 64, 2 * (S_ / 32) + c.m * 4 + w);
}

__device__ __forceinline__ void epi_up(const Ctx& c, const Params& p, float (&acc)[2][96], int t, int type) {
  const int lane = c.lane, w = c.w, g = lane >> 2, cc = lane & 3;
  float rs[4], nm[4];
#pragma unroll
  for (int r = 0; r < 4; r++) { const float2 v = lds64f(c.sb + OFF_RST + (w * 32 + 8 * r + g) * 8); rs[r] = v.x; nm[r] = v.x * v.y; }
  const int loc0 = type == 3 ? 0 : (type == 4 ? 192 : 320);
  const int col0 = type == 3 ? c.j * 192 : (type == 4 ? 1536 : 2560) + c.j * 128;
  const uint32_t cb = c.sb + OFF_UP + loc0 * 8 + cc * 16;
  const uint32_t stg = c.sb + OFF_STG + w * 4096;
#pragma unroll
  for (int ch = 0; ch < 3; ch++) {
    if (ch == 2 && type != 3) break;
    uint32_t P[8][4];
#pragma unroll
    for (int n8 = 0; n8 < 8; n8++) {
      const int nt = ch * 8 + n8;
      const float4 cv = lds128f(cb + nt * 64);
#pragma unroll
      for (int r = 0; r < 4; r++)
        P[n8][r] = relu_sq_bf16(fmaf(acc[r & 1][4 * nt + 2 * (r >> 1)], rs[r], fmaf(cv.x, nm[r], cv.z)),
                                fmaf(acc[r & 1][4 * nt + 2 * (r >> 1) + 1], rs[r], fmaf(cv.y, nm[r], cv.w)));
    }
    if (ch > 0) bulk_wait_read_e();
#pragma unroll
    for (int n8 = 0; n8 < 8; n8++)
      stmatrix4(stg + lane * 128 + ((n8 ^ (lane & 7)) << 4), P[n8][0], P[n8][1], P[n8][2], P[n8][3]);
    fence_async_smem();
    __syncwarp();
    tma_st4_e(&p.st_h, stg, col0 + ch * 64, c.m * 4 + w);
  }
  TL(t, 4);
}

__device__ __forceinline__ void init_res(const Ctx& c, float (&acc)[2][96], int t, bool bias) {
  if (t <= 2) mbar_wait(c.sb + OFF_XBAR, 0);
  const uint32_t xb = c.sb + OFF_X + c.w * 4096 + c.lane * 128;
#pragma unroll
  for (int nt = 0; nt < 16; nt++) {
    uint32_t u[4];
    ldmatrix4(xb + (nt >> 3) * A_BYTES + (((nt & 7) ^ (c.lane & 7)) << 4), u);
    float2 b = make_float2(0.f, 0.f);
    if (bias) b = lds64f(c.sb + OFF_B2 + nt * 32 + (c.lane & 3) * 8);
#pragma unroll
    for (int r = 0; r < 4; r++) {
      acc[r & 1][4 * nt + 2 * (r >> 1)] = bf_lo(u[r]) + b.x;
      acc[r & 1][4 * nt + 2 * (r >> 1) + 1] = bf_hi(u[r]) + b.y;
    }
  }
}

__device__ __forceinline__ void epi_res(const Ctx& c, const Params& p, float (&acc)[2][96], int t, int g1) {
  const int lane = c.lane, w = c.w;
  const uint32_t xw = c.sb + OFF_X + w * 4096;
  const CUtensorMap* mp = t == 13 ? &p.st_out : &p.st_act;
  const int slab = (t == 6 ? S_ / 32 : 0) + c.m * 4 + w;
  const uint32_t peer = mapa(c.sb, c.rank ^ 1);
#pragma unroll
  for (int ch = 0; ch < 2; ch++) {
#pragma unroll
    for (int n8 = 0; n8 < 8; n8++) {
      const int nt = ch * 8 + n8;
      stmatrix4(xw + ch * A_BYTES + lane * 128 + ((n8 ^ (lane & 7)) << 4),
                pack_bf16(acc[0][4 * nt], acc[0][4 * nt + 1]), pack_bf16(acc[1][4 * nt], acc[1][4 * nt + 1]),
                pack_bf16(acc[0][4 * nt + 2], acc[0][4 * nt + 3]), pack_bf16(acc[1][4 * nt + 2], acc[1][4 * nt + 3]));
    }
    fence_async_smem();
    if (t < 13) {
      if (w == 0) { bar_sync(BAR_RES + ch, 128); mbar_arrive_e(c.sb + OFF_FULL + 8 * ((g1 + ch) & 7)); }
      else bar_arrive(BAR_RES + ch, 128);
    }
    __syncwarp();
    tma_st4_e(mp, xw + ch * A_BYTES, c.j * 128 + ch * 64, slab);
    if (t < 13) {
      if (ch == 0) mbar_wait(c.sb + OFF_EMPTY + 8 * ((g1 - 1) & 7), ((g1 - 1) >> 3) & 1);
      dsmem_copy_e(peer + ((t == 6 ? 1 : 2) + ch) * 40960 + w * 4096, xw + ch * A_BYTES, peer + OFF_FULL + 8 * ((g1 + 2 + ch) & 7));
    }
  }
  TL(t, 4);
}

__device__ __forceinline__ void row_stats(const Ctx& c, float (&acc)[2][96], int ln) {
  const int g = c.lane >> 2, cc = c.lane & 3;
  float sm[4], sq[4];
#pragma unroll
  for (int r = 0; r < 4; r++) {
    float a = 0.f, b = 0.f;
#pragma unroll
    for (int n = 0; n < 32; n++) { const float x = acc[r & 1][4 * (n >> 1) + 2 * (r >> 1) + (n & 1)]; a += x; b = fmaf(x, x, b); }
    a += __shfl_xor_sync(0xffffffffu, a, 1); b += __shfl_xor_sync(0xffffffffu, b, 1);
    a += __shfl_xor_sync(0xffffffffu, a, 2); b += __shfl_xor_sync(0xffffffffu, b, 2);
    sm[r] = a; sq[r] = b;
  }
  const float a = cc == 0 ? sm[0] : cc == 1 ? sm[1] : cc == 2 ? sm[2] : sm[3];
  const float b = cc == 0 ? sq[0] : cc == 1 ? sq[1] : cc == 2 ? sq[2] : sq[3];
  st_tag128(g_stats + ((size_t)ln * S_ + c.m * 128 + c.w * 32 + 8 * cc + g) * 8 + c.j, __float_as_uint(a), __float_as_uint(b), 0u, c.tag);
}

__device__ __forceinline__ void colsum_piece(const Ctx& c, const __nv_bfloat16* W, int ldw, uint2* out) {
  const int tid = c.w * 32 + c.lane;
  const int chunk = c.b >> 1, half = c.b & 1;
  const uint4* src = reinterpret_cast<const uint4*>(W + (size_t)(half * 512 + (tid >> 3)) * ldw + chunk * 64 + (tid & 7) * 8);
  float a[8] = {0, 0, 0, 0, 0, 0, 0, 0};
#pragma unroll 1
  for (int o = 0; o < 2; o++) {
    uint4 v[16];
#pragma unroll
    for (int i = 0; i < 16; i++) { v[i] = __ldg(src); src += 2 * ldw; }
#pragma unroll
    for (int i = 0; i < 16; i++) {
      a[0] += bf_lo(v[i].x); a[1] += bf_hi(v[i].x); a[2] += bf_lo(v[i].y); a[3] += bf_hi(v[i].y);
      a[4] += bf_lo(v[i].z); a[5] += bf_hi(v[i].z); a[6] += bf_lo(v[i].w); a[7] += bf_hi(v[i].w);
    }
  }
#pragma unroll
  for (int e = 0; e < 8; e++) { a[e] += __shfl_xor_sync(0xffffffffu, a[e], 8); a[e] += __shfl_xor_sync(0xffffffffu, a[e], 16); }
  const uint32_t red = c.sb + OFF_RED;
  if (c.lane < 8) {
    sts128(red + (c.w * 64 + c.lane * 8) * 4, __float_as_uint(a[0]), __float_as_uint(a[1]), __float_as_uint(a[2]), __float_as_uint(a[3]));
    sts128(red + (c.w * 64 + c.lane * 8) * 4 + 16, __float_as_uint(a[4]), __float_as_uint(a[5]), __float_as_uint(a[6]), __float_as_uint(a[7]));
  }
  bar_sync(BAR_WG + c.wg, 128);
  if (tid < 64) {
    const float s = (lds32f(red + tid * 4) + lds32f(red + (64 + tid) * 4)) + (lds32f(red + (128 + tid) * 4) + lds32f(red + (192 + tid) * 4));
    st_tag64(out + half * NCS + chunk * 64 + tid, s, c.tag);
  }
  __syncwarp();
}

__device__ __forceinline__ void load_tables(const Ctx& c, const Params& p, bool mlp) {
  const int tid = c.w * 32 + c.lane;
  int col[4]; uint32_t dst[4]; float v[4];
#pragma unroll
  for (int k = 0; k < 4; k++) {
    const int i = min(tid + k * 128, mlp ? 447 : 383);
    const int qq = i >= 192, rem = i - qq * 192;
    const int cu = i < 192 ? c.j * 192 + i : (i < 320 ? 1536 - 192 : 2560 - 320) + c.j * 128 + i;
    const uint32_t a = c.sb + OFF_UP + (i >> 1) * 16 + (i & 1) * 4;
    if (mlp) sts32f(a + 8, __bfloat162float(p.b1[cu]));
    col[k] = mlp ? 3 * D_ + cu : (rem >> 6) * D_ + (c.j + 8 * qq) * 64 + (rem & 63);
    dst[k] = mlp ? a : c.sb + OFF_CSQ + i * 4;
  }
  sts32f(c.sb + OFF_B2 + tid * 4, __bfloat162float(p.b2[c.j * 128 + tid]));
  for (unsigned it = 0;; it++) {
    bool ok = true;
#pragma unroll
    for (int k = 0; k < 4; k++) {
      const uint2 a = ld_tag64(g_cs + col[k]), b = ld_tag64(g_cs + NCS + col[k]);
      ok = ok && a.y == c.tag && b.y == c.tag;
      v[k] = __uint_as_float(a.x) + __uint_as_float(b.x);
    }
    if (__all_sync(0xffffffffu, ok) || it > SPIN_LIMIT) break;
  }
#pragma unroll
  for (int k = 0; k < 4; k++) sts32f(dst[k], v[k]);
}

__global__ void __cluster_dims__(2, 1, 1) __launch_bounds__(384, 1) fused_kernel(const __grid_constant__ Params p) {
  extern __shared__ uint8_t smem_raw[];
  Ctx c;
  c.sb = (smem_u32(smem_raw) + 1023) & ~1023u;
  const int tid = threadIdx.x;
  c.wg = __shfl_sync(0xffffffffu, tid >> 7, 0); c.w = __shfl_sync(0xffffffffu, (tid >> 5) & 3, 0); c.lane = tid & 31;
  {
    const int cl = blockIdx.x >> 1, u = cl - 4;
    const int grp = cl < 4 ? 0 : u < 32 ? u & 7 : 1 + (u - 32) % 7;
    const int idx = cl < 4 ? cl + 4 : u < 32 ? u >> 3 : 4 + (u - 32) / 7;
    c.rank = blockIdx.x & 1;
    c.m = (grp >> 2) * 8 + idx; c.j = (grp & 3) * 2 + c.rank; c.b = c.m * 8 + c.j;
  }
  c.tag = __ldcg(g_epoch + blockIdx.x) + 1;
  if (tid == 0) {
#pragma unroll
    for (int s = 0; s < 8; s++) { mbar_init(c.sb + OFF_FULL + 8 * s, 2); mbar_init(c.sb + OFF_EMPTY + 8 * s, 8); }
    mbar_init(c.sb + OFF_XBAR, 1);
    sts128(c.sb + OFF_ZERO, 0u, 0u, 0u, 0u);
    asm volatile("fence.mbarrier_init.release.cluster;" ::: "memory");
  }
  asm volatile("barrier.cluster.arrive.release.aligned;\nbarrier.cluster.wait.acquire.aligned;" ::: "memory");
  if (c.wg == 2) {
    reg_dealloc<40>();
    if (c.w < 2) {
      int g = 0;
#pragma unroll 1
      for (int t = 0; t < 14; t++) {
        const int layer = t >= 7, type = t - layer * 7;
        const bool wide = type < 2 || type == 3, own = type == 3 || t == 7;
        const int nkb = type == 6 ? 56 : 16, ns = wide ? 4 : 5, str = wide ? 40960 : 32768;
        const int nshort = type == 0 ? 3 : (type == 2 || type == 4) ? 4 : 0;
        int st = first_stage(type);
        if (c.w == 0) {
          const CUtensorMap* mp = type == 6 ? &p.ld_h : (t < 2 ? &p.ld_x : &p.ld_act);
          const int slab = c.m * 4 + c.rank * 2 + (type == 2 ? 2 * (S_ / 32) : (type < 2 && layer ? S_ / 32 : 0));
          int dep = own ? t - 1 : type == 2 ? t - 2 : t - 3;
          int next = own ? 4 : (type == 2 || type == 6) ? 0 : -1;
#pragma unroll 1
          for (int step = 0; step < nkb; step++, g++) {
            if (step == next) {
              const unsigned* fp = g_flags + (dep * 16 + c.m) * 32;
              for (unsigned it = 0;; it++) {
                unsigned v; asm volatile("ld.acquire.gpu.global.u32 %0, [%1];" : "=r"(v) : "l"(fp) : "memory");
                if (__all_sync(0xffffffffu, (int)(v - 32 * c.tag) >= 0) || it > SPIN_LIMIT) break;
              }
              asm volatile("fence.proxy.async.global;" ::: "memory");
              dep++;
              next = type == 2 ? step + 8 : step == 0 ? 24 : step + 16;
            }
            const int e = g - (step < nshort ? ns - 1 : ns);
            if (e >= 0) mbar_wait(c.sb + OFF_EMPTY + 8 * (e & 7), (e >> 3) & 1);
            const uint32_t full = c.sb + OFF_FULL + 8 * (g & 7);
            if (!own || step >= 2) mbar_expect_e(full, A_BYTES);
            if (!own || step >= 4) tma_ld4_mc_e(c.sb + st * str + c.rank * 8192, mp, full, (own ? ((c.j >> 1) * 4 + step) & 15 : step) * 64, slab);
            if (++st == ns) st = 0;
          }
        } else {
          const CUtensorMap* mp = type < 2 ? &p.w_qkv : type == 2 ? &p.w_o : type == 3 ? &p.w_1a : type < 6 ? &p.w_1b : &p.w_2;
          const int c0 = type < 2 ? (c.j + 8 * type) * 64 : 0;
          const int c2 = type < 2 ? 0 : type == 3 ? 3 * c.j : type == 4 ? 24 + 2 * c.j : type == 5 ? 40 + 2 * c.j : 2 * c.j;
#pragma unroll 1
          for (int step = 0; step < nkb; step++, g++) {
            const int e = g - (step < nshort ? ns - 1 : ns);
            if (e >= 0) mbar_wait(c.sb + OFF_EMPTY + 8 * (e & 7), (e >> 3) & 1);
            const uint32_t full = c.sb + OFF_FULL + 8 * (g & 7);
            const int kb = own ? ((c.j >> 1) * 4 + (step < 4 ? step ^ (2 * c.rank) : step)) & 15 : step;
            mbar_expect_e(full, str - A_BYTES);
            tma_ld3_e(c.sb + st * str + A_BYTES, mp, full, c0, kb * 64, c2);
            if (++st == ns) st = 0;
          }
        }
      }
    } else if (c.w == 2) {
      mbar_expect_e(c.sb + OFF_XBAR, 32768);
#pragma unroll
      for (int i = 0; i < 4; i++) tma_ld4_e(c.sb + OFF_X + i * 8192, &p.ld_x, c.sb + OFF_XBAR, c.j * 128 + (i >> 1) * 64, c.m * 4 + (i & 1) * 2);
    }
  } else {
    reg_alloc<232>();
#pragma unroll 1
    for (int t = -c.wg; t < 14; t += 2) {
      const int layer = t >= 7, type = t - layer * 7;
      const bool res = t < 0 || type == 2 || type == 6;
      float acc[2][96];
#pragma unroll
      for (int i = 0; i < 96; i++) { acc[0][i] = 0.f; acc[1][i] = 0.f; }
      if (res) init_res(c, acc, t, type == 6);
      const int g0 = layer * KB_LAYER + type * 16, nkb = type == 6 ? 56 : 16;
      if (t >= 0) {
        if (type < 2 || type == 3) mainloop<192>(c, acc, t, type, g0, nkb);
        else mainloop<128>(c, acc, t, type, g0, nkb);
      }
      if (res) {
        if (t == 13) asm volatile("barrier.cluster.arrive.relaxed.aligned;" ::: "memory");
        if (t >= 0) epi_res(c, p, acc, t, g0 + nkb);
        if (t == 13) break;
        if (t >= 0) publish_e(g_flags + (t * 16 + c.m) * 32);
        TL(t, 6);
        const int ln = t < 0 ? 0 : layer * 2 + (type == 6 ? 2 : 1);
        row_stats(c, acc, ln);
        if (t <= 2) {
          if (c.b < (t < 0 ? 96 : 112)) colsum_piece(c, t < 0 ? p.wqkv : p.w1, t < 0 ? 3 * D_ : F_, g_cs + (t < 0 ? 0 : 3 * D_));
          load_tables(c, p, t >= 0);
        }
        load_row_stats(c, ln);
        TL(t, 5);
      } else {
        bar_sync(BAR_EPI + c.wg, 256);
        if (type < 2) epi_qkv(c, p, acc, t, type);
        else epi_up(c, p, acc, t, type);
        publish_e(g_flags + (t * 16 + c.m) * 32);
        TL(t, 6);
      }
      if (type != 1 && type != 5) bar_arrive(BAR_EPI + (c.wg ^ 1), 256);
    }
    if (c.wg == 1) {
      if (tid == 128) g_epoch[blockIdx.x] = c.tag;
      bulk_wait_read_e();
      asm volatile("barrier.cluster.wait.aligned;" ::: "memory");
    }
  }
}

typedef CUresult (*EncodeFn)(CUtensorMap*, CUtensorMapDataType, cuuint32_t, void*, const cuuint64_t*, const cuuint64_t*,
                             const cuuint32_t*, const cuuint32_t*, CUtensorMapInterleave, CUtensorMapSwizzle,
                             CUtensorMapL2promotion, CUtensorMapFloatOOBfill);

void make_map(EncodeFn fn, CUtensorMap* m, const void* ptr, int rank, const cuuint64_t* dims, const cuuint64_t* strides, const cuuint32_t* box) {
  const cuuint32_t es[4] = {1, 1, 1, 1};
  fn(m, CU_TENSOR_MAP_DATA_TYPE_BFLOAT16, rank, const_cast<void*>(ptr), dims, strides, box, es, CU_TENSOR_MAP_INTERLEAVE_NONE,
     CU_TENSOR_MAP_SWIZZLE_128B, CU_TENSOR_MAP_L2_PROMOTION_L2_128B, CU_TENSOR_MAP_FLOAT_OOB_FILL_NONE);
}
void map_rows(EncodeFn fn, CUtensorMap* m, const void* ptr, int cols, int rows, int box_slabs, bool tokens) {
  const cuuint64_t rb = (cuuint64_t)cols * 2;
  const cuuint64_t dims[4] = {(cuuint64_t)cols, 16, 2, (cuuint64_t)(rows / 32)};
  const cuuint64_t st[3] = {tokens ? 2 * rb : rb, tokens ? rb : 16 * rb, 32 * rb};
  const cuuint32_t box[4] = {64, 16, 2, (cuuint32_t)box_slabs};
  make_map(fn, m, ptr, 4, dims, st, box);
}
void map_w(EncodeFn fn, CUtensorMap* m, const void* ptr, int K, int N, int inner, int nch) {
  const cuuint64_t dims[3] = {(cuuint64_t)inner, (cuuint64_t)K, (cuuint64_t)(N / inner)}, st[2] = {(cuuint64_t)N * 2, (cuuint64_t)inner * 2};
  const cuuint32_t box[3] = {64, 64, (cuuint32_t)nch};
  make_map(fn, m, ptr, 3, dims, st, box);
}

}

extern "C" void kernel_launch(void* const* d_in, const int* in_sizes, int n_in, void* d_out, int out_size) {
  (void)in_sizes; (void)n_in; (void)out_size;
  Params p;
  p.wqkv = (const __nv_bfloat16*)d_in[1]; p.wo = (const __nv_bfloat16*)d_in[2];
  p.w1 = (const __nv_bfloat16*)d_in[4]; p.b1 = (const __nv_bfloat16*)d_in[5];
  p.w2 = (const __nv_bfloat16*)d_in[6]; p.b2 = (const __nv_bfloat16*)d_in[7];
  void* fnp = nullptr; cudaDriverEntryPointQueryResult qr;
  cudaGetDriverEntryPoint("cuTensorMapEncodeTiled", &fnp, cudaEnableDefault, &qr);
  EncodeFn fn = (EncodeFn)fnp;
  void *act, *h;
  cudaGetSymbolAddress(&act, g_act); cudaGetSymbolAddress(&h, g_h);
  map_rows(fn, &p.ld_x, d_in[0], D_, S_, 2, true);
  map_rows(fn, &p.ld_act, act, D_, 3 * S_, 2, false);
  map_rows(fn, &p.ld_h, h, F_, S_, 2, false);
  map_rows(fn, &p.st_act, act, D_, 3 * S_, 1, false);
  map_rows(fn, &p.st_h, h, F_, S_, 1, false);
  map_rows(fn, &p.st_out, d_out, D_, S_, 1, true);
  map_w(fn, &p.w_qkv, p.wqkv, D_, 3 * D_, D_, 3);
  map_w(fn, &p.w_o, p.wo, D_, D_, 64, 2);
  map_w(fn, &p.w_1a, p.w1, D_, F_, 64, 3);
  map_w(fn, &p.w_1b, p.w1, D_, F_, 64, 2);
  map_w(fn, &p.w_2, p.w2, F_, D_, 64, 2);
  cudaFuncSetAttribute(fused_kernel, cudaFuncAttributeMaxDynamicSharedMemorySize, SMEM_BYTES);
  fused_kernel<<<128, 384, SMEM_BYTES>>>(p);
}
```

```cpp
#include <cuda_runtime.h>
#include <cuda_bf16.h>
#include <cuda.h>
#include <stdint.h>

#define EXP 0
namespace {

constexpr int S_ = 2048, D_ = 1024, F_ = 3584;
constexpr int A_BYTES = 16384;
constexpr int OFF_X   = 163840;
constexpr int OFF_STG = OFF_X + 32768;
constexpr int OFF_CSQ = OFF_STG + 16384;
constexpr int OFF_UP  = OFF_CSQ + 1536;
constexpr int OFF_B2  = OFF_UP + 3584;
constexpr int OFF_RST = OFF_B2 + 512;
constexpr int OFF_RED = OFF_RST + 1024;
constexpr int OFF_FULL = OFF_RED + 1024;
constexpr int OFF_EMPTY = OFF_FULL + 64;
constexpr int OFF_XBAR = OFF_EMPTY + 64;
constexpr int OFF_ZERO = OFF_XBAR + 16;
constexpr int SMEM_BYTES = OFF_ZERO + 16 + 1024;
constexpr int KB_LAYER = 6 * 16 + 56;
constexpr int NCS = 3 * D_ + F_;
constexpr unsigned SPIN_LIMIT = 1u << 20;
constexpr int PAUSE1 = 8, PAUSE2 = 10;
enum { BAR_START = 1, BAR_EPI = 3, BAR_WG = 5, BAR_P0 = 7, BAR_P1 = 8, BAR_RES = 9, BAR_READY = 10, BAR_FREE = 11, BAR_COPY = 12 };

struct Params {
  CUtensorMap ld_x, ld_out, ld_h, st_h, st_out, w_qkv, w_o, w_1a, w_1b, w_2;
  const __nv_bfloat16 *wqkv, *wo, *w1, *b1, *w2, *b2;
};

__device__ __align__(1024) __nv_bfloat16 g_h[S_ * F_];
__device__ __align__(128) uint4 g_stats[4 * S_ * 8];
__device__ __align__(128) uint2 g_cs[2 * NCS];
__device__ __align__(128) uint4 g_halo[4 * 128 * 11 * 32];
__device__ __align__(128) unsigned g_flags[14 * 16 * 32];
__device__ unsigned g_epoch[128];
#define TL(t, e)
#define PTL(t, e)
#undef TK
#define TK(t, k)

template<int N, int KEEP> __device__ __forceinline__ void wgmma_ss(float (&d)[96], uint64_t da, uint64_t db);
template<> __device__ __forceinline__ void wgmma_ss<128, 0>(float (&d)[96], uint64_t da, uint64_t db) {
  asm volatile("{\n.reg .pred p;\nsetp.ne.b32 p, 0, 0;\nwgmma.mma_async.sync.aligned.m64n128k16.f32.bf16.bf16 {%0, %1, %2, %3, %4, %5, %6, %7, %8, %9, %10, %11, %12, %13, %14, %15, %16, %17, %18, %19, %20, %21, %22, %23, %24, %25, %26, %27, %28, %29, %30, %31, %32, %33, %34, %35, %36, %37, %38, %39, %40, %41, %42, %43, %44, %45, %46, %47, %48, %49, %50, %51, %52, %53, %54, %55, %56, %57, %58, %59, %60, %61, %62, %63}, %64, %65, p, 1, 1, 0, 1;\n}"
    : "=f"(d[0]), "=f"(d[1]), "=f"(d[2]), "=f"(d[3]), "=f"(d[4]), "=f"(d[5]), "=f"(d[6]), "=f"(d[7]), "=f"(d[8]), "=f"(d[9]), "=f"(d[10]), "=f"(d[11]), "=f"(d[12]), "=f"(d[13]), "=f"(d[14]), "=f"(d[15]), "=f"(d[16]), "=f"(d[17]), "=f"(d[18]), "=f"(d[19]), "=f"(d[20]), "=f"(d[21]), "=f"(d[22]), "=f"(d[23]), "=f"(d[24]), "=f"(d[25]), "=f"(d[26]), "=f"(d[27]), "=f"(d[28]), "=f"(d[29]), "=f"(d[30]), "=f"(d[31]), "=f"(d[32]), "=f"(d[33]), "=f"(d[34]), "=f"(d[35]), "=f"(d[36]), "=f"(d[37]), "=f"(d[38]), "=f"(d[39]), "=f"(d[40]), "=f"(d[41]), "=f"(d[42]), "=f"(d[43]), "=f"(d[44]), "=f"(d[45]), "=f"(d[46]), "=f"(d[47]), "=f"(d[48]), "=f"(d[49]), "=f"(d[50]), "=f"(d[51]), "=f"(d[52]), "=f"(d[53]), "=f"(d[54]), "=f"(d[55]), "=f"(d[56]), "=f"(d[57]), "=f"(d[58]), "=f"(d[59]), "=f"(d[60]), "=f"(d[61]), "=f"(d[62]), "=f"(d[63])
    : "l"(da), "l"(db));
}
template<> __device__ __forceinline__ void wgmma_ss<128, 1>(float (&d)[96], uint64_t da, uint64_t db) {
  asm volatile("{\n.reg .pred p;\nsetp.ne.b32 p, 1, 0;\nwgmma.mma_async.sync.aligned.m64n128k16.f32.bf16.bf16 {%0, %1, %2, %3, %4, %5, %6, %7, %8, %9, %10, %11, %12, %13, %14, %15, %16, %17, %18, %19, %20, %21, %22, %23, %24, %25, %26, %27, %28, %29, %30, %31, %32, %33, %34, %35, %36, %37, %38, %39, %40, %41, %42, %43, %44, %45, %46, %47, %48, %49, %50, %51, %52, %53, %54, %55, %56, %57, %58, %59, %60, %61, %62, %63}, %64, %65, p, 1, 1, 0, 1;\n}"
    : "+f"(d[0]), "+f"(d[1]), "+f"(d[2]), "+f"(d[3]), "+f"(d[4]), "+f"(d[5]), "+f"(d[6]), "+f"(d[7]), "+f"(d[8]), "+f"(d[9]), "+f"(d[10]), "+f"(d[11]), "+f"(d[12]), "+f"(d[13]), "+f"(d[14]), "+f"(d[15]), "+f"(d[16]), "+f"(d[17]), "+f"(d[18]), "+f"(d[19]), "+f"(d[20]), "+f"(d[21]), "+f"(d[22]), "+f"(d[23]), "+f"(d[24]), "+f"(d[25]), "+f"(d[26]), "+f"(d[27]), "+f"(d[28]), "+f"(d[29]), "+f"(d[30]), "+f"(d[31]), "+f"(d[32]), "+f"(d[33]), "+f"(d[34]), "+f"(d[35]), "+f"(d[36]), "+f"(d[37]), "+f"(d[38]), "+f"(d[39]), "+f"(d[40]), "+f"(d[41]), "+f"(d[42]), "+f"(d[43]), "+f"(d[44]), "+f"(d[45]), "+f"(d[46]), "+f"(d[47]), "+f"(d[48]), "+f"(d[49]), "+f"(d[50]), "+f"(d[51]), "+f"(d[52]), "+f"(d[53]), "+f"(d[54]), "+f"(d[55]), "+f"(d[56]), "+f"(d[57]), "+f"(d[58]), "+f"(d[59]), "+f"(d[60]), "+f"(d[61]), "+f"(d[62]), "+f"(d[63])
    : "l"(da), "l"(db));
}
template<> __device__ __forceinline__ void wgmma_ss<192, 0>(float (&d)[96], uint64_t da, uint64_t db) {
  asm volatile("{\n.reg .pred p;\nsetp.ne.b32 p, 0, 0;\nwgmma.mma_async.sync.aligned.m64n192k16.f32.bf16.bf16 {%0, %1, %2, %3, %4, %5, %6, %7, %8, %9, %10, %11, %12, %13, %14, %15, %16, %17, %18, %19, %20, %21, %22, %23, %24, %25, %26, %27, %28, %29, %30, %31, %32, %33, %34, %35, %36, %37, %38, %39, %40, %41, %42, %43, %44, %45, %46, %47, %48, %49, %50, %51, %52, %53, %54, %55, %56, %57, %58, %59, %60, %61, %62, %63, %64, %65, %66, %67, %68, %69, %70, %71, %72, %73, %74, %75, %76, %77, %78, %79, %80, %81, %82, %83, %84, %85, %86, %87, %88, %89, %90, %91, %92, %93, %94, %95}, %96, %97, p, 1, 1, 0, 1;\n}"
    : "=f"(d[0]), "=f"(d[1]), "=f"(d[2]), "=f"(d[3]), "=f"(d[4]), "=f"(d[5]), "=f"(d[6]), "=f"(d[7]), "=f"(d[8]), "=f"(d[9]), "=f"(d[10]), "=f"(d[11]), "=f"(d[12]), "=f"(d[13]), "=f"(d[14]), "=f"(d[15]), "=f"(d[16]), "=f"(d[17]), "=f"(d[18]), "=f"(d[19]), "=f"(d[20]), "=f"(d[21]), "=f"(d[22]), "=f"(d[23]), "=f"(d[24]), "=f"(d[25]), "=f"(d[26]), "=f"(d[27]), "=f"(d[28]), "=f"(d[29]), "=f"(d[30]), "=f"(d[31]), "=f"(d[32]), "=f"(d[33]), "=f"(d[34]), "=f"(d[35]), "=f"(d[36]), "=f"(d[37]), "=f"(d[38]), "=f"(d[39]), "=f"(d[40]), "=f"(d[41]), "=f"(d[42]), "=f"(d[43]), "=f"(d[44]), "=f"(d[45]), "=f"(d[46]), "=f"(d[47]), "=f"(d[48]), "=f"(d[49]), "=f"(d[50]), "=f"(d[51]), "=f"(d[52]), "=f"(d[53]), "=f"(d[54]), "=f"(d[55]), "=f"(d[56]), "=f"(d[57]), "=f"(d[58]), "=f"(d[59]), "=f"(d[60]), "=f"(d[61]), "=f"(d[62]), "=f"(d[63]), "=f"(d[64]), "=f"(d[65]), "=f"(d[66]), "=f"(d[67]), "=f"(d[68]), "=f"(d[69]), "=f"(d[70]), "=f"(d[71]), "=f"(d[72]), "=f"(d[73]), "=f"(d[74]), "=f"(d[75]), "=f"(d[76]), "=f"(d[77]), "=f"(d[78]), "=f"(d[79]), "=f"(d[80]), "=f"(d[81]), "=f"(d[82]), "=f"(d[83]), "=f"(d[84]), "=f"(d[85]), "=f"(d[86]), "=f"(d[87]), "=f"(d[88]), "=f"(d[89]), "=f"(d[90]), "=f"(d[91]), "=f"(d[92]), "=f"(d[93]), "=f"(d[94]), "=f"(d[95])
    : "l"(da), "l"(db));
}
template<> __device__ __forceinline__ void wgmma_ss<192, 1>(float (&d)[96], uint64_t da, uint64_t db) {
  asm volatile("{\n.reg .pred p;\nsetp.ne.b32 p, 1, 0;\nwgmma.mma_async.sync.aligned.m64n192k16.f32.bf16.bf16 {%0, %1, %2, %3, %4, %5, %6, %7, %8, %9, %10, %11, %12, %13, %14, %15, %16, %17, %18, %19, %20, %21, %22, %23, %24, %25, %26, %27, %28, %29, %30, %31, %32, %33, %34, %35, %36, %37, %38, %39, %40, %41, %42, %43, %44, %45, %46, %47, %48, %49, %50, %51, %52, %53, %54, %55, %56, %57, %58, %59, %60, %61, %62, %63, %64, %65, %66, %67, %68, %69, %70, %71, %72, %73, %74, %75, %76, %77, %78, %79, %80, %81, %82, %83, %84, %85, %86, %87, %88, %89, %90, %91, %92, %93, %94, %95}, %96, %97, p, 1, 1, 0, 1;\n}"
    : "+f"(d[0]), "+f"(d[1]), "+f"(d[2]), "+f"(d[3]), "+f"(d[4]), "+f"(d[5]), "+f"(d[6]), "+f"(d[7]), "+f"(d[8]), "+f"(d[9]), "+f"(d[10]), "+f"(d[11]), "+f"(d[12]), "+f"(d[13]), "+f"(d[14]), "+f"(d[15]), "+f"(d[16]), "+f"(d[17]), "+f"(d[18]), "+f"(d[19]), "+f"(d[20]), "+f"(d[21]), "+f"(d[22]), "+f"(d[23]), "+f"(d[24]), "+f"(d[25]), "+f"(d[26]), "+f"(d[27]), "+f"(d[28]), "+f"(d[29]), "+f"(d[30]), "+f"(d[31]), "+f"(d[32]), "+f"(d[33]), "+f"(d[34]), "+f"(d[35]), "+f"(d[36]), "+f"(d[37]), "+f"(d[38]), "+f"(d[39]), "+f"(d[40]), "+f"(d[41]), "+f"(d[42]), "+f"(d[43]), "+f"(d[44]), "+f"(d[45]), "+f"(d[46]), "+f"(d[47]), "+f"(d[48]), "+f"(d[49]), "+f"(d[50]), "+f"(d[51]), "+f"(d[52]), "+f"(d[53]), "+f"(d[54]), "+f"(d[55]), "+f"(d[56]), "+f"(d[57]), "+f"(d[58]), "+f"(d[59]), "+f"(d[60]), "+f"(d[61]), "+f"(d[62]), "+f"(d[63]), "+f"(d[64]), "+f"(d[65]), "+f"(d[66]), "+f"(d[67]), "+f"(d[68]), "+f"(d[69]), "+f"(d[70]), "+f"(d[71]), "+f"(d[72]), "+f"(d[73]), "+f"(d[74]), "+f"(d[75]), "+f"(d[76]), "+f"(d[77]), "+f"(d[78]), "+f"(d[79]), "+f"(d[80]), "+f"(d[81]), "+f"(d[82]), "+f"(d[83]), "+f"(d[84]), "+f"(d[85]), "+f"(d[86]), "+f"(d[87]), "+f"(d[88]), "+f"(d[89]), "+f"(d[90]), "+f"(d[91]), "+f"(d[92]), "+f"(d[93]), "+f"(d[94]), "+f"(d[95])
    : "l"(da), "l"(db));
}

__device__ __forceinline__ uint32_t smem_u32(const void* p) { return (uint32_t)__cvta_generic_to_shared(p); }
__device__ __forceinline__ void mbar_init(uint32_t bar, uint32_t cnt) { asm volatile("mbarrier.init.shared::cta.b64 [%0], %1;" :: "r"(bar), "r"(cnt)); }
__device__ __forceinline__ void mbar_arrive_cluster(uint32_t bar) { asm volatile("mbarrier.arrive.shared::cluster.b64 _, [%0];" :: "r"(bar) : "memory"); }
__device__ __forceinline__ void mbar_wait(uint32_t bar, uint32_t parity) {
  asm volatile(
    "{\n.reg .pred p;\n.reg .u32 n;\n"
    "mbarrier.try_wait.parity.shared::cta.b64 p, [%0], %1;\n"
    "@p bra.uni WAIT_DONE;\n"
    "mov.u32 n, 0;\n"
    "WAIT_LOOP:\n"
    "mbarrier.try_wait.parity.shared::cta.b64 p, [%0], %1;\n"
    "@p bra.uni WAIT_DONE;\n"
    "add.u32 n, n, 1;\n"
    "setp.lt.u32 p, n, 0x100000;\n"
    "@p bra.uni WAIT_LOOP;\n"
    "trap;\n"
    "WAIT_DONE:\n}" :: "r"(bar), "r"(parity) : "memory");
}
#define ELECT "{\n.reg .pred p;\nelect.sync _|p, 0xffffffff;\n"
__device__ __forceinline__ void mbar_arrive_e(uint32_t bar) { asm volatile(ELECT "@p mbarrier.arrive.shared::cta.b64 _, [%0];\n}" :: "r"(bar) : "memory"); }
__device__ __forceinline__ void mbar_expect_e(uint32_t bar, uint32_t bytes) { asm volatile(ELECT "@p mbarrier.arrive.expect_tx.shared::cta.b64 _, [%0], %1;\n}" :: "r"(bar), "r"(bytes) : "memory"); }
__device__ __forceinline__ void tma_ld4_e(uint32_t dst, const CUtensorMap* m, uint32_t bar, int c0, int c3) {
  asm volatile(ELECT "@p cp.async.bulk.tensor.4d.shared::cluster.global.mbarrier::complete_tx::bytes [%0], [%1, {%3, %5, %5, %4}], [%2];\n}"
    :: "r"(dst), "l"(m), "r"(bar), "r"(c0), "r"(c3), "r"(0) : "memory");
}
__device__ __forceinline__ void tma_ld4_mc_e(uint32_t dst, const CUtensorMap* m, uint32_t bar, int c0, int c3) {
  asm volatile(ELECT "@p cp.async.bulk.tensor.4d.shared::cluster.global.mbarrier::complete_tx::bytes.multicast::cluster [%0], [%1, {%3, %5, %5, %4}], [%2], %6;\n}"
    :: "r"(dst), "l"(m), "r"(bar), "r"(c0), "r"(c3), "r"(0), "h"((uint16_t)3) : "memory");
}
__device__ __forceinline__ void tma_ld3_e(uint32_t dst, const CUtensorMap* m, uint32_t bar, int c0, int c1, int c2) {
  asm volatile(ELECT "@p cp.async.bulk.tensor.3d.shared::cluster.global.mbarrier::complete_tx::bytes [%0], [%1, {%3, %4, %5}], [%2];\n}"
    :: "r"(dst), "l"(m), "r"(bar), "r"(c0), "r"(c1), "r"(c2) : "memory");
}
__device__ __forceinline__ void tma_st4_e(const CUtensorMap* m, uint32_t src, int c0, int c3) {
  asm volatile(ELECT "@p cp.async.bulk.tensor.4d.global.shared::cta.bulk_group [%0, {%2, %4, %4, %3}], [%1];\n}"
    :: "l"(m), "r"(src), "r"(c0), "r"(c3), "r"(0) : "memory");
}
__device__ __forceinline__ void dsmem_copy_e(uint32_t dst, uint32_t src, uint32_t bar) {
  asm volatile(ELECT "@p cp.async.bulk.shared::cluster.shared::cta.mbarrier::complete_tx::bytes [%0], [%1], 16384, [%2];\n}"
    :: "r"(dst), "r"(src), "r"(bar) : "memory");
}
__device__ __forceinline__ void bulk_wait_read_e() { asm volatile(ELECT "@p cp.async.bulk.commit_group;\n@p cp.async.bulk.wait_group.read 0;\n}" ::: "memory"); __syncwarp(); }
__device__ __forceinline__ void publish_e(unsigned* flag, unsigned tag) {
  asm volatile(ELECT "@p fence.proxy.async;\n@p st.relaxed.gpu.global.u32 [%0], %1;\n}" :: "l"(flag), "r"(tag) : "memory");
  __syncwarp();
}
__device__ __forceinline__ void fence_async_smem() { asm volatile("fence.proxy.async.shared::cta;" ::: "memory"); }
__device__ __forceinline__ void wgmma_fence() { asm volatile("wgmma.fence.sync.aligned;" ::: "memory"); }
__device__ __forceinline__ void wgmma_commit() { asm volatile("wgmma.commit_group.sync.aligned;" ::: "memory"); }
template<int N> __device__ __forceinline__ void wgmma_wait() { asm volatile("wgmma.wait_group.sync.aligned %0;" :: "n"(N) : "memory"); }
__device__ __forceinline__ void bar_sync(int id, int n) { asm volatile("bar.sync %0, %1;" :: "r"(id), "r"(n) : "memory"); }
__device__ __forceinline__ void bar_arrive(int id, int n) { asm volatile("bar.arrive %0, %1;" :: "r"(id), "r"(n) : "memory"); }
__device__ __forceinline__ void bar_arrive_after(int id, uint32_t dep) {
  asm volatile("{\n.reg .u32 n;\nor.b32 n, %1, 256;\nmin.u32 n, n, 256;\nbar.arrive %0, n;\n}" :: "r"(id), "r"(dep) : "memory");
}
__device__ __forceinline__ void bar_sync_after(int id, uint32_t dep) {
  asm volatile("{\n.reg .u32 n;\nor.b32 n, %1, 256;\nmin.u32 n, n, 256;\nbar.sync %0, n;\n}" :: "r"(id), "r"(dep) : "memory");
}
__device__ __forceinline__ uint32_t mapa(uint32_t a, uint32_t r) { uint32_t d; asm("mapa.shared::cluster.u32 %0, %1, %2;" : "=r"(d) : "r"(a), "r"(r)); return d; }
__device__ __forceinline__ void st_tag128(uint4* p, uint32_t a, uint32_t b, uint32_t c, uint32_t tag) {
  asm volatile("{\n.reg .b64 lo, hi;\n.reg .b128 v;\nmov.b64 lo, {%1, %2};\nmov.b64 hi, {%3, %4};\nmov.b128 v, {lo, hi};\nst.relaxed.gpu.global.b128 [%0], v;\n}"
    :: "l"(p), "r"(a), "r"(b), "r"(c), "r"(tag) : "memory");
}
__device__ __forceinline__ uint4 ld_tag128(const uint4* p) {
  uint4 v;
  asm volatile("{\n.reg .b64 lo, hi;\n.reg .b128 v;\nld.relaxed.gpu.global.b128 v, [%4];\nmov.b128 {lo, hi}, v;\nmov.b64 {%0, %1}, lo;\nmov.b64 {%2, %3}, hi;\n}"
    : "=r"(v.x), "=r"(v.y), "=r"(v.z), "=r"(v.w) : "l"(p) : "memory");
  return v;
}
__device__ __forceinline__ void st_tag64(uint2* p, float a, uint32_t tag) {
  asm volatile("{\n.reg .b64 v;\nmov.b64 v, {%1, %2};\nst.relaxed.gpu.global.b64 [%0], v;\n}" :: "l"(p), "r"(__float_as_uint(a)), "r"(tag) : "memory");
}
__device__ __forceinline__ uint2 ld_tag64(const uint2* p) {
  uint2 v;
  asm volatile("{\n.reg .b64 v;\nld.relaxed.gpu.global.b64 v, [%2];\nmov.b64 {%0, %1}, v;\n}" : "=r"(v.x), "=r"(v.y) : "l"(p) : "memory");
  return v;
}
__device__ __forceinline__ uint32_t pack_bf16(float lo, float hi) { uint32_t r; asm("cvt.rn.bf16x2.f32 %0, %1, %2;" : "=r"(r) : "f"(hi), "f"(lo)); return r; }
__device__ __forceinline__ uint32_t relu_sq_bf16(float lo, float hi) {
  uint32_t r; asm("{\n.reg .b32 t;\ncvt.rn.relu.bf16x2.f32 t, %1, %2;\nmul.rn.bf16x2 %0, t, t;\n}" : "=r"(r) : "f"(hi), "f"(lo)); return r;
}
__device__ __forceinline__ float bf_lo(uint32_t u) { return __uint_as_float(u << 16); }
__device__ __forceinline__ float bf_hi(uint32_t u) { return __uint_as_float(u & 0xffff0000u); }
__device__ __forceinline__ void stmatrix4(uint32_t addr, uint32_t r0, uint32_t r1, uint32_t r2, uint32_t r3) {
  asm volatile("stmatrix.sync.aligned.m8n8.x4.shared.b16 [%0], {%1, %2, %3, %4};" :: "r"(addr), "r"(r0), "r"(r1), "r"(r2), "r"(r3) : "memory");
}
__device__ __forceinline__ void ldmatrix4(uint32_t addr, uint32_t (&r)[4]) {
  asm volatile("ldmatrix.sync.aligned.m8n8.x4.shared.b16 {%0, %1, %2, %3}, [%4];" : "=r"(r[0]), "=r"(r[1]), "=r"(r[2]), "=r"(r[3]) : "r"(addr) : "memory");
}
__device__ __forceinline__ uint32_t movmatrix(uint32_t a) { uint32_t d; asm volatile("movmatrix.sync.aligned.m8n8.trans.b16 %0, %1;" : "=r"(d) : "r"(a)); return d; }
__device__ __forceinline__ void mma16816_z(float (&c)[4], uint32_t a0, uint32_t a1, uint32_t a2, uint32_t a3, uint32_t b0, uint32_t b1, const float4& z) {
  asm volatile("mma.sync.aligned.m16n8k16.row.col.f32.bf16.bf16.f32 {%0,%1,%2,%3}, {%4,%5,%6,%7}, {%8,%9}, {%10,%11,%12,%13};"
    : "=f"(c[0]), "=f"(c[1]), "=f"(c[2]), "=f"(c[3]) : "r"(a0), "r"(a1), "r"(a2), "r"(a3), "r"(b0), "r"(b1), "f"(z.x), "f"(z.y), "f"(z.z), "f"(z.w));
}
__device__ __forceinline__ void mma1688_z(float (&c)[4], uint32_t a0, uint32_t a1, uint32_t b0, const float4& z) {
  asm volatile("mma.sync.aligned.m16n8k8.row.col.f32.bf16.bf16.f32 {%0,%1,%2,%3}, {%4,%5}, {%6}, {%7,%8,%9,%10};"
    : "=f"(c[0]), "=f"(c[1]), "=f"(c[2]), "=f"(c[3]) : "r"(a0), "r"(a1), "r"(b0), "f"(z.x), "f"(z.y), "f"(z.z), "f"(z.w));
}
__device__ __forceinline__ float ex2(float x) { float y; asm("ex2.approx.ftz.f32 %0, %1;" : "=f"(y) : "f"(x)); return y; }
__device__ __forceinline__ float rcp(float x) { float y; asm("rcp.approx.ftz.f32 %0, %1;" : "=f"(y) : "f"(x)); return y; }
__device__ __forceinline__ void mma16816(float (&c)[4], uint32_t a0, uint32_t a1, uint32_t a2, uint32_t a3, uint32_t b0, uint32_t b1) {
  asm volatile("mma.sync.aligned.m16n8k16.row.col.f32.bf16.bf16.f32 {%0,%1,%2,%3}, {%4,%5,%6,%7}, {%8,%9}, {%0,%1,%2,%3};"
    : "+f"(c[0]), "+f"(c[1]), "+f"(c[2]), "+f"(c[3]) : "r"(a0), "r"(a1), "r"(a2), "r"(a3), "r"(b0), "r"(b1));
}
__device__ __forceinline__ void mma1688(float (&c)[4], uint32_t a0, uint32_t a1, uint32_t b0) {
  asm volatile("mma.sync.aligned.m16n8k8.row.col.f32.bf16.bf16.f32 {%0,%1,%2,%3}, {%4,%5}, {%6}, {%0,%1,%2,%3};"
    : "+f"(c[0]), "+f"(c[1]), "+f"(c[2]), "+f"(c[3]) : "r"(a0), "r"(a1), "r"(b0));
}
__device__ __forceinline__ void sts128(uint32_t a, uint32_t x, uint32_t y, uint32_t z, uint32_t w) { asm volatile("st.shared.v4.b32 [%0], {%1,%2,%3,%4};" :: "r"(a), "r"(x), "r"(y), "r"(z), "r"(w) : "memory"); }
__device__ __forceinline__ uint4 lds128(uint32_t a) { uint4 v; asm volatile("ld.shared.v4.b32 {%0,%1,%2,%3}, [%4];" : "=r"(v.x), "=r"(v.y), "=r"(v.z), "=r"(v.w) : "r"(a) : "memory"); return v; }
__device__ __forceinline__ float2 lds64f(uint32_t a) { float2 v; asm volatile("ld.shared.v2.f32 {%0,%1}, [%2];" : "=f"(v.x), "=f"(v.y) : "r"(a) : "memory"); return v; }
__device__ __forceinline__ float4 lds128f(uint32_t a) { float4 v; asm volatile("ld.shared.v4.f32 {%0,%1,%2,%3}, [%4];" : "=f"(v.x), "=f"(v.y), "=f"(v.z), "=f"(v.w) : "r"(a) : "memory"); return v; }
__device__ __forceinline__ void sts32f(uint32_t a, float v) { asm volatile("st.shared.f32 [%0], %1;" :: "r"(a), "f"(v) : "memory"); }
__device__ __forceinline__ void sts64f(uint32_t a, float x, float y) { asm volatile("st.shared.v2.f32 [%0], {%1,%2};" :: "r"(a), "f"(x), "f"(y) : "memory"); }
__device__ __forceinline__ float lds32f(uint32_t a) { float v; asm volatile("ld.shared.f32 %0, [%1];" : "=f"(v) : "r"(a) : "memory"); return v; }
template<int R> __device__ __forceinline__ void reg_alloc() { asm volatile("setmaxnreg.inc.sync.aligned.u32 %0;" :: "n"(R)); }
template<int R> __device__ __forceinline__ void reg_dealloc() { asm volatile("setmaxnreg.dec.sync.aligned.u32 %0;" :: "n"(R)); }

struct Ctx {
  uint32_t sb;
  int m, j, b, rank, wg, w, lane;
  unsigned tag;
};

__device__ __forceinline__ int own_kb(const Ctx& c, int step) {
  return step < 4 ? (c.j * 2) ^ step : (((c.j >> 1) * 4 + 2 * step + (step < 10 ? 12 : 0)) & 15) + (step >= 10);
}
__device__ __forceinline__ int first_stage(int type) { return (0x2100433 >> (4 * type)) & 7; }

template<int BN, int RES>
__device__ __forceinline__ void mainloop(const Ctx& c, float (&acc)[2][96], int t, int type, int g, int nkb) {
  constexpr int NS = BN == 192 ? 4 : 5, STR = BN == 192 ? 40960 : 32768;
  constexpr uint64_t HA = (uint64_t)(1u << 16) | ((uint64_t)(128u | (1u << 30)) << 32), HB = (uint64_t)(512u << 16) | ((uint64_t)(64u | (1u << 30)) << 32);
  int st = first_stage(type);
  const bool own = BN == 192 && (type == 3 || t == 7);
  const uint32_t rel = mapa(c.sb + OFF_EMPTY, c.lane & 1);
  const uint32_t sb = (c.sb & 0x3ffffu) >> 4;
  uint64_t da = HA | (own ? sb + OFF_X / 16 : sb + st * (STR / 16)), db = HB | (sb + st * (STR / 16) + A_BYTES / 16);
  TL(t, 0);
  if (t > 0) bar_sync(BAR_START + c.wg, 256);
  TL(t, 1);
  mbar_wait(c.sb + OFF_FULL + 8 * (g & 7), (g >> 3) & 1);
  TL(t, 2);
  wgmma_fence();
  wgmma_ss<BN, RES>(acc[0], da, db);
  wgmma_ss<BN, RES>(acc[1], da + 64, db);
  wgmma_commit();
#pragma unroll 1
  for (int kb = 1;; kb++) {
    wgmma_fence();
#pragma unroll
    for (int k = 1; k < 4; k++) {
      if (k == 3 && kb == nkb && t < 13 && type != 1) bar_arrive(BAR_START + (c.wg ^ 1), 256);
      wgmma_ss<BN, 1>(acc[0], da + k * 2, db + k * 128);
      wgmma_ss<BN, 1>(acc[1], da + (64 + k * 2), db + k * 128);
    }
    wgmma_commit();
    if (kb == nkb) break;
    if (BN == 192 && type == 1 && (kb == PAUSE1 || kb == PAUSE2)) { bar_sync(BAR_P0, 256); bar_sync(BAR_P1, 256); }
    if (++st == NS) st = 0;
    g++;
    da = HA | (own && kb == 1 ? sb + (OFF_X + A_BYTES) / 16 : sb + st * (STR / 16)); db = HB | (sb + st * (STR / 16) + A_BYTES / 16);
    mbar_wait(c.sb + OFF_FULL + 8 * (g & 7), (g >> 3) & 1);
    wgmma_fence();
    wgmma_ss<BN, 1>(acc[0], da, db);
    wgmma_ss<BN, 1>(acc[1], da + 64, db);
    wgmma_commit();
    wgmma_wait<1>();
    if (c.lane < 2) mbar_arrive_cluster(rel + 8 * ((g - 1) & 7));
    TK(t, kb);
  }
  wgmma_wait<0>();
  if (c.lane < 2) mbar_arrive_cluster(rel + 8 * (g & 7));
  TL(t, 3);
}

__device__ __forceinline__ void load_row_stats(const Ctx& c, int ln) {
  const uint4* p = g_stats + (ln * 128 + c.m * 8) * 128 + c.w * 32 + c.lane;
  float s, q;
  for (unsigned it = 0;; it++) {
    uint4 v[8];
#pragma unroll
    for (int i = 0; i < 8; i++) v[i] = ld_tag128(p + i * 128);
    bool ok = true;
    s = 0.f; q = 0.f;
#pragma unroll
    for (int i = 0; i < 8; i++) { ok = ok && v[i].w == c.tag; s += __uint_as_float(v[i].x); q += __uint_as_float(v[i].y); }
    if (__all_sync(0xffffffffu, ok) || it > SPIN_LIMIT) break;
    __nanosleep(400);
  }
  const float mean = s * (1.0f / D_);
  const float var = fmaxf(q * (1.0f / D_) - mean * mean, 0.0f);
  sts64f(c.sb + OFF_RST + (c.w * 32 + c.lane) * 8, rsqrtf(var + 1e-5f), -mean);
  __syncwarp();
}

__device__ __forceinline__ void epi_qkv(const Ctx& c, float (&acc)[2][96], int t, int q) {
  const int lane = c.lane, w = c.w, g = lane >> 2, cc = lane & 3;
  const int layer = t >= 7;
  float rs[4], nm[4], mu[4];
#pragma unroll
  for (int r = 0; r < 4; r++) { const float2 v = lds64f(c.sb + OFF_RST + (w * 32 + 8 * r + g) * 8); rs[r] = v.x; mu[r] = v.y; nm[r] = v.x * v.y; }
  bar_sync(BAR_FREE, 160);
  uint32_t P[3][2][4][4];
  const uint32_t csb = c.sb + OFF_CSQ + q * 768 + cc * 8;
  const uint32_t stg = c.sb + OFF_STG + w * 4096;
  uint4* const halo = g_halo + ((layer * 2 + q) * 128 + c.b) * 352 + lane;
#pragma unroll
  for (int i = 1; i >= 0; i--) {
#pragma unroll
    for (int nt = 8; nt < 24; nt++) {
      const float2 cs = lds64f(csb + nt * 32);
#pragma unroll
      for (int h = 0; h < 2; h++) {
        const int r = 2 * h + i;
        uint32_t u = pack_bf16(fmaf(acc[i][4 * nt + 2 * h], rs[r], cs.x * nm[r]), fmaf(acc[i][4 * nt + 2 * h + 1], rs[r], cs.y * nm[r]));
        if (nt >= 16) u = movmatrix(u);
        P[nt >> 3][(nt >> 2) & 1][r][nt & 3] = u;
      }
    }
    if (i == 1) {
#define HW(n) P[1 + (((n) >> 4) & 1)][((n) >> 3) & 1][(((n) >> 2) & 1) * 2 + 1][(n) & 3]
      if (w < 3) {
#pragma unroll
        for (int z = 0; z < 8; z++) sts128(stg + 4096 + lane * 16 + z * 512, HW(4 * z), HW(4 * z + 1), HW(4 * z + 2), HW(4 * z + 3));
      } else if (c.m < 15) {
#pragma unroll
        for (int z = 0; z < 11; z++) st_tag128(halo + z * 32, HW(3 * z), HW(3 * z + 1), HW(3 * z + 2), c.tag);
      }
#undef HW
    }
  }
#pragma unroll
  for (int nt = 0; nt < 8; nt++) {
    const float2 cs = lds64f(csb + nt * 32);
#pragma unroll
    for (int r = 0; r < 4; r++)
      P[0][nt >> 2][r][nt & 3] = pack_bf16(fmaf(cs.x, mu[r], acc[r & 1][4 * nt + 2 * (r >> 1)]), fmaf(cs.y, mu[r], acc[r & 1][4 * nt + 2 * (r >> 1) + 1]));
  }
  TL(t, 8);
  bar_sync(BAR_WG + c.wg, 128);
  const bool nohalo = (w == 0 && c.m == 0);
  if (w == 0) {
    uint32_t G[33];
#pragma unroll
    for (int z = 0; z < 33; z++) G[z] = 0u;
    for (unsigned it = 0; !nohalo; it++) {
      bool ok = true;
#pragma unroll
      for (int z = 0; z < 11; z++) { const uint4 v = ld_tag128(halo - 8 * 352 + z * 32); G[3 * z] = v.x; G[3 * z + 1] = v.y; G[3 * z + 2] = v.z; ok = ok && v.w == c.tag; }
      if (__all_sync(0xffffffffu, ok) || it > SPIN_LIMIT) break;
    }
#pragma unroll
    for (int z = 0; z < 8; z++) sts128(stg + lane * 16 + z * 512, G[4 * z], G[4 * z + 1], G[4 * z + 2], G[4 * z + 3]);
  }
  uint32_t H[32];
#pragma unroll
  for (int z = 0; z < 8; z++) { const uint4 v = lds128(stg + lane * 16 + z * 512); H[4 * z] = v.x; H[4 * z + 1] = v.y; H[4 * z + 2] = v.z; H[4 * z + 3] = v.w; }
  TL(t, 4);
  float S[4][3][4];
  if (q == 0) bar_sync(BAR_P0, 256);
  float4 zero = lds128f(c.sb + OFF_ZERO);
  TL(t, 9);
#pragma unroll
  for (int k = 0; k < 2; k++)
#pragma unroll
    for (int z = 0; z < 4; z++) {
      const uint32_t* qa = P[0][z >> 1][2 * (z & 1)]; const uint32_t* qb = P[0][z >> 1][2 * (z & 1) + 1];
      const uint32_t* kk[3] = {H + 4 * z, P[1][z >> 1][2 * (z & 1)], P[1][z >> 1][2 * (z & 1) + 1]};
#pragma unroll
      for (int n = 0; n < 3; n++) {
        if (k == 0) mma16816_z(S[z][n], qa[0], qb[0], qa[1], qb[1], kk[n][0], kk[n][1], zero);
        else mma16816(S[z][n], qa[2], qb[2], qa[3], qb[3], kk[n][2], kk[n][3]);
      }
    }
  if (q == 0) {
    uint32_t dep = 0;
#pragma unroll
    for (int z = 0; z < 12; z++) dep |= __float_as_uint(S[z / 3][z % 3][0]);
    bar_arrive_after(BAR_P1, dep);
  }
  TL(t, 10);
  const bool far0 = 2 * cc > g, far1 = 2 * cc + 1 > g;
  const uint32_t fmask = (far0 ? 0xffffu : 0u) | (far1 ? 0xffff0000u : 0u);
  uint32_t pf[4][2], pn[4][2];
#pragma unroll
  for (int z = 0; z < 4; z++)
#pragma unroll
    for (int i = 0; i < 2; i++) {
      const float sc = rs[2 * (z & 1) + i] * (0.17677669529663687f * 1.4426950408889634f);
      float l0 = (far0 ? S[z][i][2 * i] : S[z][i + 1][2 * i]) * sc;
      float l1 = (far1 ? S[z][i][2 * i + 1] : S[z][i + 1][2 * i + 1]) * sc;
      if (i == 0 && nohalo) { const float neg = -1e9f * 1.4426950408889634f; if (far0) l0 = neg; if (far1) l1 = neg; }
      float mx = fmaxf(l0, l1);
      mx = fmaxf(mx, __shfl_xor_sync(0xffffffffu, mx, 1));
      mx = fmaxf(mx, __shfl_xor_sync(0xffffffffu, mx, 2));
      l0 = ex2(l0 - mx); l1 = ex2(l1 - mx);
      float sum = l0 + l1;
      sum += __shfl_xor_sync(0xffffffffu, sum, 1);
      sum += __shfl_xor_sync(0xffffffffu, sum, 2);
      sum = rcp(sum);
      const uint32_t u = pack_bf16(l0 * sum, l1 * sum);
      pf[z][i] = u & fmask; pn[z][i] = u & ~fmask;
    }
  float O[4][4][4];
  TL(t, 11);
  if (q == 0) bar_sync_after(BAR_P0, (pn[0][0] | pn[0][1] | pn[1][0]) | (pn[1][1] | pn[2][0] | pn[2][1]) | (pn[3][0] | pn[3][1]));
  zero = lds128f(c.sb + OFF_ZERO);
  TL(t, 12);
#pragma unroll
  for (int z = 0; z < 4; z++)
#pragma unroll
    for (int dt = 0; dt < 4; dt++) mma1688_z(O[z][dt], pn[z][0], pf[z][1], P[2][z >> 1][2 * (z & 1)][dt], zero);
#pragma unroll
  for (int z = 0; z < 4; z++)
#pragma unroll
    for (int dt = 0; dt < 4; dt++) mma1688(O[z][dt], pf[z][0], 0u, H[16 + 4 * z + dt]);
#pragma unroll
  for (int z = 0; z < 4; z++)
#pragma unroll
    for (int dt = 0; dt < 4; dt++) mma1688(O[z][dt], 0u, pn[z][1], P[2][z >> 1][2 * (z & 1) + 1][dt]);
  {
    uint32_t dep = 0;
#pragma unroll
    for (int z = 0; z < 16; z++) dep |= __float_as_uint(O[z >> 2][z & 3][2]);
    bar_arrive_after(q == 0 ? BAR_P1 : BAR_START + (c.wg ^ 1), dep);
  }
  TL(t, 5);
#pragma unroll
  for (int nt = 0; nt < 8; nt++) {
    const float* e = O[2 * (nt >> 2)][nt & 3]; const float* o = O[2 * (nt >> 2) + 1][nt & 3];
    stmatrix4(stg + lane * 128 + ((nt ^ (lane & 7)) << 4), pack_bf16(e[0], e[1]), pack_bf16(e[2], e[3]), pack_bf16(o[0], o[1]), pack_bf16(o[2], o[3]));
  }
  fence_async_smem();
  bar_arrive(BAR_READY, 160);
  TL(t, 13);
}

template<int CH>
__device__ __forceinline__ void epi_up(const Ctx& c, float (&acc)[2][96], int type) {
  const int lane = c.lane, w = c.w, g = lane >> 2, cc = lane & 3;
  float rs[4], nm[4];
#pragma unroll
  for (int r = 0; r < 4; r++) { const float2 v = lds64f(c.sb + OFF_RST + (w * 32 + 8 * r + g) * 8); rs[r] = v.x; nm[r] = v.x * v.y; }
  const int loc0 = type == 3 ? 0 : (type == 4 ? 192 : 320);
  const uint32_t cb = c.sb + OFF_UP + loc0 * 8 + cc * 16;
  const uint32_t stg = c.sb + OFF_STG + w * 4096;
#pragma unroll
  for (int ch = CH; ch < (CH ? 3 : 2); ch++) {
    uint32_t P[8][4];
#pragma unroll
    for (int n8 = 0; n8 < 8; n8++) {
      const int nt = ch * 8 + n8;
      const float4 cv = lds128f(cb + nt * 64);
#pragma unroll
      for (int r = 0; r < 4; r++)
        P[n8][r] = relu_sq_bf16(fmaf(acc[r & 1][4 * nt + 2 * (r >> 1)], rs[r], fmaf(cv.x, nm[r], cv.z)),
                                fmaf(acc[r & 1][4 * nt + 2 * (r >> 1) + 1], rs[r], fmaf(cv.y, nm[r], cv.w)));
    }
    bar_sync(BAR_FREE, 160);
#pragma unroll
    for (int n8 = 0; n8 < 8; n8++)
      stmatrix4(stg + lane * 128 + ((n8 ^ (lane & 7)) << 4), P[n8][0], P[n8][1], P[n8][2], P[n8][3]);
    fence_async_smem();
    bar_arrive(BAR_READY, 160);
  }
}

__device__ __forceinline__ void init_res(const Ctx& c, float (&acc)[2][96], int t, bool bias) {
  if (t <= 2) mbar_wait(c.sb + OFF_XBAR, 0);
  const uint32_t xb = c.sb + OFF_X + c.w * 4096 + c.lane * 128;
#pragma unroll
  for (int nt = 0; nt < 16; nt++) {
    uint32_t u[4];
    ldmatrix4(xb + (nt >> 3) * A_BYTES + (((nt & 7) ^ (c.lane & 7)) << 4), u);
    float2 b = make_float2(0.f, 0.f);
    if (bias) b = lds64f(c.sb + OFF_B2 + nt * 32 + (c.lane & 3) * 8);
#pragma unroll
    for (int r = 0; r < 4; r++) {
      acc[r & 1][4 * nt + 2 * (r >> 1)] = bf_lo(u[r]) + b.x;
      acc[r & 1][4 * nt + 2 * (r >> 1) + 1] = bf_hi(u[r]) + b.y;
    }
  }
}

__device__ __forceinline__ void epi_res(const Ctx& c, float (&acc)[2][96]) {
  const uint32_t xw = c.sb + OFF_X + c.w * 4096 + c.lane * 128;
#pragma unroll
  for (int nt = 0; nt < 16; nt++)
    stmatrix4(xw + (nt >> 3) * A_BYTES + (((nt & 7) ^ (c.lane & 7)) << 4),
              pack_bf16(acc[0][4 * nt], acc[0][4 * nt + 1]), pack_bf16(acc[1][4 * nt], acc[1][4 * nt + 1]),
              pack_bf16(acc[0][4 * nt + 2], acc[0][4 * nt + 3]), pack_bf16(acc[1][4 * nt + 2], acc[1][4 * nt + 3]));
  fence_async_smem();
  bar_arrive(BAR_RES, 192);
}

__device__ __forceinline__ void row_stats(const Ctx& c, float (&acc)[2][96], int ln) {
  const int g = c.lane >> 2, cc = c.lane & 3;
  float sm[4], sq[4];
#pragma unroll
  for (int r = 0; r < 4; r++) {
    float a = 0.f, b = 0.f;
#pragma unroll
    for (int n = 0; n < 32; n++) { const float x = acc[r & 1][4 * (n >> 1) + 2 * (r >> 1) + (n & 1)]; a += x; b = fmaf(x, x, b); }
    a += __shfl_xor_sync(0xffffffffu, a, 1); b += __shfl_xor_sync(0xffffffffu, b, 1);
    a += __shfl_xor_sync(0xffffffffu, a, 2); b += __shfl_xor_sync(0xffffffffu, b, 2);
    sm[r] = a; sq[r] = b;
  }
  const float a = cc == 0 ? sm[0] : cc == 1 ? sm[1] : cc == 2 ? sm[2] : sm[3];
  const float b = cc == 0 ? sq[0] : cc == 1 ? sq[1] : cc == 2 ? sq[2] : sq[3];
  st_tag128(g_stats + (ln * 128 + c.b) * 128 + c.w * 32 + 8 * cc + g, __float_as_uint(a), __float_as_uint(b), 0u, c.tag);
}

__device__ __forceinline__ void colsum_piece(const Ctx& c, const __nv_bfloat16* W, int ldw, uint2* out) {
  const int tid = c.w * 32 + c.lane;
  const int chunk = c.b >> 1, half = c.b & 1;
  const uint4* src = reinterpret_cast<const uint4*>(W + (size_t)(half * 512 + (tid >> 3)) * ldw + chunk * 64 + (tid & 7) * 8);
  float a[8] = {0, 0, 0, 0, 0, 0, 0, 0};
#pragma unroll 1
  for (int o = 0; o < 2; o++) {
    uint4 v[16];
#pragma unroll
    for (int i = 0; i < 16; i++) { v[i] = __ldg(src); src += 2 * ldw; }
#pragma unroll
    for (int i = 0; i < 16; i++) {
      a[0] += bf_lo(v[i].x); a[1] += bf_hi(v[i].x); a[2] += bf_lo(v[i].y); a[3] += bf_hi(v[i].y);
      a[4] += bf_lo(v[i].z); a[5] += bf_hi(v[i].z); a[6] += bf_lo(v[i].w); a[7] += bf_hi(v[i].w);
    }
  }
#pragma unroll
  for (int e = 0; e < 8; e++) { a[e] += __shfl_xor_sync(0xffffffffu, a[e], 8); a[e] += __shfl_xor_sync(0xffffffffu, a[e], 16); }
  const uint32_t red = c.sb + OFF_RED;
  if (c.lane < 8) {
    sts128(red + (c.w * 64 + c.lane * 8) * 4, __float_as_uint(a[0]), __float_as_uint(a[1]), __float_as_uint(a[2]), __float_as_uint(a[3]));
    sts128(red + (c.w * 64 + c.lane * 8) * 4 + 16, __float_as_uint(a[4]), __float_as_uint(a[5]), __float_as_uint(a[6]), __float_as_uint(a[7]));
  }
  bar_sync(BAR_WG + c.wg, 128);
  if (tid < 64) {
    const float s = (lds32f(red + tid * 4) + lds32f(red + (64 + tid) * 4)) + (lds32f(red + (128 + tid) * 4) + lds32f(red + (192 + tid) * 4));
    st_tag64(out + half * NCS + chunk * 64 + tid, s, c.tag);
  }
  __syncwarp();
}

__device__ __forceinline__ void load_tables(const Ctx& c, const Params& p, bool mlp) {
  const int tid = c.w * 32 + c.lane;
  int col[4]; uint32_t dst[4]; float v[4];
#pragma unroll
  for (int k = 0; k < 4; k++) {
    const int i = min(tid + k * 128, mlp ? 447 : 383);
    const int qq = i >= 192, rem = i - qq * 192;
    const int cu = i < 192 ? c.j * 192 + i : (i < 320 ? 1536 - 192 : 2560 - 320) + c.j * 128 + i;
    const uint32_t a = c.sb + OFF_UP + (i >> 1) * 16 + (i & 1) * 4;
    if (mlp) sts32f(a + 8, __bfloat162float(p.b1[cu]));
    col[k] = mlp ? 3 * D_ + cu : (rem >> 6) * D_ + (c.j + 8 * qq) * 64 + (rem & 63);
    dst[k] = mlp ? a : c.sb + OFF_CSQ + i * 4;
  }
  sts32f(c.sb + OFF_B2 + tid * 4, __bfloat162float(p.b2[c.j * 128 + tid]));
  for (unsigned it = 0;; it++) {
    bool ok = true;
#pragma unroll
    for (int k = 0; k < 4; k++) {
      const uint2 a = ld_tag64(g_cs + col[k]), b = ld_tag64(g_cs + NCS + col[k]);
      ok = ok && a.y == c.tag && b.y == c.tag;
      v[k] = __uint_as_float(a.x) + __uint_as_float(b.x);
    }
    if (__all_sync(0xffffffffu, ok) || it > SPIN_LIMIT) break;
    __nanosleep(400);
  }
#pragma unroll
  for (int k = 0; k < 4; k++) sts32f(dst[k], v[k]);
}

__global__ void __cluster_dims__(2, 1, 1) __launch_bounds__(384, 1) fused_kernel(const __grid_constant__ Params p) {
  extern __shared__ uint8_t smem_raw[];
  Ctx c;
  c.sb = (smem_u32(smem_raw) + 1023) & ~1023u;
  const int tid = threadIdx.x;
  c.wg = __shfl_sync(0xffffffffu, tid >> 7, 0); c.w = __shfl_sync(0xffffffffu, (tid >> 5) & 3, 0); c.lane = tid & 31;
  {
    uint32_t smid; asm volatile("mov.u32 %0, %%smid;" : "=r"(smid));
    const int u = smid >> 1, cl = u >= 62 ? u - 62 : u + 4;
    const int grp = cl < 4 ? 0 : u < 32 ? u & 7 : 1 + (u - 32) % 7;
    const int idx = cl < 4 ? cl + 4 : u < 32 ? u >> 3 : 4 + (u - 32) / 7;
    c.rank = blockIdx.x & 1;
    c.m = (grp >> 2) * 8 + idx; c.j = (grp & 3) * 2 + c.rank; c.b = c.m * 8 + c.j;
  }
  c.tag = __ldcg(g_epoch + blockIdx.x) + 1;
  if (tid == 0) {
#pragma unroll
    for (int s = 0; s < 8; s++) { mbar_init(c.sb + OFF_FULL + 8 * s, 2); mbar_init(c.sb + OFF_EMPTY + 8 * s, 8); }
    mbar_init(c.sb + OFF_XBAR, 1);
    sts128(c.sb + OFF_ZERO, 0u, 0u, 0u, 0u);
    asm volatile("fence.mbarrier_init.release.cluster;" ::: "memory");
  }
  asm volatile("barrier.cluster.arrive.release.aligned;\nbarrier.cluster.wait.acquire.aligned;" ::: "memory");
  if (c.wg == 2) {
    reg_dealloc<40>();
    if (c.w < 2) {
      int g = 0;
#pragma unroll 1
      for (int t = 0; t < 14; t++) {
        const int layer = t >= 7, type = t - layer * 7;
        const bool wide = type < 2 || type == 3, own = type == 3 || t == 7;
        const int nkb = type == 6 ? 56 : 16, ns = wide ? 4 : 5, str = wide ? 40960 : 32768;
        const int nshort = type == 0 ? 3 : (type == 2 || type == 4) ? 4 : 0;
        int st = first_stage(type);
        if (c.w == 0) {
          const CUtensorMap* mp = type == 2 || type == 6 ? &p.ld_h : (t < 2 ? &p.ld_x : &p.ld_out);
          const int slab = c.m * 4 + c.rank * 2;
          const unsigned* fp = g_flags + (t * 16 + c.m) * 32 + c.lane;
          unsigned ready = own ? 15u << (c.j >> 1) * 4 : (type == 2 || type == 6) ? 0u : ~0u;
#pragma unroll 1
          for (int step = 0; step < nkb; step++, g++) {
            const int kb = own ? own_kb(c, step) : step;
            const int piece = type != 6 ? kb : step < 24 ? (step * 43) >> 7 : (step >> 1) - 4;
            for (unsigned it = 0; !((ready >> piece) & 1) && it < SPIN_LIMIT; it++) {
              unsigned v; asm volatile("ld.relaxed.gpu.global.u32 %0, [%1];" : "=r"(v) : "l"(fp) : "memory");
              ready |= __ballot_sync(0xffffffffu, v == c.tag);
              asm volatile("fence.proxy.async.global;" ::: "memory");
            }
            const int e = g - (step < nshort ? ns - 1 : ns);
            if (e >= 0) mbar_wait(c.sb + OFF_EMPTY + 8 * (e & 7), (e >> 3) & 1);
            const uint32_t full = c.sb + OFF_FULL + 8 * (g & 7);
            if (!own || step >= 2) mbar_expect_e(full, A_BYTES);
            if (!own || step >= 4) tma_ld4_mc_e(c.sb + st * str + c.rank * 8192, mp, full, kb * 64, slab);
            if (++st == ns) st = 0;
          }
        } else {
          const CUtensorMap* mp = type < 2 ? &p.w_qkv : type == 2 ? &p.w_o : type == 3 ? &p.w_1a : type < 6 ? &p.w_1b : &p.w_2;
          const int c0 = type < 2 ? (c.j + 8 * type) * 64 : 0;
          const int c2 = type < 2 ? 0 : type == 3 ? 3 * c.j : type == 4 ? 24 + 2 * c.j : type == 5 ? 40 + 2 * c.j : 2 * c.j;
#pragma unroll 1
          for (int step = 0; step < nkb; step++, g++) {
            const int e = g - (step < nshort ? ns - 1 : ns);
            if (e >= 0) mbar_wait(c.sb + OFF_EMPTY + 8 * (e & 7), (e >> 3) & 1);
            const uint32_t full = c.sb + OFF_FULL + 8 * (g & 7);
            const int kb = own ? own_kb(c, step) : step;
            mbar_expect_e(full, str - A_BYTES);
            tma_ld3_e(c.sb + st * str + A_BYTES, mp, full, c0, kb * 64, c2);
            if (++st == ns) st = 0;
          }
        }
      }
    } else if (c.w == 2) {
      bar_arrive(BAR_FREE, 160);
#pragma unroll 1
      for (int t = 0; t < 14; t++) {
        const int layer = t >= 7, type = t - layer * 7;
        const int slab = c.m * 4;
        unsigned* flag = g_flags + c.m * 32 + c.j;
        if (type == 2 || type == 6) {
          flag += (t + 1) * 512 + c.j;
          bar_sync(BAR_RES, 192);
          tma_st4_e(&p.st_out, c.sb + OFF_X, c.j * 128, slab);
          if (t < 13) {
            bulk_wait_read_e();
            bar_arrive(BAR_COPY, 64);
            PTL(t, 8);
            publish_e(flag++, c.tag);
            PTL(t, 9);
          }
          tma_st4_e(&p.st_out, c.sb + OFF_X + A_BYTES, c.j * 128 + 64, slab);
          bulk_wait_read_e();
          PTL(t, 11);
        } else {
          flag += (layer * 7 + (type < 2 ? 2 : 6)) * 512 + (type < 2 ? type : type - 3) * 8;
          const int col = type < 2 ? (c.j + 8 * type) * 64 : type == 3 ? c.j * 192 : (type == 4 ? 1536 : 2560) + c.j * 128;
#pragma unroll 1
          for (int ch = type == 3 ? -1 : 0; ch < (type < 2 ? 1 : 2); ch++) {
            bar_sync(BAR_READY, 160);
            tma_st4_e(&p.st_h, c.sb + OFF_STG, col + (ch < 0 ? 128 : ch * 64), slab);
            bulk_wait_read_e();
            if (t < 12 || ch == 0) bar_arrive(BAR_FREE, 160);
          }
          PTL(t, 14);
        }
        if (t < 13) publish_e(flag, c.tag);
        PTL(t, 6);
      }
    } else {
      mbar_expect_e(c.sb + OFF_XBAR, 32768);
#pragma unroll
      for (int i = 0; i < 4; i++) tma_ld4_e(c.sb + OFF_X + i * 8192, &p.ld_x, c.sb + OFF_XBAR, c.j * 128 + (i >> 1) * 64, c.m * 4 + (i & 1) * 2);
      const uint32_t peer = mapa(c.sb, c.rank ^ 1);
#pragma unroll 1
      for (int i = 0; i < 3; i++) {
        const int g1 = i == 0 ? 48 : i == 1 ? KB_LAYER : KB_LAYER + 48;
        bar_sync(BAR_RES, 192);
        mbar_arrive_e(c.sb + OFF_FULL);
        mbar_arrive_e(c.sb + OFF_FULL + 8);
        mbar_wait(c.sb + OFF_EMPTY + 56, ((g1 - 1) >> 3) & 1);
        bar_sync(BAR_COPY, 64);
        __nanosleep(40);
#pragma unroll
        for (int ch = 0; ch < 2; ch++)
          dsmem_copy_e(peer + ((i == 1 ? 1 : 2) + ch) * 40960, c.sb + OFF_X + ch * A_BYTES, peer + OFF_FULL + 16 + 8 * ch);
        PTL(i == 0 ? 2 : i == 1 ? 6 : 9, 10);
      }
      bar_arrive(BAR_RES, 192);
    }
  } else {
    reg_alloc<232>();
#pragma unroll 1
    for (int t = -c.wg; t < 14; t += 2) {
      const int layer = t >= 7, type = t - layer * 7;
      const int g0 = layer * KB_LAYER + type * 16;
      float acc[2][96];
      if (t < 0 || type == 2 || type == 6) {
        init_res(c, acc, t, type == 6);
        if (t >= 0) {
          const int nkb = type == 6 ? 56 : 16;
          mainloop<128, 1>(c, acc, t, type, g0, nkb);
          if (t == 13) asm volatile("barrier.cluster.arrive.relaxed.aligned;" ::: "memory");
          epi_res(c, acc);
          if (t == 13) break;
        }
        TL(t, 4);
        const int ln = t < 0 ? 0 : layer * 2 + (type == 6 ? 2 : 1);
        row_stats(c, acc, ln);
        if (t <= 2) {
          if (c.b < (t < 0 ? 96 : 112)) colsum_piece(c, t < 0 ? p.wqkv : p.w1, t < 0 ? 3 * D_ : F_, g_cs + (t < 0 ? 0 : 3 * D_));
          load_tables(c, p, t >= 0);
        }
        load_row_stats(c, ln);
        TL(t, 5);
      } else {
        if (type < 4) {
          mainloop<192, 0>(c, acc, t, type, g0, 16);
          bar_sync(BAR_EPI + c.wg, 256);
          if (type < 2) { epi_qkv(c, acc, t, type); goto done; }
          epi_up<2>(c, acc, type);
        } else {
          mainloop<128, 0>(c, acc, t, type, g0, 16);
          bar_sync(BAR_EPI + c.wg, 256);
        }
        epi_up<0>(c, acc, type);
        TL(t, 4);
      done:;
      }
      if (type != 1 && type != 5) bar_arrive(BAR_EPI + (c.wg ^ 1), 256);
    }
    if (c.wg == 1) {
      if (tid == 128) g_epoch[blockIdx.x] = c.tag;
      asm volatile("barrier.cluster.wait.aligned;" ::: "memory");
    }
  }
}

typedef CUresult (*EncodeFn)(CUtensorMap*, CUtensorMapDataType, cuuint32_t, void*, const cuuint64_t*, const cuuint64_t*,
                             const cuuint32_t*, const cuuint32_t*, CUtensorMapInterleave, CUtensorMapSwizzle,
                             CUtensorMapL2promotion, CUtensorMapFloatOOBfill);

void make_map(EncodeFn fn, CUtensorMap* m, const void* ptr, int rank, const cuuint64_t* dims, const cuuint64_t* strides, const cuuint32_t* box) {
  const cuuint32_t es[4] = {1, 1, 1, 1};
  fn(m, CU_TENSOR_MAP_DATA_TYPE_BFLOAT16, rank, const_cast<void*>(ptr), dims, strides, box, es, CU_TENSOR_MAP_INTERLEAVE_NONE,
     CU_TENSOR_MAP_SWIZZLE_128B, CU_TENSOR_MAP_L2_PROMOTION_L2_128B, CU_TENSOR_MAP_FLOAT_OOB_FILL_NONE);
}
void map_rows(EncodeFn fn, CUtensorMap* m, const void* ptr, int cols, int rows, int box_slabs, bool tokens) {
  const cuuint64_t rb = (cuuint64_t)cols * 2;
  const cuuint64_t dims[4] = {(cuuint64_t)cols, 16, 2, (cuuint64_t)(rows / 32)};
  const cuuint64_t st[3] = {tokens ? 2 * rb : rb, tokens ? rb : 16 * rb, 32 * rb};
  const cuuint32_t box[4] = {64, 16, 2, (cuuint32_t)box_slabs};
  make_map(fn, m, ptr, 4, dims, st, box);
}
void map_w(EncodeFn fn, CUtensorMap* m, const void* ptr, int K, int N, int inner, int nch) {
  const cuuint64_t dims[3] = {(cuuint64_t)inner, (cuuint64_t)K, (cuuint64_t)(N / inner)}, st[2] = {(cuuint64_t)N * 2, (cuuint64_t)inner * 2};
  const cuuint32_t box[3] = {64, 64, (cuuint32_t)nch};
  make_map(fn, m, ptr, 3, dims, st, box);
}

}

extern "C" void kernel_launch(void* const* d_in, const int* in_sizes, int n_in, void* d_out, int out_size) {
  (void)in_sizes; (void)n_in; (void)out_size;
  Params p;
  p.wqkv = (const __nv_bfloat16*)d_in[1]; p.wo = (const __nv_bfloat16*)d_in[2];
  p.w1 = (const __nv_bfloat16*)d_in[4]; p.b1 = (const __nv_bfloat16*)d_in[5];
  p.w2 = (const __nv_bfloat16*)d_in[6]; p.b2 = (const __nv_bfloat16*)d_in[7];
  void* fnp = nullptr; cudaDriverEntryPointQueryResult qr;
  cudaGetDriverEntryPoint("cuTensorMapEncodeTiled", &fnp, cudaEnableDefault, &qr);
  EncodeFn fn = (EncodeFn)fnp;
  void* h;
  cudaGetSymbolAddress(&h, g_h);
  map_rows(fn, &p.ld_x, d_in[0], D_, S_, 2, true);
  map_rows(fn, &p.ld_out, d_out, D_, S_, 2, true);
  map_rows(fn, &p.ld_h, h, F_, S_, 2, false);
  map_rows(fn, &p.st_h, h, F_, S_, 4, false);
  map_rows(fn, &p.st_out, d_out, D_, S_, 4, true);
  map_w(fn, &p.w_qkv, p.wqkv, D_, 3 * D_, D_, 3);
  map_w(fn, &p.w_o, p.wo, D_, D_, 64, 2);
  map_w(fn, &p.w_1a, p.w1, D_, F_, 64, 3);
  map_w(fn, &p.w_1b, p.w1, D_, F_, 64, 2);
  map_w(fn, &p.w_2, p.w2, F_, D_, 64, 2);
  cudaFuncSetAttribute(fused_kernel, cudaFuncAttributeMaxDynamicSharedMemorySize, SMEM_BYTES);
  fused_kernel<<<128, 384, SMEM_BYTES>>>(p);
}
```

```cpp
#include <cuda_runtime.h>
#include <cuda_bf16.h>
#include <cuda.h>
#include <stdint.h>

#define EXP 0
namespace {

constexpr int S_ = 2048, D_ = 1024, F_ = 3584;
constexpr int A_BYTES = 16384;
constexpr int OFF_X   = 163840;
constexpr int OFF_STG = OFF_X + 32768;
constexpr int OFF_CSQ = OFF_STG + 16384;
constexpr int OFF_UP  = OFF_CSQ + 1536;
constexpr int OFF_B2  = OFF_UP + 3584;
constexpr int OFF_RST = OFF_B2 + 512;
constexpr int OFF_FULL = OFF_RST + 1024;
constexpr int OFF_EMPTY = OFF_FULL + 64;
constexpr int OFF_XBAR = OFF_EMPTY + 64;
constexpr int OFF_TBL = OFF_XBAR + 8;
constexpr int OFF_ZERO = OFF_XBAR + 32;
constexpr int OFF_TAG = OFF_ZERO + 16;
constexpr int SMEM_BYTES = OFF_TAG + 16 + 1024;
constexpr int KB_LAYER = 6 * 16 + 56;
constexpr int NCS = 384 + 448;
constexpr unsigned SPIN_LIMIT = 1u << 20;
constexpr int PAUSE1 = 8, PAUSE2 = 10;
enum { BAR_START = 1, BAR_EPI = 3, BAR_WG = 5, BAR_P0 = 7, BAR_P1 = 8, BAR_RES = 9, BAR_READY = 10, BAR_FREE = 11, BAR_COPY = 12 };

struct Params {
  CUtensorMap ld_x, ld_out, ld_h, st_h, st_out, w_qkv, w_o, w_1a, w_1b, w_2;
  const __nv_bfloat16 *b1, *b2;
};

__device__ __align__(1024) __nv_bfloat16 g_h[S_ * F_];
__device__ __align__(128) uint4 g_stats[4 * S_ * 8];
__device__ __align__(128) uint2 g_cs[8 * NCS];
__device__ __align__(128) uint4 g_halo[4 * 128 * 11 * 32];
__device__ __align__(128) unsigned g_flags[14 * 16 * 32];
__device__ unsigned g_epoch[132];
#define TL(t, e)
#define PTL(t, e)
#undef TK
#define TK(t, k)

template<int N, int KEEP> __device__ __forceinline__ void wgmma_ss(float (&d)[96], uint64_t da, uint64_t db);
template<> __device__ __forceinline__ void wgmma_ss<128, 0>(float (&d)[96], uint64_t da, uint64_t db) {
  asm volatile("{\n.reg .pred p;\nsetp.ne.b32 p, 0, 0;\nwgmma.mma_async.sync.aligned.m64n128k16.f32.bf16.bf16 {%0, %1, %2, %3, %4, %5, %6, %7, %8, %9, %10, %11, %12, %13, %14, %15, %16, %17, %18, %19, %20, %21, %22, %23, %24, %25, %26, %27, %28, %29, %30, %31, %32, %33, %34, %35, %36, %37, %38, %39, %40, %41, %42, %43, %44, %45, %46, %47, %48, %49, %50, %51, %52, %53, %54, %55, %56, %57, %58, %59, %60, %61, %62, %63}, %64, %65, p, 1, 1, 0, 1;\n}"
    : "=f"(d[0]), "=f"(d[1]), "=f"(d[2]), "=f"(d[3]), "=f"(d[4]), "=f"(d[5]), "=f"(d[6]), "=f"(d[7]), "=f"(d[8]), "=f"(d[9]), "=f"(d[10]), "=f"(d[11]), "=f"(d[12]), "=f"(d[13]), "=f"(d[14]), "=f"(d[15]), "=f"(d[16]), "=f"(d[17]), "=f"(d[18]), "=f"(d[19]), "=f"(d[20]), "=f"(d[21]), "=f"(d[22]), "=f"(d[23]), "=f"(d[24]), "=f"(d[25]), "=f"(d[26]), "=f"(d[27]), "=f"(d[28]), "=f"(d[29]), "=f"(d[30]), "=f"(d[31]), "=f"(d[32]), "=f"(d[33]), "=f"(d[34]), "=f"(d[35]), "=f"(d[36]), "=f"(d[37]), "=f"(d[38]), "=f"(d[39]), "=f"(d[40]), "=f"(d[41]), "=f"(d[42]), "=f"(d[43]), "=f"(d[44]), "=f"(d[45]), "=f"(d[46]), "=f"(d[47]), "=f"(d[48]), "=f"(d[49]), "=f"(d[50]), "=f"(d[51]), "=f"(d[52]), "=f"(d[53]), "=f"(d[54]), "=f"(d[55]), "=f"(d[56]), "=f"(d[57]), "=f"(d[58]), "=f"(d[59]), "=f"(d[60]), "=f"(d[61]), "=f"(d[62]), "=f"(d[63])
    : "l"(da), "l"(db));
}
template<> __device__ __forceinline__ void wgmma_ss<128, 1>(float (&d)[96], uint64_t da, uint64_t db) {
  asm volatile("{\n.reg .pred p;\nsetp.ne.b32 p, 1, 0;\nwgmma.mma_async.sync.aligned.m64n128k16.f32.bf16.bf16 {%0, %1, %2, %3, %4, %5, %6, %7, %8, %9, %10, %11, %12, %13, %14, %15, %16, %17, %18, %19, %20, %21, %22, %23, %24, %25, %26, %27, %28, %29, %30, %31, %32, %33, %34, %35, %36, %37, %38, %39, %40, %41, %42, %43, %44, %45, %46, %47, %48, %49, %50, %51, %52, %53, %54, %55, %56, %57, %58, %59, %60, %61, %62, %63}, %64, %65, p, 1, 1, 0, 1;\n}"
    : "+f"(d[0]), "+f"(d[1]), "+f"(d[2]), "+f"(d[3]), "+f"(d[4]), "+f"(d[5]), "+f"(d[6]), "+f"(d[7]), "+f"(d[8]), "+f"(d[9]), "+f"(d[10]), "+f"(d[11]), "+f"(d[12]), "+f"(d[13]), "+f"(d[14]), "+f"(d[15]), "+f"(d[16]), "+f"(d[17]), "+f"(d[18]), "+f"(d[19]), "+f"(d[20]), "+f"(d[21]), "+f"(d[22]), "+f"(d[23]), "+f"(d[24]), "+f"(d[25]), "+f"(d[26]), "+f"(d[27]), "+f"(d[28]), "+f"(d[29]), "+f"(d[30]), "+f"(d[31]), "+f"(d[32]), "+f"(d[33]), "+f"(d[34]), "+f"(d[35]), "+f"(d[36]), "+f"(d[37]), "+f"(d[38]), "+f"(d[39]), "+f"(d[40]), "+f"(d[41]), "+f"(d[42]), "+f"(d[43]), "+f"(d[44]), "+f"(d[45]), "+f"(d[46]), "+f"(d[47]), "+f"(d[48]), "+f"(d[49]), "+f"(d[50]), "+f"(d[51]), "+f"(d[52]), "+f"(d[53]), "+f"(d[54]), "+f"(d[55]), "+f"(d[56]), "+f"(d[57]), "+f"(d[58]), "+f"(d[59]), "+f"(d[60]), "+f"(d[61]), "+f"(d[62]), "+f"(d[63])
    : "l"(da), "l"(db));
}
template<> __device__ __forceinline__ void wgmma_ss<192, 0>(float (&d)[96], uint64_t da, uint64_t db) {
  asm volatile("{\n.reg .pred p;\nsetp.ne.b32 p, 0, 0;\nwgmma.mma_async.sync.aligned.m64n192k16.f32.bf16.bf16 {%0, %1, %2, %3, %4, %5, %6, %7, %8, %9, %10, %11, %12, %13, %14, %15, %16, %17, %18, %19, %20, %21, %22, %23, %24, %25, %26, %27, %28, %29, %30, %31, %32, %33, %34, %35, %36, %37, %38, %39, %40, %41, %42, %43, %44, %45, %46, %47, %48, %49, %50, %51, %52, %53, %54, %55, %56, %57, %58, %59, %60, %61, %62, %63, %64, %65, %66, %67, %68, %69, %70, %71, %72, %73, %74, %75, %76, %77, %78, %79, %80, %81, %82, %83, %84, %85, %86, %87, %88, %89, %90, %91, %92, %93, %94, %95}, %96, %97, p, 1, 1, 0, 1;\n}"
    : "=f"(d[0]), "=f"(d[1]), "=f"(d[2]), "=f"(d[3]), "=f"(d[4]), "=f"(d[5]), "=f"(d[6]), "=f"(d[7]), "=f"(d[8]), "=f"(d[9]), "=f"(d[10]), "=f"(d[11]), "=f"(d[12]), "=f"(d[13]), "=f"(d[14]), "=f"(d[15]), "=f"(d[16]), "=f"(d[17]), "=f"(d[18]), "=f"(d[19]), "=f"(d[20]), "=f"(d[21]), "=f"(d[22]), "=f"(d[23]), "=f"(d[24]), "=f"(d[25]), "=f"(d[26]), "=f"(d[27]), "=f"(d[28]), "=f"(d[29]), "=f"(d[30]), "=f"(d[31]), "=f"(d[32]), "=f"(d[33]), "=f"(d[34]), "=f"(d[35]), "=f"(d[36]), "=f"(d[37]), "=f"(d[38]), "=f"(d[39]), "=f"(d[40]), "=f"(d[41]), "=f"(d[42]), "=f"(d[43]), "=f"(d[44]), "=f"(d[45]), "=f"(d[46]), "=f"(d[47]), "=f"(d[48]), "=f"(d[49]), "=f"(d[50]), "=f"(d[51]), "=f"(d[52]), "=f"(d[53]), "=f"(d[54]), "=f"(d[55]), "=f"(d[56]), "=f"(d[57]), "=f"(d[58]), "=f"(d[59]), "=f"(d[60]), "=f"(d[61]), "=f"(d[62]), "=f"(d[63]), "=f"(d[64]), "=f"(d[65]), "=f"(d[66]), "=f"(d[67]), "=f"(d[68]), "=f"(d[69]), "=f"(d[70]), "=f"(d[71]), "=f"(d[72]), "=f"(d[73]), "=f"(d[74]), "=f"(d[75]), "=f"(d[76]), "=f"(d[77]), "=f"(d[78]), "=f"(d[79]), "=f"(d[80]), "=f"(d[81]), "=f"(d[82]), "=f"(d[83]), "=f"(d[84]), "=f"(d[85]), "=f"(d[86]), "=f"(d[87]), "=f"(d[88]), "=f"(d[89]), "=f"(d[90]), "=f"(d[91]), "=f"(d[92]), "=f"(d[93]), "=f"(d[94]), "=f"(d[95])
    : "l"(da), "l"(db));
}
template<> __device__ __forceinline__ void wgmma_ss<192, 1>(float (&d)[96], uint64_t da, uint64_t db) {
  asm volatile("{\n.reg .pred p;\nsetp.ne.b32 p, 1, 0;\nwgmma.mma_async.sync.aligned.m64n192k16.f32.bf16.bf16 {%0, %1, %2, %3, %4, %5, %6, %7, %8, %9, %10, %11, %12, %13, %14, %15, %16, %17, %18, %19, %20, %21, %22, %23, %24, %25, %26, %27, %28, %29, %30, %31, %32, %33, %34, %35, %36, %37, %38, %39, %40, %41, %42, %43, %44, %45, %46, %47, %48, %49, %50, %51, %52, %53, %54, %55, %56, %57, %58, %59, %60, %61, %62, %63, %64, %65, %66, %67, %68, %69, %70, %71, %72, %73, %74, %75, %76, %77, %78, %79, %80, %81, %82, %83, %84, %85, %86, %87, %88, %89, %90, %91, %92, %93, %94, %95}, %96, %97, p, 1, 1, 0, 1;\n}"
    : "+f"(d[0]), "+f"(d[1]), "+f"(d[2]), "+f"(d[3]), "+f"(d[4]), "+f"(d[5]), "+f"(d[6]), "+f"(d[7]), "+f"(d[8]), "+f"(d[9]), "+f"(d[10]), "+f"(d[11]), "+f"(d[12]), "+f"(d[13]), "+f"(d[14]), "+f"(d[15]), "+f"(d[16]), "+f"(d[17]), "+f"(d[18]), "+f"(d[19]), "+f"(d[20]), "+f"(d[21]), "+f"(d[22]), "+f"(d[23]), "+f"(d[24]), "+f"(d[25]), "+f"(d[26]), "+f"(d[27]), "+f"(d[28]), "+f"(d[29]), "+f"(d[30]), "+f"(d[31]), "+f"(d[32]), "+f"(d[33]), "+f"(d[34]), "+f"(d[35]), "+f"(d[36]), "+f"(d[37]), "+f"(d[38]), "+f"(d[39]), "+f"(d[40]), "+f"(d[41]), "+f"(d[42]), "+f"(d[43]), "+f"(d[44]), "+f"(d[45]), "+f"(d[46]), "+f"(d[47]), "+f"(d[48]), "+f"(d[49]), "+f"(d[50]), "+f"(d[51]), "+f"(d[52]), "+f"(d[53]), "+f"(d[54]), "+f"(d[55]), "+f"(d[56]), "+f"(d[57]), "+f"(d[58]), "+f"(d[59]), "+f"(d[60]), "+f"(d[61]), "+f"(d[62]), "+f"(d[63]), "+f"(d[64]), "+f"(d[65]), "+f"(d[66]), "+f"(d[67]), "+f"(d[68]), "+f"(d[69]), "+f"(d[70]), "+f"(d[71]), "+f"(d[72]), "+f"(d[73]), "+f"(d[74]), "+f"(d[75]), "+f"(d[76]), "+f"(d[77]), "+f"(d[78]), "+f"(d[79]), "+f"(d[80]), "+f"(d[81]), "+f"(d[82]), "+f"(d[83]), "+f"(d[84]), "+f"(d[85]), "+f"(d[86]), "+f"(d[87]), "+f"(d[88]), "+f"(d[89]), "+f"(d[90]), "+f"(d[91]), "+f"(d[92]), "+f"(d[93]), "+f"(d[94]), "+f"(d[95])
    : "l"(da), "l"(db));
}

__device__ __forceinline__ uint32_t smem_u32(const void* p) { return (uint32_t)__cvta_generic_to_shared(p); }
__device__ __forceinline__ void mbar_arrive_cluster(uint32_t bar) { asm volatile("mbarrier.arrive.shared::cluster.b64 _, [%0];" :: "r"(bar) : "memory"); }
__device__ __forceinline__ void mbar_wait(uint32_t bar, uint32_t parity) {
  asm volatile(
    "{\n.reg .pred p;\n.reg .u32 n;\n"
    "mbarrier.try_wait.parity.shared::cta.b64 p, [%0], %1;\n"
    "@p bra.uni WAIT_DONE;\n"
    "mov.u32 n, 0;\n"
    "WAIT_LOOP:\n"
    "mbarrier.try_wait.parity.shared::cta.b64 p, [%0], %1;\n"
    "@p bra.uni WAIT_DONE;\n"
    "add.u32 n, n, 1;\n"
    "setp.lt.u32 p, n, 0x100000;\n"
    "@p bra.uni WAIT_LOOP;\n"
    "trap;\n"
    "WAIT_DONE:\n}" :: "r"(bar), "r"(parity) : "memory");
}
#define ELECT "{\n.reg .pred p;\nelect.sync _|p, 0xffffffff;\n"
__device__ __forceinline__ void mbar_init_e(uint32_t bar, uint32_t cnt) { asm volatile(ELECT "@p mbarrier.init.shared::cta.b64 [%0], %1;\n}" :: "r"(bar), "r"(cnt) : "memory"); }
__device__ __forceinline__ void mbar_arrive_e(uint32_t bar) { asm volatile(ELECT "@p mbarrier.arrive.shared::cta.b64 _, [%0];\n}" :: "r"(bar) : "memory"); }
__device__ __forceinline__ void mbar_expect_e(uint32_t bar, uint32_t bytes) { asm volatile(ELECT "@p mbarrier.arrive.expect_tx.shared::cta.b64 _, [%0], %1;\n}" :: "r"(bar), "r"(bytes) : "memory"); }
__device__ __forceinline__ void tma_ld4_e(uint32_t dst, const CUtensorMap* m, uint32_t bar, int c0, int c3) {
  asm volatile(ELECT "@p cp.async.bulk.tensor.4d.shared::cluster.global.mbarrier::complete_tx::bytes [%0], [%1, {%3, %5, %5, %4}], [%2];\n}"
    :: "r"(dst), "l"(m), "r"(bar), "r"(c0), "r"(c3), "r"(0) : "memory");
}
__device__ __forceinline__ void tma_ld4_mc_e(uint32_t dst, const CUtensorMap* m, uint32_t bar, int c0, int c3) {
  asm volatile(ELECT "@p cp.async.bulk.tensor.4d.shared::cluster.global.mbarrier::complete_tx::bytes.multicast::cluster [%0], [%1, {%3, %5, %5, %4}], [%2], %6;\n}"
    :: "r"(dst), "l"(m), "r"(bar), "r"(c0), "r"(c3), "r"(0), "h"((uint16_t)3) : "memory");
}
__device__ __forceinline__ void tma_ld3_e(uint32_t dst, const CUtensorMap* m, uint32_t bar, int c0, int c1, int c2) {
  asm volatile(ELECT "@p cp.async.bulk.tensor.3d.shared::cluster.global.mbarrier::complete_tx::bytes [%0], [%1, {%3, %4, %5}], [%2];\n}"
    :: "r"(dst), "l"(m), "r"(bar), "r"(c0), "r"(c1), "r"(c2) : "memory");
}
__device__ __forceinline__ void tma_pf3_e(const CUtensorMap* m, int c0, int c1, int c2) {
  asm volatile(ELECT "@p cp.async.bulk.prefetch.tensor.3d.L2.global [%0, {%1, %2, %3}];\n}" :: "l"(m), "r"(c0), "r"(c1), "r"(c2) : "memory");
}
__device__ __forceinline__ void tma_st4_e(const CUtensorMap* m, uint32_t src, int c0, int c3) {
  asm volatile(ELECT "@p cp.async.bulk.tensor.4d.global.shared::cta.bulk_group [%0, {%2, %4, %4, %3}], [%1];\n}"
    :: "l"(m), "r"(src), "r"(c0), "r"(c3), "r"(0) : "memory");
}
__device__ __forceinline__ void dsmem_copy_e(uint32_t dst, uint32_t src, uint32_t bar) {
  asm volatile(ELECT "@p cp.async.bulk.shared::cluster.shared::cta.mbarrier::complete_tx::bytes [%0], [%1], 16384, [%2];\n}"
    :: "r"(dst), "r"(src), "r"(bar) : "memory");
}
__device__ __forceinline__ void bulk_wait_read_e() { asm volatile(ELECT "@p cp.async.bulk.commit_group;\n@p cp.async.bulk.wait_group.read 0;\n}" ::: "memory"); __syncwarp(); }
__device__ __forceinline__ void publish_e(unsigned* flag, unsigned tag) {
  asm volatile(ELECT "@p fence.proxy.async;\n@p st.relaxed.gpu.global.u32 [%0], %1;\n}" :: "l"(flag), "r"(tag) : "memory");
  __syncwarp();
}
__device__ __forceinline__ void fence_async_smem() { asm volatile("fence.proxy.async.shared::cta;" ::: "memory"); }
__device__ __forceinline__ void wgmma_fence() { asm volatile("wgmma.fence.sync.aligned;" ::: "memory"); }
__device__ __forceinline__ void wgmma_commit() { asm volatile("wgmma.commit_group.sync.aligned;" ::: "memory"); }
template<int N> __device__ __forceinline__ void wgmma_wait() { asm volatile("wgmma.wait_group.sync.aligned %0;" :: "n"(N) : "memory"); }
__device__ __forceinline__ void bar_sync(int id, int n) { asm volatile("bar.sync %0, %1;" :: "r"(id), "r"(n) : "memory"); }
__device__ __forceinline__ void bar_arrive(int id, int n) { asm volatile("bar.arrive %0, %1;" :: "r"(id), "r"(n) : "memory"); }
__device__ __forceinline__ void bar_arrive_after(int id, uint32_t dep) {
  asm volatile("{\n.reg .u32 n;\nor.b32 n, %1, 256;\nmin.u32 n, n, 256;\nbar.arrive %0, n;\n}" :: "r"(id), "r"(dep) : "memory");
}
__device__ __forceinline__ void bar_sync_after(int id, uint32_t dep) {
  asm volatile("{\n.reg .u32 n;\nor.b32 n, %1, 256;\nmin.u32 n, n, 256;\nbar.sync %0, n;\n}" :: "r"(id), "r"(dep) : "memory");
}
__device__ __forceinline__ uint32_t mapa(uint32_t a, uint32_t r) { uint32_t d; asm("mapa.shared::cluster.u32 %0, %1, %2;" : "=r"(d) : "r"(a), "r"(r)); return d; }
__device__ __forceinline__ void st_tag128(uint4* p, uint32_t a, uint32_t b, uint32_t c, uint32_t tag) {
  asm volatile("{\n.reg .b64 lo, hi;\n.reg .b128 v;\nmov.b64 lo, {%1, %2};\nmov.b64 hi, {%3, %4};\nmov.b128 v, {lo, hi};\nst.relaxed.gpu.global.b128 [%0], v;\n}"
    :: "l"(p), "r"(a), "r"(b), "r"(c), "r"(tag) : "memory");
}
__device__ __forceinline__ uint4 ld_tag128(const uint4* p) {
  uint4 v;
  asm volatile("{\n.reg .b64 lo, hi;\n.reg .b128 v;\nld.relaxed.gpu.global.b128 v, [%4];\nmov.b128 {lo, hi}, v;\nmov.b64 {%0, %1}, lo;\nmov.b64 {%2, %3}, hi;\n}"
    : "=r"(v.x), "=r"(v.y), "=r"(v.z), "=r"(v.w) : "l"(p) : "memory");
  return v;
}
__device__ __forceinline__ void st_tag64(uint2* p, float a, uint32_t tag) {
  asm volatile("{\n.reg .b64 v;\nmov.b64 v, {%1, %2};\nst.relaxed.gpu.global.b64 [%0], v;\n}" :: "l"(p), "r"(__float_as_uint(a)), "r"(tag) : "memory");
}
__device__ __forceinline__ uint2 ld_tag64(const uint2* p) {
  uint2 v;
  asm volatile("{\n.reg .b64 v;\nld.relaxed.gpu.global.b64 v, [%2];\nmov.b64 {%0, %1}, v;\n}" : "=r"(v.x), "=r"(v.y) : "l"(p) : "memory");
  return v;
}
__device__ __forceinline__ uint32_t pack_bf16(float lo, float hi) { uint32_t r; asm("cvt.rn.bf16x2.f32 %0, %1, %2;" : "=r"(r) : "f"(hi), "f"(lo)); return r; }
__device__ __forceinline__ uint32_t relu_sq_bf16(float lo, float hi) {
  uint32_t r; asm("{\n.reg .b32 t;\ncvt.rn.relu.bf16x2.f32 t, %1, %2;\nmul.rn.bf16x2 %0, t, t;\n}" : "=r"(r) : "f"(hi), "f"(lo)); return r;
}
__device__ __forceinline__ float bf_lo(uint32_t u) { return __uint_as_float(u << 16); }
__device__ __forceinline__ float bf_hi(uint32_t u) { return __uint_as_float(u & 0xffff0000u); }
__device__ __forceinline__ void stmatrix4(uint32_t addr, uint32_t r0, uint32_t r1, uint32_t r2, uint32_t r3) {
  asm volatile("stmatrix.sync.aligned.m8n8.x4.shared.b16 [%0], {%1, %2, %3, %4};" :: "r"(addr), "r"(r0), "r"(r1), "r"(r2), "r"(r3) : "memory");
}
__device__ __forceinline__ void ldmatrix4(uint32_t addr, uint32_t (&r)[4]) {
  asm volatile("ldmatrix.sync.aligned.m8n8.x4.shared.b16 {%0, %1, %2, %3}, [%4];" : "=r"(r[0]), "=r"(r[1]), "=r"(r[2]), "=r"(r[3]) : "r"(addr) : "memory");
}
__device__ __forceinline__ uint32_t movmatrix(uint32_t a) { uint32_t d; asm volatile("movmatrix.sync.aligned.m8n8.trans.b16 %0, %1;" : "=r"(d) : "r"(a)); return d; }
__device__ __forceinline__ void mma16816_z(float (&c)[4], uint32_t a0, uint32_t a1, uint32_t a2, uint32_t a3, uint32_t b0, uint32_t b1, const float4& z) {
  asm volatile("mma.sync.aligned.m16n8k16.row.col.f32.bf16.bf16.f32 {%0,%1,%2,%3}, {%4,%5,%6,%7}, {%8,%9}, {%10,%11,%12,%13};"
    : "=f"(c[0]), "=f"(c[1]), "=f"(c[2]), "=f"(c[3]) : "r"(a0), "r"(a1), "r"(a2), "r"(a3), "r"(b0), "r"(b1), "f"(z.x), "f"(z.y), "f"(z.z), "f"(z.w));
}
__device__ __forceinline__ void mma1688_z(float (&c)[4], uint32_t a0, uint32_t a1, uint32_t b0, const float4& z) {
  asm volatile("mma.sync.aligned.m16n8k8.row.col.f32.bf16.bf16.f32 {%0,%1,%2,%3}, {%4,%5}, {%6}, {%7,%8,%9,%10};"
    : "=f"(c[0]), "=f"(c[1]), "=f"(c[2]), "=f"(c[3]) : "r"(a0), "r"(a1), "r"(b0), "f"(z.x), "f"(z.y), "f"(z.z), "f"(z.w));
}
__device__ __forceinline__ float ex2(float x) { float y; asm("ex2.approx.ftz.f32 %0, %1;" : "=f"(y) : "f"(x)); return y; }
__device__ __forceinline__ float rcp(float x) { float y; asm("rcp.approx.ftz.f32 %0, %1;" : "=f"(y) : "f"(x)); return y; }
__device__ __forceinline__ void mma16816(float (&c)[4], uint32_t a0, uint32_t a1, uint32_t a2, uint32_t a3, uint32_t b0, uint32_t b1) {
  asm volatile("mma.sync.aligned.m16n8k16.row.col.f32.bf16.bf16.f32 {%0,%1,%2,%3}, {%4,%5,%6,%7}, {%8,%9}, {%0,%1,%2,%3};"
    : "+f"(c[0]), "+f"(c[1]), "+f"(c[2]), "+f"(c[3]) : "r"(a0), "r"(a1), "r"(a2), "r"(a3), "r"(b0), "r"(b1));
}
__device__ __forceinline__ void mma1688(float (&c)[4], uint32_t a0, uint32_t a1, uint32_t b0) {
  asm volatile("mma.sync.aligned.m16n8k8.row.col.f32.bf16.bf16.f32 {%0,%1,%2,%3}, {%4,%5}, {%6}, {%0,%1,%2,%3};"
    : "+f"(c[0]), "+f"(c[1]), "+f"(c[2]), "+f"(c[3]) : "r"(a0), "r"(a1), "r"(b0));
}
__device__ __forceinline__ void sts128(uint32_t a, uint32_t x, uint32_t y, uint32_t z, uint32_t w) { asm volatile("st.shared.v4.b32 [%0], {%1,%2,%3,%4};" :: "r"(a), "r"(x), "r"(y), "r"(z), "r"(w) : "memory"); }
__device__ __forceinline__ uint4 lds128(uint32_t a) { uint4 v; asm volatile("ld.shared.v4.b32 {%0,%1,%2,%3}, [%4];" : "=r"(v.x), "=r"(v.y), "=r"(v.z), "=r"(v.w) : "r"(a) : "memory"); return v; }
__device__ __forceinline__ float2 lds64f(uint32_t a) { float2 v; asm volatile("ld.shared.v2.f32 {%0,%1}, [%2];" : "=f"(v.x), "=f"(v.y) : "r"(a) : "memory"); return v; }
__device__ __forceinline__ float4 lds128f(uint32_t a) { float4 v; asm volatile("ld.shared.v4.f32 {%0,%1,%2,%3}, [%4];" : "=f"(v.x), "=f"(v.y), "=f"(v.z), "=f"(v.w) : "r"(a) : "memory"); return v; }
__device__ __forceinline__ void sts32f(uint32_t a, float v) { asm volatile("st.shared.f32 [%0], %1;" :: "r"(a), "f"(v) : "memory"); }
__device__ __forceinline__ void sts64f(uint32_t a, float x, float y) { asm volatile("st.shared.v2.f32 [%0], {%1,%2};" :: "r"(a), "f"(x), "f"(y) : "memory"); }
template<int R> __device__ __forceinline__ void reg_alloc() { asm volatile("setmaxnreg.inc.sync.aligned.u32 %0;" :: "n"(R)); }
template<int R> __device__ __forceinline__ void reg_dealloc() { asm volatile("setmaxnreg.dec.sync.aligned.u32 %0;" :: "n"(R)); }

struct Ctx {
  uint32_t sb;
  int m, j, b, rank, wg, w, lane;
};

__device__ __forceinline__ unsigned global_tag() { unsigned v; asm volatile("ld.relaxed.gpu.global.u32 %0, [%1];" : "=r"(v) : "l"(g_epoch + blockIdx.x) : "memory"); return v + 1; }
__device__ __forceinline__ unsigned smem_tag(const Ctx& c) { unsigned v; asm volatile("ld.shared.u32 %0, [%1];" : "=r"(v) : "r"(c.sb + OFF_TAG) : "memory"); return v; }

__device__ __forceinline__ int own_kb(const Ctx& c, int step) {
  return step < 4 ? (c.j * 2) ^ step : (((c.j >> 1) * 4 + 2 * step + (step < 10 ? 12 : 0)) & 15) + (step >= 10);
}
struct WTile { const CUtensorMap* mp; int c0, c2; };
__device__ __forceinline__ WTile wtile(const Params& p, int type, int j) {
  WTile w;
  w.mp = type < 2 ? &p.w_qkv : type == 2 ? &p.w_o : type == 3 ? &p.w_1a : type < 6 ? &p.w_1b : &p.w_2;
  w.c0 = type < 2 ? (j + 8 * type) * 64 : 0;
  w.c2 = type < 2 ? 0 : type == 3 ? 3 * j : type == 4 ? 24 + 2 * j : type == 5 ? 40 + 2 * j : 2 * j;
  return w;
}
__device__ __forceinline__ int first_stage(int type) { return (0x2100433 >> (4 * type)) & 7; }

template<int BN, int RES>
__device__ __forceinline__ void mainloop(const Ctx& c, float (&acc)[2][96], int t, int type, int g, int nkb) {
  constexpr int NS = BN == 192 ? 4 : 5, STR = BN == 192 ? 40960 : 32768;
  constexpr uint64_t HA = (uint64_t)(1u << 16) | ((uint64_t)(128u | (1u << 30)) << 32), HB = (uint64_t)(512u << 16) | ((uint64_t)(64u | (1u << 30)) << 32);
  int st = first_stage(type);
  const bool own = BN == 192 && (type == 3 || t == 7);
  const uint32_t rel = mapa(c.sb + OFF_EMPTY, c.lane & 1);
  const uint32_t sb = (c.sb & 0x3ffffu) >> 4;
  uint64_t da = HA | (own ? sb + OFF_X / 16 : sb + st * (STR / 16)), db = HB | (sb + st * (STR / 16) + A_BYTES / 16);
  TL(t, 0);
  if (t > 0) bar_sync(BAR_START + c.wg, 256);
  TL(t, 1);
  mbar_wait(c.sb + OFF_FULL + 8 * (g & 7), (g >> 3) & 1);
  TL(t, 2);
  wgmma_fence();
  wgmma_ss<BN, RES>(acc[0], da, db);
  wgmma_ss<BN, RES>(acc[1], da + 64, db);
  wgmma_commit();
#pragma unroll 1
  for (int kb = 1;; kb++) {
    wgmma_fence();
#pragma unroll
    for (int k = 1; k < 4; k++) {
      if (k == 3 && kb == nkb && t < 13 && type != 1) bar_arrive(BAR_START + (c.wg ^ 1), 256);
      wgmma_ss<BN, 1>(acc[0], da + k * 2, db + k * 128);
      wgmma_ss<BN, 1>(acc[1], da + (64 + k * 2), db + k * 128);
    }
    wgmma_commit();
    if (kb == nkb) break;
    if (BN == 192 && type == 1 && (kb == PAUSE1 || kb == PAUSE2)) { bar_sync(BAR_P0, 256); bar_sync(BAR_P1, 256); }
    if (++st == NS) st = 0;
    g++;
    da = HA | (own && kb == 1 ? sb + (OFF_X + A_BYTES) / 16 : sb + st * (STR / 16)); db = HB | (sb + st * (STR / 16) + A_BYTES / 16);
    mbar_wait(c.sb + OFF_FULL + 8 * (g & 7), (g >> 3) & 1);
    wgmma_fence();
    wgmma_ss<BN, 1>(acc[0], da, db);
    wgmma_ss<BN, 1>(acc[1], da + 64, db);
    wgmma_commit();
    wgmma_wait<1>();
    if (c.lane < 2) mbar_arrive_cluster(rel + 8 * ((g - 1) & 7));
    TK(t, kb);
  }
  wgmma_wait<0>();
  if (c.lane < 2) mbar_arrive_cluster(rel + 8 * (g & 7));
  TL(t, 3);
}

__device__ __forceinline__ void load_row_stats(const Ctx& c, int ln) {
  const uint4* p = g_stats + (ln * 128 + c.m * 8) * 128 + c.w * 32 + c.lane;
  const unsigned tag = smem_tag(c);
  float s, q;
  for (unsigned it = 0;; it++) {
    uint4 v[8];
#pragma unroll
    for (int i = 0; i < 8; i++) v[i] = ld_tag128(p + i * 128);
    bool ok = true;
    s = 0.f; q = 0.f;
#pragma unroll
    for (int i = 0; i < 8; i++) { ok = ok && v[i].w == tag; s += __uint_as_float(v[i].x); q += __uint_as_float(v[i].y); }
    if (__all_sync(0xffffffffu, ok) || it > SPIN_LIMIT) break;
    __nanosleep(400);
  }
  const float mean = s * (1.0f / D_);
  const float var = fmaxf(q * (1.0f / D_) - mean * mean, 0.0f);
  sts64f(c.sb + OFF_RST + (c.w * 32 + c.lane) * 8, rsqrtf(var + 1e-5f), -mean);
  __syncwarp();
}

__device__ __forceinline__ void epi_qkv(const Ctx& c, float (&acc)[2][96], int t, int q) {
  const int lane = c.lane, w = c.w, g = lane >> 2, cc = lane & 3;
  const int layer = t >= 7;
  float rs[4], nm[4], mu[4];
#pragma unroll
  for (int r = 0; r < 4; r++) { const float2 v = lds64f(c.sb + OFF_RST + (w * 32 + 8 * r + g) * 8); rs[r] = v.x; mu[r] = v.y; nm[r] = v.x * v.y; }
  bar_sync(BAR_FREE, 160);
  uint32_t P[3][2][4][4];
  const uint32_t csb = c.sb + OFF_CSQ + q * 768 + cc * 8;
  const uint32_t stg = c.sb + OFF_STG + w * 4096;
  uint4* const halo = g_halo + ((layer * 2 + q) * 128 + c.b) * 352 + lane;
#pragma unroll
  for (int i = 1; i >= 0; i--) {
#pragma unroll
    for (int nt = 8; nt < 24; nt++) {
      const float2 cs = lds64f(csb + nt * 32);
#pragma unroll
      for (int h = 0; h < 2; h++) {
        const int r = 2 * h + i;
        uint32_t u = pack_bf16(fmaf(acc[i][4 * nt + 2 * h], rs[r], cs.x * nm[r]), fmaf(acc[i][4 * nt + 2 * h + 1], rs[r], cs.y * nm[r]));
        if (nt >= 16) u = movmatrix(u);
        P[nt >> 3][(nt >> 2) & 1][r][nt & 3] = u;
      }
    }
    if (i == 1) {
#define HW(n) P[1 + (((n) >> 4) & 1)][((n) >> 3) & 1][(((n) >> 2) & 1) * 2 + 1][(n) & 3]
      if (w < 3) {
#pragma unroll
        for (int z = 0; z < 8; z++) sts128(stg + 4096 + lane * 16 + z * 512, HW(4 * z), HW(4 * z + 1), HW(4 * z + 2), HW(4 * z + 3));
      } else if (c.m < 15) {
        const unsigned tag = smem_tag(c);
#pragma unroll
        for (int z = 0; z < 11; z++) st_tag128(halo + z * 32, HW(3 * z), HW(3 * z + 1), HW(3 * z + 2), tag);
      }
#undef HW
    }
  }
#pragma unroll
  for (int nt = 0; nt < 8; nt++) {
    const float2 cs = lds64f(csb + nt * 32);
#pragma unroll
    for (int r = 0; r < 4; r++)
      P[0][nt >> 2][r][nt & 3] = pack_bf16(fmaf(cs.x, mu[r], acc[r & 1][4 * nt + 2 * (r >> 1)]), fmaf(cs.y, mu[r], acc[r & 1][4 * nt + 2 * (r >> 1) + 1]));
  }
  TL(t, 8);
  bar_sync(BAR_WG + c.wg, 128);
  const bool nohalo = (w == 0 && c.m == 0);
  if (w == 0) {
    const unsigned tag = smem_tag(c);
    uint32_t G[33];
#pragma unroll
    for (int z = 0; z < 33; z++) G[z] = 0u;
    for (unsigned it = 0; !nohalo; it++) {
      bool ok = true;
#pragma unroll
      for (int z = 0; z < 11; z++) { const uint4 v = ld_tag128(halo - 8 * 352 + z * 32); G[3 * z] = v.x; G[3 * z + 1] = v.y; G[3 * z + 2] = v.z; ok = ok && v.w == tag; }
      if (__all_sync(0xffffffffu, ok) || it > SPIN_LIMIT) break;
    }
#pragma unroll
    for (int z = 0; z < 8; z++) sts128(stg + lane * 16 + z * 512, G[4 * z], G[4 * z + 1], G[4 * z + 2], G[4 * z + 3]);
  }
  uint32_t H[32];
#pragma unroll
  for (int z = 0; z < 8; z++) { const uint4 v = lds128(stg + lane * 16 + z * 512); H[4 * z] = v.x; H[4 * z + 1] = v.y; H[4 * z + 2] = v.z; H[4 * z + 3] = v.w; }
  TL(t, 4);
  float S[4][3][4];
  if (q == 0) bar_sync(BAR_P0, 256);
  float4 zero = lds128f(c.sb + OFF_ZERO);
  TL(t, 9);
#pragma unroll
  for (int k = 0; k < 2; k++)
#pragma unroll
    for (int z = 0; z < 4; z++) {
      const uint32_t* qa = P[0][z >> 1][2 * (z & 1)]; const uint32_t* qb = P[0][z >> 1][2 * (z & 1) + 1];
      const uint32_t* kk[3] = {H + 4 * z, P[1][z >> 1][2 * (z & 1)], P[1][z >> 1][2 * (z & 1) + 1]};
#pragma unroll
      for (int n = 0; n < 3; n++) {
        if (k == 0) mma16816_z(S[z][n], qa[0], qb[0], qa[1], qb[1], kk[n][0], kk[n][1], zero);
        else mma16816(S[z][n], qa[2], qb[2], qa[3], qb[3], kk[n][2], kk[n][3]);
      }
    }
  if (q == 0) {
    uint32_t dep = 0;
#pragma unroll
    for (int z = 0; z < 12; z++) dep |= __float_as_uint(S[z / 3][z % 3][0]);
    bar_arrive_after(BAR_P1, dep);
  }
  TL(t, 10);
  const bool far0 = 2 * cc > g, far1 = 2 * cc + 1 > g;
  const uint32_t fmask = (far0 ? 0xffffu : 0u) | (far1 ? 0xffff0000u : 0u);
  uint32_t pf[4][2], pn[4][2];
#pragma unroll
  for (int z = 0; z < 4; z++)
#pragma unroll
    for (int i = 0; i < 2; i++) {
      const float sc = rs[2 * (z & 1) + i] * (0.17677669529663687f * 1.4426950408889634f);
      float l0 = (far0 ? S[z][i][2 * i] : S[z][i + 1][2 * i]) * sc;
      float l1 = (far1 ? S[z][i][2 * i + 1] : S[z][i + 1][2 * i + 1]) * sc;
      if (i == 0 && nohalo) { const float neg = -1e9f * 1.4426950408889634f; if (far0) l0 = neg; if (far1) l1 = neg; }
      float mx = fmaxf(l0, l1);
      mx = fmaxf(mx, __shfl_xor_sync(0xffffffffu, mx, 1));
      mx = fmaxf(mx, __shfl_xor_sync(0xffffffffu, mx, 2));
      l0 = ex2(l0 - mx); l1 = ex2(l1 - mx);
      float sum = l0 + l1;
      sum += __shfl_xor_sync(0xffffffffu, sum, 1);
      sum += __shfl_xor_sync(0xffffffffu, sum, 2);
      sum = rcp(sum);
      const uint32_t u = pack_bf16(l0 * sum, l1 * sum);
      pf[z][i] = u & fmask; pn[z][i] = u & ~fmask;
    }
  float O[4][4][4];
  TL(t, 11);
  if (q == 0) bar_sync_after(BAR_P0, (pn[0][0] | pn[0][1] | pn[1][0]) | (pn[1][1] | pn[2][0] | pn[2][1]) | (pn[3][0] | pn[3][1]));
  zero = lds128f(c.sb + OFF_ZERO);
  TL(t, 12);
#pragma unroll
  for (int z = 0; z < 4; z++)
#pragma unroll
    for (int dt = 0; dt < 4; dt++) mma1688_z(O[z][dt], pn[z][0], pf[z][1], P[2][z >> 1][2 * (z & 1)][dt], zero);
#pragma unroll
  for (int z = 0; z < 4; z++)
#pragma unroll
    for (int dt = 0; dt < 4; dt++) mma1688(O[z][dt], pf[z][0], 0u, H[16 + 4 * z + dt]);
#pragma unroll
  for (int z = 0; z < 4; z++)
#pragma unroll
    for (int dt = 0; dt < 4; dt++) mma1688(O[z][dt], 0u, pn[z][1], P[2][z >> 1][2 * (z & 1) + 1][dt]);
  {
    uint32_t dep = 0;
#pragma unroll
    for (int z = 0; z < 16; z++) dep |= __float_as_uint(O[z >> 2][z & 3][2]);
    bar_arrive_after(q == 0 ? BAR_P1 : BAR_START + (c.wg ^ 1), dep);
  }
  TL(t, 5);
#pragma unroll
  for (int nt = 0; nt < 8; nt++) {
    const float* e = O[2 * (nt >> 2)][nt & 3]; const float* o = O[2 * (nt >> 2) + 1][nt & 3];
    stmatrix4(stg + lane * 128 + ((nt ^ (lane & 7)) << 4), pack_bf16(e[0], e[1]), pack_bf16(e[2], e[3]), pack_bf16(o[0], o[1]), pack_bf16(o[2], o[3]));
  }
  fence_async_smem();
  bar_arrive(BAR_READY, 160);
  TL(t, 13);
}

template<int CH>
__device__ __forceinline__ void epi_up(const Ctx& c, float (&acc)[2][96], int type) {
  const int lane = c.lane, w = c.w, g = lane >> 2, cc = lane & 3;
  float rs[4], nm[4];
#pragma unroll
  for (int r = 0; r < 4; r++) { const float2 v = lds64f(c.sb + OFF_RST + (w * 32 + 8 * r + g) * 8); rs[r] = v.x; nm[r] = v.x * v.y; }
  const int loc0 = type == 3 ? 0 : (type == 4 ? 192 : 320);
  const uint32_t cb = c.sb + OFF_UP + loc0 * 8 + cc * 16;
  const uint32_t stg = c.sb + OFF_STG + w * 4096;
#pragma unroll
  for (int ch = CH; ch < (CH ? 3 : 2); ch++) {
    uint32_t P[8][4];
#pragma unroll
    for (int n8 = 0; n8 < 8; n8++) {
      const int nt = ch * 8 + n8;
      const float4 cv = lds128f(cb + nt * 64);
#pragma unroll
      for (int r = 0; r < 4; r++)
        P[n8][r] = relu_sq_bf16(fmaf(acc[r & 1][4 * nt + 2 * (r >> 1)], rs[r], fmaf(cv.x, nm[r], cv.z)),
                                fmaf(acc[r & 1][4 * nt + 2 * (r >> 1) + 1], rs[r], fmaf(cv.y, nm[r], cv.w)));
    }
    bar_sync(BAR_FREE, 160);
#pragma unroll
    for (int n8 = 0; n8 < 8; n8++)
      stmatrix4(stg + lane * 128 + ((n8 ^ (lane & 7)) << 4), P[n8][0], P[n8][1], P[n8][2], P[n8][3]);
    fence_async_smem();
    bar_arrive(BAR_READY, 160);
  }
}

__device__ __forceinline__ void init_res(const Ctx& c, float (&acc)[2][96], int t, bool bias) {
  if (t <= 2) mbar_wait(c.sb + OFF_XBAR, 0);
  const uint32_t xb = c.sb + OFF_X + c.w * 4096 + c.lane * 128;
#pragma unroll
  for (int nt = 0; nt < 16; nt++) {
    uint32_t u[4];
    ldmatrix4(xb + (nt >> 3) * A_BYTES + (((nt & 7) ^ (c.lane & 7)) << 4), u);
    float2 b = make_float2(0.f, 0.f);
    if (bias) b = lds64f(c.sb + OFF_B2 + nt * 32 + (c.lane & 3) * 8);
#pragma unroll
    for (int r = 0; r < 4; r++) {
      acc[r & 1][4 * nt + 2 * (r >> 1)] = bf_lo(u[r]) + b.x;
      acc[r & 1][4 * nt + 2 * (r >> 1) + 1] = bf_hi(u[r]) + b.y;
    }
  }
}

__device__ __forceinline__ void epi_res(const Ctx& c, float (&acc)[2][96]) {
  const uint32_t xw = c.sb + OFF_X + c.w * 4096 + c.lane * 128;
#pragma unroll
  for (int nt = 0; nt < 16; nt++)
    stmatrix4(xw + (nt >> 3) * A_BYTES + (((nt & 7) ^ (c.lane & 7)) << 4),
              pack_bf16(acc[0][4 * nt], acc[0][4 * nt + 1]), pack_bf16(acc[1][4 * nt], acc[1][4 * nt + 1]),
              pack_bf16(acc[0][4 * nt + 2], acc[0][4 * nt + 3]), pack_bf16(acc[1][4 * nt + 2], acc[1][4 * nt + 3]));
  fence_async_smem();
  bar_arrive(BAR_RES, 192);
}

__device__ __forceinline__ void row_stats(const Ctx& c, float (&acc)[2][96], int ln) {
  const int g = c.lane >> 2, cc = c.lane & 3;
  float sm[4], sq[4];
#pragma unroll
  for (int r = 0; r < 4; r++) {
    float a = 0.f, b = 0.f;
#pragma unroll
    for (int n = 0; n < 32; n++) { const float x = acc[r & 1][4 * (n >> 1) + 2 * (r >> 1) + (n & 1)]; a += x; b = fmaf(x, x, b); }
    a += __shfl_xor_sync(0xffffffffu, a, 1); b += __shfl_xor_sync(0xffffffffu, b, 1);
    a += __shfl_xor_sync(0xffffffffu, a, 2); b += __shfl_xor_sync(0xffffffffu, b, 2);
    sm[r] = a; sq[r] = b;
  }
  const float a = cc == 0 ? sm[0] : cc == 1 ? sm[1] : cc == 2 ? sm[2] : sm[3];
  const float b = cc == 0 ? sq[0] : cc == 1 ? sq[1] : cc == 2 ? sq[2] : sq[3];
  st_tag128(g_stats + (ln * 128 + c.b) * 128 + c.w * 32 + 8 * cc + g, __float_as_uint(a), __float_as_uint(b), 0u, smem_tag(c));
}

__device__ __forceinline__ void load_table(const Ctx& c, const Params& p, int part, unsigned tag) {
  const int i0 = (part < 4 ? part * 192 : 704) + c.lane, n = part < 3 ? 6 : 4;
  const uint2* src = g_cs + c.j * NCS + i0;
  const uint32_t dst = c.sb + OFF_CSQ + (part < 2 ? i0 * 4 : 1536 + ((i0 - 384) >> 1) * 16 + (i0 & 1) * 4);
  const __nv_bfloat16* bias = p.b1 + (part == 2 ? c.j * 192 : (part == 3 ? 1536 : 2560) + c.j * 128) + c.lane;
  float v[6];
  if (part >= 2) {
#pragma unroll
    for (int k = 0; k < 6; k++) if (k < n) sts32f(dst + k * 256 + 8, __bfloat162float(bias[k * 32]));
  }
  for (unsigned it = 0;; it++) {
    bool ok = true;
#pragma unroll
    for (int k = 0; k < 6; k++) { const uint2 a = ld_tag64(src + (k < n ? k * 32 : 0)); ok = ok && a.y == tag; v[k] = __uint_as_float(a.x); }
    if (__all_sync(0xffffffffu, ok) || it > SPIN_LIMIT) break;
    __nanosleep(400);
  }
#pragma unroll
  for (int k = 0; k < 6; k++) if (k < n) sts32f(dst + k * (part < 2 ? 128 : 256), v[k]);
  __syncwarp();
}

__device__ __forceinline__ void colsum_cta(const Ctx& c, const Params& p) {
  if (c.wg < 2) mbar_init_e(c.sb + OFF_FULL + 32 * c.wg + 8 * c.w, 1);
  sts32f(c.sb + OFF_STG + threadIdx.x * 4, __uint_as_float(0x3f803f80u));
  fence_async_smem();
  __syncthreads();
  if (c.wg == 2) return;
  const unsigned tag = global_tag();
  const int j = (blockIdx.x - 128) * 2 + c.wg;
  const uint32_t ring = c.sb + c.wg * 98304, full = c.sb + OFF_FULL + 32 * c.wg;
  const uint64_t ones = (uint64_t)(((c.sb + OFF_STG) & 0x3ffffu) >> 4) | (8u << 16) | ((uint64_t)16u << 32);
  float d[3][4];
#pragma unroll 1
  for (int n = -4; n < 80; n++) {
    if (n >= 0) {
      mbar_wait(full + 8 * (n & 3), (n >> 2) & 1);
      const uint64_t da = (uint64_t)(((ring + (n & 3) * 24576) & 0x3ffffu) >> 4) | (64u << 16) | ((uint64_t)(64u | (1u << 30)) << 32);
      wgmma_fence();
#pragma unroll
      for (int k = 0; k < 4; k++)
#pragma unroll
        for (int z = 0; z < 3; z++)
          asm volatile("{\n.reg .pred p;\nsetp.ne.b32 p, %6, 0;\nwgmma.mma_async.sync.aligned.m64n8k16.f32.bf16.bf16 {%0,%1,%2,%3}, %4, %5, p, 1, 1, 1, 0;\n}"
            : "+f"(d[z][0]), "+f"(d[z][1]), "+f"(d[z][2]), "+f"(d[z][3]) : "l"(da + z * 512 + k * 128), "l"(ones), "r"((n & 15) | k));
      wgmma_commit();
      wgmma_wait<0>();
      bar_sync(BAR_WG + c.wg, 128);
      if ((n & 15) == 15 && (c.lane & 3) < 2) {
        const int u = n >> 4;
        uint2* out = g_cs + j * NCS + (u < 4 ? u * 192 : 704) + c.w * 16 + (c.lane >> 2) + (c.lane & 1) * 8;
#pragma unroll
        for (int z = 0; z < 3; z++) if (z < 2 || u < 3) st_tag64(out + z * 64, (c.lane & 1) ? d[z][2] : d[z][0], tag);
      }
      __syncwarp();
    }
    if (c.w == 0 && n < 76) {
      const int u = (n + 4) >> 4;
      const WTile w = wtile(p, u + (u >= 2), j);
      mbar_expect_e(full + 8 * (n & 3), u < 3 ? 24576 : 16384);
      tma_ld3_e(ring + (n & 3) * 24576, w.mp, full + 8 * (n & 3), w.c0, ((n + 4) & 15) * 64, w.c2);
    }
  }
  bar_sync(BAR_START, 256);
  if (threadIdx.x == 0) g_epoch[blockIdx.x] = tag;
}

__global__ void __cluster_dims__(2, 1, 1) __launch_bounds__(384, 1) fused_kernel(const __grid_constant__ Params p) {
  extern __shared__ uint8_t smem_raw[];
  Ctx c;
  c.sb = (smem_u32(smem_raw) + 1023) & ~1023u;
  const int tid = threadIdx.x;
  c.wg = __shfl_sync(0xffffffffu, tid >> 7, 0); c.w = __shfl_sync(0xffffffffu, (tid >> 5) & 3, 0); c.lane = tid & 31;
  {
    const int cl = blockIdx.x >> 1;
    const int quad = cl < 4 ? 15 : cl < 36 ? (cl - 4) & 7 : 8 + (cl - 36) % 7;
    const int idx = cl < 4 ? cl : cl < 36 ? (cl - 4) >> 3 : (cl - 36) / 7;
    c.rank = blockIdx.x & 1;
    c.m = ((quad & 1) * 2 + (quad >> 3)) * 4 + idx; c.j = (quad & 6) + c.rank; c.b = c.m * 8 + c.j;
  }
  if (blockIdx.x >= 128) { colsum_cta(c, p); return; }
  if (c.wg == 2 && c.w == 1) {
#pragma unroll 1
    for (int s = 0; s < 4; s++) {
      const uint32_t full = c.sb + OFF_FULL + 8 * s, dst = c.sb + ((s + 3) & 3) * 40960;
      mbar_init_e(full, 2);
      fence_async_smem();
      mbar_expect_e(full, 40960);
      tma_ld4_e(dst, &p.ld_x, full, s * 64, c.m * 4);
      tma_ld4_e(dst + 8192, &p.ld_x, full, s * 64, c.m * 4 + 2);
      tma_ld3_e(dst + A_BYTES, &p.w_qkv, full, c.j * 64, s * 64, 0);
      mbar_arrive_e(full);
    }
    PTL(14, 8);
  } else {
    const int k = c.wg * 4 + c.w;
    if (k < 8) { mbar_init_e(c.sb + OFF_EMPTY + 8 * k, 8); mbar_init_e(c.sb + (k < 4 ? OFF_XBAR : OFF_FULL) + 8 * k, k < 4 ? 1 : 2); }
    sts128(c.sb + OFF_ZERO, 0u, 0u, 0u, 0u);
  }
  asm volatile("fence.mbarrier_init.release.cluster;" ::: "memory");
  asm volatile("barrier.cluster.arrive.relaxed.aligned;\nbarrier.cluster.wait.aligned;" ::: "memory");
  if (tid < 32) PTL(14, 12);
  if (c.wg == 2) {
    reg_dealloc<40>();
    const unsigned tag = global_tag();
    if (c.w < 2) {
      int g = 4;
#pragma unroll 1
      for (int t = 0; t < 14; t++) {
        const int layer = t >= 7, type = t - layer * 7;
        const bool wide = type < 2 || type == 3, own = type == 3 || t == 7;
        const int nkb = type == 6 ? 56 : 16, ns = wide ? 4 : 5, str = wide ? 40960 : 32768;
        const int nshort = type == 0 ? 3 : (type == 2 || type == 4) ? 4 : 0;
        int st = first_stage(type);
        if (c.w == 0) {
          const CUtensorMap* mp = type == 2 || type == 6 ? &p.ld_h : (t < 2 ? &p.ld_x : &p.ld_out);
          const int slab = c.m * 4 + c.rank * 2;
          const unsigned* fp = g_flags + (t * 16 + c.m) * 32 + c.lane;
          unsigned ready = own ? 15u << (c.j >> 1) * 4 : (type == 2 || type == 6) ? 0u : ~0u;
#pragma unroll 1
          for (int step = t ? 0 : 4; step < nkb; step++, g++) {
            const int kb = own ? own_kb(c, step) : step;
            const int piece = type != 6 ? kb : step < 24 ? (step * 43) >> 7 : (step >> 1) - 4;
            for (unsigned it = 0; !((ready >> piece) & 1) && it < SPIN_LIMIT; it++) {
              unsigned v; asm volatile("ld.relaxed.gpu.global.u32 %0, [%1];" : "=r"(v) : "l"(fp) : "memory");
              ready |= __ballot_sync(0xffffffffu, v == tag);
              asm volatile("fence.proxy.async.global;" ::: "memory");
            }
            const int e = g - (step < nshort ? ns - 1 : ns);
            if (e >= 0) mbar_wait(c.sb + OFF_EMPTY + 8 * (e & 7), (e >> 3) & 1);
            const uint32_t full = c.sb + OFF_FULL + 8 * (g & 7);
            if (!own || step >= 2) mbar_expect_e(full, A_BYTES);
            if (!own || step >= 4) tma_ld4_mc_e(c.sb + st * str + c.rank * 8192, mp, full, kb * 64, slab);
            if (++st == ns) st = 0;
          }
        } else {
          const WTile w = wtile(p, type, c.j);
#pragma unroll 1
          for (int step = t ? 0 : 4; step < nkb; step++, g++) {
            const int e = g - (step < nshort ? ns - 1 : ns);
            if (e >= 0) mbar_wait(c.sb + OFF_EMPTY + 8 * (e & 7), (e >> 3) & 1);
            const uint32_t full = c.sb + OFF_FULL + 8 * (g & 7);
            const int kb = own ? own_kb(c, step) : step;
            mbar_expect_e(full, str - A_BYTES);
            tma_ld3_e(c.sb + st * str + A_BYTES, w.mp, full, w.c0, kb * 64, w.c2);
            if ((g & 15) == c.m && g + 16 < 2 * KB_LAYER) {
              const bool nx = step + 16 >= nkb;
              const int s2 = step + 16 - (nx ? nkb : 0);
              const WTile v = wtile(p, nx ? (type == 6 ? 0 : type + 1) : 6, c.j);
              tma_pf3_e(v.mp, v.c0, (nx && (type == 2 || type == 6) ? own_kb(c, s2) : s2) * 64, v.c2);
            }
            if (++st == ns) st = 0;
          }
        }
      }
    } else if (c.w == 2) {
      bar_arrive(BAR_FREE, 160);
#pragma unroll 1
      for (int t = 0; t < 14; t++) {
        const int layer = t >= 7, type = t - layer * 7;
        const int slab = c.m * 4;
        unsigned* flag = g_flags + c.m * 32 + c.j;
        if (type == 2 || type == 6) {
          flag += (t + 1) * 512 + c.j;
          bar_sync(BAR_RES, 192);
          tma_st4_e(&p.st_out, c.sb + OFF_X, c.j * 128, slab);
          if (t < 13) {
            bulk_wait_read_e();
            bar_arrive(BAR_COPY, 64);
            PTL(t, 8);
            publish_e(flag++, tag);
            PTL(t, 9);
          }
          tma_st4_e(&p.st_out, c.sb + OFF_X + A_BYTES, c.j * 128 + 64, slab);
          bulk_wait_read_e();
          PTL(t, 11);
        } else {
          flag += (layer * 7 + (type < 2 ? 2 : 6)) * 512 + (type < 2 ? type : type - 3) * 8;
          const int col = type < 2 ? (c.j + 8 * type) * 64 : type == 3 ? c.j * 192 : (type == 4 ? 1536 : 2560) + c.j * 128;
#pragma unroll 1
          for (int ch = type == 3 ? -1 : 0; ch < (type < 2 ? 1 : 2); ch++) {
            bar_sync(BAR_READY, 160);
            tma_st4_e(&p.st_h, c.sb + OFF_STG, col + (ch < 0 ? 128 : ch * 64), slab);
            bulk_wait_read_e();
            if (t < 12 || ch == 0) bar_arrive(BAR_FREE, 160);
          }
          PTL(t, 14);
        }
        if (t < 13) publish_e(flag, tag);
        PTL(t, 6);
      }
      if (c.lane == 0) g_epoch[blockIdx.x] = tag;
    } else {
      mbar_wait(c.sb + OFF_FULL, 0);
      PTL(14, 14);
      sts32f(c.sb + OFF_TAG, __uint_as_float(tag));
      mbar_expect_e(c.sb + OFF_XBAR, 32768);
#pragma unroll
      for (int i = 0; i < 4; i++) tma_ld4_e(c.sb + OFF_X + i * 8192, &p.ld_x, c.sb + OFF_XBAR, c.j * 128 + (i >> 1) * 64, c.m * 4 + (i & 1) * 2);
#pragma unroll
      for (int i = 0; i < 4; i++) sts32f(c.sb + OFF_B2 + i * 128 + c.lane * 4, __bfloat162float(p.b2[c.j * 128 + i * 32 + c.lane]));
      const uint32_t peer = mapa(c.sb, c.rank ^ 1);
      int part = 0;
#pragma unroll 1
      for (int i = 0; i < 3; i++) {
        const int g1 = i == 0 ? 48 : i == 1 ? KB_LAYER : KB_LAYER + 48;
#pragma unroll 1
        for (; part < (i ? 5 : 2); part++) {
          load_table(c, p, part, tag);
          if (part != 2 && part != 3) mbar_arrive_e(c.sb + OFF_TBL + 8 * (part < 2 ? part : 2));
          PTL(part, 7);
        }
        bar_sync(BAR_RES, 192);
        mbar_arrive_e(c.sb + OFF_FULL);
        mbar_arrive_e(c.sb + OFF_FULL + 8);
        mbar_wait(c.sb + OFF_EMPTY + 56, ((g1 - 1) >> 3) & 1);
        bar_sync(BAR_COPY, 64);
        __nanosleep(40);
#pragma unroll
        for (int ch = 0; ch < 2; ch++)
          dsmem_copy_e(peer + ((i == 1 ? 1 : 2) + ch) * 40960, c.sb + OFF_X + ch * A_BYTES, peer + OFF_FULL + 16 + 8 * ch);
        PTL(i == 0 ? 2 : i == 1 ? 6 : 9, 10);
      }
      bar_arrive(BAR_RES, 192);
    }
  } else {
    reg_alloc<232>();
    if (tid < 32) PTL(14, 13);
#pragma unroll 1
    for (int t = -c.wg; t < 14; t += 2) {
      const int layer = t >= 7, type = t - layer * 7;
      const int g0 = layer * KB_LAYER + type * 16;
      float acc[2][96];
      if (t < 0 || type == 2 || type == 6) {
        init_res(c, acc, t, type == 6);
        if (t >= 0) {
          const int nkb = type == 6 ? 56 : 16;
          mainloop<128, 1>(c, acc, t, type, g0, nkb);
          if (t == 13) asm volatile("barrier.cluster.arrive.relaxed.aligned;" ::: "memory");
          epi_res(c, acc);
          if (t == 13) break;
        }
        TL(t, 4);
        const int ln = t < 0 ? 0 : layer * 2 + (type == 6 ? 2 : 1);
        row_stats(c, acc, ln);
        load_row_stats(c, ln);
        TL(t, 5);
      } else {
        if (type < 4) {
          mainloop<192, 0>(c, acc, t, type, g0, 16);
          bar_sync(BAR_EPI + c.wg, 256);
          mbar_wait(c.sb + OFF_TBL + 8 * (type - (type >> 1)), 0);
          if (type < 2) { epi_qkv(c, acc, t, type); goto done; }
          epi_up<2>(c, acc, type);
        } else {
          mainloop<128, 0>(c, acc, t, type, g0, 16);
          bar_sync(BAR_EPI + c.wg, 256);
        }
        epi_up<0>(c, acc, type);
        TL(t, 4);
      done:;
      }
      if (type != 1 && type != 5) bar_arrive(BAR_EPI + (c.wg ^ 1), 256);
    }
    if (c.wg == 1) {
      asm volatile("barrier.cluster.wait.aligned;" ::: "memory");
    }
  }
}

typedef CUresult (*EncodeFn)(CUtensorMap*, CUtensorMapDataType, cuuint32_t, void*, const cuuint64_t*, const cuuint64_t*,
                             const cuuint32_t*, const cuuint32_t*, CUtensorMapInterleave, CUtensorMapSwizzle,
                             CUtensorMapL2promotion, CUtensorMapFloatOOBfill);

void make_map(EncodeFn fn, CUtensorMap* m, const void* ptr, int rank, const cuuint64_t* dims, const cuuint64_t* strides, const cuuint32_t* box) {
  const cuuint32_t es[4] = {1, 1, 1, 1};
  fn(m, CU_TENSOR_MAP_DATA_TYPE_BFLOAT16, rank, const_cast<void*>(ptr), dims, strides, box, es, CU_TENSOR_MAP_INTERLEAVE_NONE,
     CU_TENSOR_MAP_SWIZZLE_128B, CU_TENSOR_MAP_L2_PROMOTION_L2_128B, CU_TENSOR_MAP_FLOAT_OOB_FILL_NONE);
}
void map_rows(EncodeFn fn, CUtensorMap* m, const void* ptr, int cols, int rows, int box_slabs, bool tokens) {
  const cuuint64_t rb = (cuuint64_t)cols * 2;
  const cuuint64_t dims[4] = {(cuuint64_t)cols, 16, 2, (cuuint64_t)(rows / 32)};
  const cuuint64_t st[3] = {tokens ? 2 * rb : rb, tokens ? rb : 16 * rb, 32 * rb};
  const cuuint32_t box[4] = {64, 16, 2, (cuuint32_t)box_slabs};
  make_map(fn, m, ptr, 4, dims, st, box);
}
void map_w(EncodeFn fn, CUtensorMap* m, const void* ptr, int K, int N, int inner, int nch) {
  const cuuint64_t dims[3] = {(cuuint64_t)inner, (cuuint64_t)K, (cuuint64_t)(N / inner)}, st[2] = {(cuuint64_t)N * 2, (cuuint64_t)inner * 2};
  const cuuint32_t box[3] = {64, 64, (cuuint32_t)nch};
  make_map(fn, m, ptr, 3, dims, st, box);
}

}

extern "C" void kernel_launch(void* const* d_in, const int* in_sizes, int n_in, void* d_out, int out_size) {
  (void)in_sizes; (void)n_in; (void)out_size;
  Params p;
  p.b1 = (const __nv_bfloat16*)d_in[5]; p.b2 = (const __nv_bfloat16*)d_in[7];
  void* fnp = nullptr; cudaDriverEntryPointQueryResult qr;
  cudaGetDriverEntryPoint("cuTensorMapEncodeTiled", &fnp, cudaEnableDefault, &qr);
  EncodeFn fn = (EncodeFn)fnp;
  void* h;
  cudaGetSymbolAddress(&h, g_h);
  map_rows(fn, &p.ld_x, d_in[0], D_, S_, 2, true);
  map_rows(fn, &p.ld_out, d_out, D_, S_, 2, true);
  map_rows(fn, &p.ld_h, h, F_, S_, 2, false);
  map_rows(fn, &p.st_h, h, F_, S_, 4, false);
  map_rows(fn, &p.st_out, d_out, D_, S_, 4, true);
  map_w(fn, &p.w_qkv, d_in[1], D_, 3 * D_, D_, 3);
  map_w(fn, &p.w_o, d_in[2], D_, D_, 64, 2);
  map_w(fn, &p.w_1a, d_in[4], D_, F_, 64, 3);
  map_w(fn, &p.w_1b, d_in[4], D_, F_, 64, 2);
  map_w(fn, &p.w_2, d_in[6], F_, D_, 64, 2);
  cudaFuncSetAttribute(fused_kernel, cudaFuncAttributeMaxDynamicSharedMemorySize, SMEM_BYTES);
  fused_kernel<<<132, 384, SMEM_BYTES>>>(p);
}
```

```cpp
#include <cuda_runtime.h>
#include <cuda_bf16.h>
#include <cuda.h>
#include <stdint.h>

#define EXP 0
namespace {

constexpr int S_ = 2048, D_ = 1024, F_ = 3584;
constexpr int A_BYTES = 16384;
constexpr int OFF_X   = 163840;
constexpr int OFF_STG = OFF_X + 32768;
constexpr int OFF_CSQ = OFF_STG + 20480;
constexpr int OFF_UP  = OFF_CSQ + 1536;
constexpr int OFF_B2  = OFF_UP + 3584;
constexpr int OFF_RST = OFF_B2 + 512 + 256;
constexpr int OFF_FULL = OFF_RST + 1024;
constexpr int OFF_EMPTY = OFF_FULL + 64;
constexpr int OFF_XBAR = OFF_EMPTY + 64;
constexpr int OFF_TBL = OFF_XBAR + 8;
constexpr int OFF_HALO = OFF_XBAR + 32;
constexpr int OFF_SLOT = OFF_XBAR + 40;
constexpr int OFF_ZERO = OFF_XBAR + 48;
constexpr int OFF_TAG = OFF_ZERO + 16;
constexpr int SMEM_BYTES = OFF_TAG + 16 + 1024;
constexpr int KB_LAYER = 6 * 16 + 56;
constexpr int NCS = 384 + 448;
constexpr unsigned SPIN_LIMIT = 1u << 20;
constexpr int PAUSE1 = 5, PAUSE2 = PAUSE1 + 2, EARLY = (EXP & 3), HGO = (EXP & 16) ? 9 : 11;
constexpr uint32_t DESC_A = 1u << 16, DESC_B = (512u << 16) + A_BYTES / 16;
enum { BAR_START = 1, BAR_EPI = 3, BAR_WG = 5, BAR_P0 = 7, BAR_P1 = 8, BAR_RES = 9, BAR_READY = 10, BAR_FREE = 11, BAR_COPY = 12, BAR_HGO = 13 };

struct Params {
  CUtensorMap ld_x, ld_out, ld_h, st_h, st_out, w_qkv, w_o, w_1a, w_1b, w_2;
  const __nv_bfloat16 *b1, *b2;
};

__device__ __align__(1024) __nv_bfloat16 g_h[S_ * F_];
__device__ __align__(128) uint4 g_stats[4 * S_ * 8];
__device__ __align__(128) uint2 g_cs[8 * NCS];
__device__ __align__(128) uint4 g_halo[4 * 128 * 11 * 32];
__device__ __align__(128) unsigned g_flags[14 * 16 * 32];
__device__ unsigned g_epoch[132], g_slot[64];
#define TL(t, e)
#define PTL(t, e)
#if !defined(TIMELINE) || !(EXP & 8)
#undef TK
#define TK(t, k)
#endif

template<int N, int KEEP> __device__ __forceinline__ void wgmma_ss(float (&d)[96], uint32_t da, uint32_t db);
template<> __device__ __forceinline__ void wgmma_ss<128, 0>(float (&d)[96], uint32_t da, uint32_t db) {
  asm volatile("{\n.reg .pred p;\n.reg .b64 a, b;\nsetp.ne.b32 p, 0, 0;\nmov.b64 a, {%64, 0x40000080};\nmov.b64 b, {%65, 0x40000040};\nwgmma.mma_async.sync.aligned.m64n128k16.f32.bf16.bf16 {%0, %1, %2, %3, %4, %5, %6, %7, %8, %9, %10, %11, %12, %13, %14, %15, %16, %17, %18, %19, %20, %21, %22, %23, %24, %25, %26, %27, %28, %29, %30, %31, %32, %33, %34, %35, %36, %37, %38, %39, %40, %41, %42, %43, %44, %45, %46, %47, %48, %49, %50, %51, %52, %53, %54, %55, %56, %57, %58, %59, %60, %61, %62, %63}, a, b, p, 1, 1, 0, 1;\n}"
    : "=f"(d[0]), "=f"(d[1]), "=f"(d[2]), "=f"(d[3]), "=f"(d[4]), "=f"(d[5]), "=f"(d[6]), "=f"(d[7]), "=f"(d[8]), "=f"(d[9]), "=f"(d[10]), "=f"(d[11]), "=f"(d[12]), "=f"(d[13]), "=f"(d[14]), "=f"(d[15]), "=f"(d[16]), "=f"(d[17]), "=f"(d[18]), "=f"(d[19]), "=f"(d[20]), "=f"(d[21]), "=f"(d[22]), "=f"(d[23]), "=f"(d[24]), "=f"(d[25]), "=f"(d[26]), "=f"(d[27]), "=f"(d[28]), "=f"(d[29]), "=f"(d[30]), "=f"(d[31]), "=f"(d[32]), "=f"(d[33]), "=f"(d[34]), "=f"(d[35]), "=f"(d[36]), "=f"(d[37]), "=f"(d[38]), "=f"(d[39]), "=f"(d[40]), "=f"(d[41]), "=f"(d[42]), "=f"(d[43]), "=f"(d[44]), "=f"(d[45]), "=f"(d[46]), "=f"(d[47]), "=f"(d[48]), "=f"(d[49]), "=f"(d[50]), "=f"(d[51]), "=f"(d[52]), "=f"(d[53]), "=f"(d[54]), "=f"(d[55]), "=f"(d[56]), "=f"(d[57]), "=f"(d[58]), "=f"(d[59]), "=f"(d[60]), "=f"(d[61]), "=f"(d[62]), "=f"(d[63])
    : "r"(da), "r"(db));
}
template<> __device__ __forceinline__ void wgmma_ss<128, 1>(float (&d)[96], uint32_t da, uint32_t db) {
  asm volatile("{\n.reg .pred p;\n.reg .b64 a, b;\nsetp.ne.b32 p, 1, 0;\nmov.b64 a, {%64, 0x40000080};\nmov.b64 b, {%65, 0x40000040};\nwgmma.mma_async.sync.aligned.m64n128k16.f32.bf16.bf16 {%0, %1, %2, %3, %4, %5, %6, %7, %8, %9, %10, %11, %12, %13, %14, %15, %16, %17, %18, %19, %20, %21, %22, %23, %24, %25, %26, %27, %28, %29, %30, %31, %32, %33, %34, %35, %36, %37, %38, %39, %40, %41, %42, %43, %44, %45, %46, %47, %48, %49, %50, %51, %52, %53, %54, %55, %56, %57, %58, %59, %60, %61, %62, %63}, a, b, p, 1, 1, 0, 1;\n}"
    : "+f"(d[0]), "+f"(d[1]), "+f"(d[2]), "+f"(d[3]), "+f"(d[4]), "+f"(d[5]), "+f"(d[6]), "+f"(d[7]), "+f"(d[8]), "+f"(d[9]), "+f"(d[10]), "+f"(d[11]), "+f"(d[12]), "+f"(d[13]), "+f"(d[14]), "+f"(d[15]), "+f"(d[16]), "+f"(d[17]), "+f"(d[18]), "+f"(d[19]), "+f"(d[20]), "+f"(d[21]), "+f"(d[22]), "+f"(d[23]), "+f"(d[24]), "+f"(d[25]), "+f"(d[26]), "+f"(d[27]), "+f"(d[28]), "+f"(d[29]), "+f"(d[30]), "+f"(d[31]), "+f"(d[32]), "+f"(d[33]), "+f"(d[34]), "+f"(d[35]), "+f"(d[36]), "+f"(d[37]), "+f"(d[38]), "+f"(d[39]), "+f"(d[40]), "+f"(d[41]), "+f"(d[42]), "+f"(d[43]), "+f"(d[44]), "+f"(d[45]), "+f"(d[46]), "+f"(d[47]), "+f"(d[48]), "+f"(d[49]), "+f"(d[50]), "+f"(d[51]), "+f"(d[52]), "+f"(d[53]), "+f"(d[54]), "+f"(d[55]), "+f"(d[56]), "+f"(d[57]), "+f"(d[58]), "+f"(d[59]), "+f"(d[60]), "+f"(d[61]), "+f"(d[62]), "+f"(d[63])
    : "r"(da), "r"(db));
}
template<> __device__ __forceinline__ void wgmma_ss<192, 0>(float (&d)[96], uint32_t da, uint32_t db) {
  asm volatile("{\n.reg .pred p;\n.reg .b64 a, b;\nsetp.ne.b32 p, 0, 0;\nmov.b64 a, {%96, 0x40000080};\nmov.b64 b, {%97, 0x40000040};\nwgmma.mma_async.sync.aligned.m64n192k16.f32.bf16.bf16 {%0, %1, %2, %3, %4, %5, %6, %7, %8, %9, %10, %11, %12, %13, %14, %15, %16, %17, %18, %19, %20, %21, %22, %23, %24, %25, %26, %27, %28, %29, %30, %31, %32, %33, %34, %35, %36, %37, %38, %39, %40, %41, %42, %43, %44, %45, %46, %47, %48, %49, %50, %51, %52, %53, %54, %55, %56, %57, %58, %59, %60, %61, %62, %63, %64, %65, %66, %67, %68, %69, %70, %71, %72, %73, %74, %75, %76, %77, %78, %79, %80, %81, %82, %83, %84, %85, %86, %87, %88, %89, %90, %91, %92, %93, %94, %95}, a, b, p, 1, 1, 0, 1;\n}"
    : "=f"(d[0]), "=f"(d[1]), "=f"(d[2]), "=f"(d[3]), "=f"(d[4]), "=f"(d[5]), "=f"(d[6]), "=f"(d[7]), "=f"(d[8]), "=f"(d[9]), "=f"(d[10]), "=f"(d[11]), "=f"(d[12]), "=f"(d[13]), "=f"(d[14]), "=f"(d[15]), "=f"(d[16]), "=f"(d[17]), "=f"(d[18]), "=f"(d[19]), "=f"(d[20]), "=f"(d[21]), "=f"(d[22]), "=f"(d[23]), "=f"(d[24]), "=f"(d[25]), "=f"(d[26]), "=f"(d[27]), "=f"(d[28]), "=f"(d[29]), "=f"(d[30]), "=f"(d[31]), "=f"(d[32]), "=f"(d[33]), "=f"(d[34]), "=f"(d[35]), "=f"(d[36]), "=f"(d[37]), "=f"(d[38]), "=f"(d[39]), "=f"(d[40]), "=f"(d[41]), "=f"(d[42]), "=f"(d[43]), "=f"(d[44]), "=f"(d[45]), "=f"(d[46]), "=f"(d[47]), "=f"(d[48]), "=f"(d[49]), "=f"(d[50]), "=f"(d[51]), "=f"(d[52]), "=f"(d[53]), "=f"(d[54]), "=f"(d[55]), "=f"(d[56]), "=f"(d[57]), "=f"(d[58]), "=f"(d[59]), "=f"(d[60]), "=f"(d[61]), "=f"(d[62]), "=f"(d[63]), "=f"(d[64]), "=f"(d[65]), "=f"(d[66]), "=f"(d[67]), "=f"(d[68]), "=f"(d[69]), "=f"(d[70]), "=f"(d[71]), "=f"(d[72]), "=f"(d[73]), "=f"(d[74]), "=f"(d[75]), "=f"(d[76]), "=f"(d[77]), "=f"(d[78]), "=f"(d[79]), "=f"(d[80]), "=f"(d[81]), "=f"(d[82]), "=f"(d[83]), "=f"(d[84]), "=f"(d[85]), "=f"(d[86]), "=f"(d[87]), "=f"(d[88]), "=f"(d[89]), "=f"(d[90]), "=f"(d[91]), "=f"(d[92]), "=f"(d[93]), "=f"(d[94]), "=f"(d[95])
    : "r"(da), "r"(db));
}
template<> __device__ __forceinline__ void wgmma_ss<192, 1>(float (&d)[96], uint32_t da, uint32_t db) {
  asm volatile("{\n.reg .pred p;\n.reg .b64 a, b;\nsetp.ne.b32 p, 1, 0;\nmov.b64 a, {%96, 0x40000080};\nmov.b64 b, {%97, 0x40000040};\nwgmma.mma_async.sync.aligned.m64n192k16.f32.bf16.bf16 {%0, %1, %2, %3, %4, %5, %6, %7, %8, %9, %10, %11, %12, %13, %14, %15, %16, %17, %18, %19, %20, %21, %22, %23, %24, %25, %26, %27, %28, %29, %30, %31, %32, %33, %34, %35, %36, %37, %38, %39, %40, %41, %42, %43, %44, %45, %46, %47, %48, %49, %50, %51, %52, %53, %54, %55, %56, %57, %58, %59, %60, %61, %62, %63, %64, %65, %66, %67, %68, %69, %70, %71, %72, %73, %74, %75, %76, %77, %78, %79, %80, %81, %82, %83, %84, %85, %86, %87, %88, %89, %90, %91, %92, %93, %94, %95}, a, b, p, 1, 1, 0, 1;\n}"
    : "+f"(d[0]), "+f"(d[1]), "+f"(d[2]), "+f"(d[3]), "+f"(d[4]), "+f"(d[5]), "+f"(d[6]), "+f"(d[7]), "+f"(d[8]), "+f"(d[9]), "+f"(d[10]), "+f"(d[11]), "+f"(d[12]), "+f"(d[13]), "+f"(d[14]), "+f"(d[15]), "+f"(d[16]), "+f"(d[17]), "+f"(d[18]), "+f"(d[19]), "+f"(d[20]), "+f"(d[21]), "+f"(d[22]), "+f"(d[23]), "+f"(d[24]), "+f"(d[25]), "+f"(d[26]), "+f"(d[27]), "+f"(d[28]), "+f"(d[29]), "+f"(d[30]), "+f"(d[31]), "+f"(d[32]), "+f"(d[33]), "+f"(d[34]), "+f"(d[35]), "+f"(d[36]), "+f"(d[37]), "+f"(d[38]), "+f"(d[39]), "+f"(d[40]), "+f"(d[41]), "+f"(d[42]), "+f"(d[43]), "+f"(d[44]), "+f"(d[45]), "+f"(d[46]), "+f"(d[47]), "+f"(d[48]), "+f"(d[49]), "+f"(d[50]), "+f"(d[51]), "+f"(d[52]), "+f"(d[53]), "+f"(d[54]), "+f"(d[55]), "+f"(d[56]), "+f"(d[57]), "+f"(d[58]), "+f"(d[59]), "+f"(d[60]), "+f"(d[61]), "+f"(d[62]), "+f"(d[63]), "+f"(d[64]), "+f"(d[65]), "+f"(d[66]), "+f"(d[67]), "+f"(d[68]), "+f"(d[69]), "+f"(d[70]), "+f"(d[71]), "+f"(d[72]), "+f"(d[73]), "+f"(d[74]), "+f"(d[75]), "+f"(d[76]), "+f"(d[77]), "+f"(d[78]), "+f"(d[79]), "+f"(d[80]), "+f"(d[81]), "+f"(d[82]), "+f"(d[83]), "+f"(d[84]), "+f"(d[85]), "+f"(d[86]), "+f"(d[87]), "+f"(d[88]), "+f"(d[89]), "+f"(d[90]), "+f"(d[91]), "+f"(d[92]), "+f"(d[93]), "+f"(d[94]), "+f"(d[95])
    : "r"(da), "r"(db));
}

__device__ __forceinline__ uint32_t smem_u32(const void* p) { return (uint32_t)__cvta_generic_to_shared(p); }
__device__ __forceinline__ void mbar_arrive_cluster(uint32_t bar) { asm volatile("mbarrier.arrive.shared::cluster.b64 _, [%0];" :: "r"(bar) : "memory"); }
__device__ __forceinline__ void mbar_wait(uint32_t bar, uint32_t parity) {
  asm volatile(
    "{\n.reg .pred p;\n.reg .u32 n;\n"
    "mbarrier.try_wait.parity.shared::cta.b64 p, [%0], %1;\n"
    "@p bra.uni WAIT_DONE;\n"
    "mov.u32 n, 0;\n"
    "WAIT_LOOP:\n"
    "mbarrier.try_wait.parity.shared::cta.b64 p, [%0], %1;\n"
    "@p bra.uni WAIT_DONE;\n"
    "add.u32 n, n, 1;\n"
    "setp.lt.u32 p, n, 0x100000;\n"
    "@p bra.uni WAIT_LOOP;\n"
    "trap;\n"
    "WAIT_DONE:\n}" :: "r"(bar), "r"(parity) : "memory");
}
#define ELECT "{\n.reg .pred p;\nelect.sync _|p, 0xffffffff;\n"
__device__ __forceinline__ void mbar_init_e(uint32_t bar, uint32_t cnt) { asm volatile(ELECT "@p mbarrier.init.shared::cta.b64 [%0], %1;\n}" :: "r"(bar), "r"(cnt) : "memory"); }
__device__ __forceinline__ void mbar_arrive_e(uint32_t bar) { asm volatile(ELECT "@p mbarrier.arrive.shared::cta.b64 _, [%0];\n}" :: "r"(bar) : "memory"); }
__device__ __forceinline__ void mbar_expect_e(uint32_t bar, uint32_t bytes) { asm volatile(ELECT "@p mbarrier.arrive.expect_tx.shared::cta.b64 _, [%0], %1;\n}" :: "r"(bar), "r"(bytes) : "memory"); }
__device__ __forceinline__ void tma_ld4_e(uint32_t dst, const CUtensorMap* m, uint32_t bar, int c0, int c3) {
  asm volatile(ELECT "@p cp.async.bulk.tensor.4d.shared::cluster.global.mbarrier::complete_tx::bytes [%0], [%1, {%3, %5, %5, %4}], [%2];\n}"
    :: "r"(dst), "l"(m), "r"(bar), "r"(c0), "r"(c3), "r"(0) : "memory");
}
__device__ __forceinline__ void tma_ld4_mc_e(uint32_t dst, const CUtensorMap* m, uint32_t bar, int c0, int c3) {
  asm volatile(ELECT "@p cp.async.bulk.tensor.4d.shared::cluster.global.mbarrier::complete_tx::bytes.multicast::cluster [%0], [%1, {%3, %5, %5, %4}], [%2], %6;\n}"
    :: "r"(dst), "l"(m), "r"(bar), "r"(c0), "r"(c3), "r"(0), "h"((uint16_t)3) : "memory");
}
__device__ __forceinline__ void tma_ld3_e(uint32_t dst, const CUtensorMap* m, uint32_t bar, int c0, int c1, int c2) {
  asm volatile(ELECT "@p cp.async.bulk.tensor.3d.shared::cluster.global.mbarrier::complete_tx::bytes [%0], [%1, {%3, %4, %5}], [%2];\n}"
    :: "r"(dst), "l"(m), "r"(bar), "r"(c0), "r"(c1), "r"(c2) : "memory");
}
__device__ __forceinline__ void tma_pf3_e(const CUtensorMap* m, int c0, int c1, int c2) {
  asm volatile(ELECT "@p cp.async.bulk.prefetch.tensor.3d.L2.global [%0, {%1, %2, %3}];\n}" :: "l"(m), "r"(c0), "r"(c1), "r"(c2) : "memory");
}
__device__ __forceinline__ void tma_st4_e(const CUtensorMap* m, uint32_t src, int c0, int c3) {
  asm volatile(ELECT "@p cp.async.bulk.tensor.4d.global.shared::cta.bulk_group [%0, {%2, %4, %4, %3}], [%1];\n}"
    :: "l"(m), "r"(src), "r"(c0), "r"(c3), "r"(0) : "memory");
}
__device__ __forceinline__ void dsmem_copy_e(uint32_t dst, uint32_t src, uint32_t bar) {
  asm volatile(ELECT "@p cp.async.bulk.shared::cluster.shared::cta.mbarrier::complete_tx::bytes [%0], [%1], 16384, [%2];\n}"
    :: "r"(dst), "r"(src), "r"(bar) : "memory");
}
__device__ __forceinline__ void bulk_wait_read_e() { asm volatile(ELECT "@p cp.async.bulk.commit_group;\n@p cp.async.bulk.wait_group.read 0;\n}" ::: "memory"); __syncwarp(); }
__device__ __forceinline__ void publish_e(unsigned* flag, unsigned tag) {
  asm volatile(ELECT "@p fence.proxy.async;\n@p st.relaxed.gpu.global.u32 [%0], %1;\n}" :: "l"(flag), "r"(tag) : "memory");
  __syncwarp();
}
__device__ __forceinline__ void fence_async_smem() { asm volatile("fence.proxy.async.shared::cta;" ::: "memory"); }
__device__ __forceinline__ void wgmma_fence() { asm volatile("wgmma.fence.sync.aligned;" ::: "memory"); }
__device__ __forceinline__ void wgmma_commit() { asm volatile("wgmma.commit_group.sync.aligned;" ::: "memory"); }
template<int N> __device__ __forceinline__ void wgmma_wait() { asm volatile("wgmma.wait_group.sync.aligned %0;" :: "n"(N) : "memory"); }
__device__ __forceinline__ void bar_sync(int id, int n) { asm volatile("bar.sync %0, %1;" :: "r"(id), "r"(n) : "memory"); }
__device__ __forceinline__ void bar_arrive(int id, int n) { asm volatile("bar.arrive %0, %1;" :: "r"(id), "r"(n) : "memory"); }
__device__ __forceinline__ void bar_arrive_after(int id, uint32_t dep) {
  asm volatile("{\n.reg .u32 n;\nor.b32 n, %1, 256;\nmin.u32 n, n, 256;\nbar.arrive %0, n;\n}" :: "r"(id), "r"(dep) : "memory");
}
__device__ __forceinline__ void bar_sync_after(int id, uint32_t dep) {
  asm volatile("{\n.reg .u32 n;\nor.b32 n, %1, 256;\nmin.u32 n, n, 256;\nbar.sync %0, n;\n}" :: "r"(id), "r"(dep) : "memory");
}
__device__ __forceinline__ uint32_t mapa(uint32_t a, uint32_t r) { uint32_t d; asm("mapa.shared::cluster.u32 %0, %1, %2;" : "=r"(d) : "r"(a), "r"(r)); return d; }
__device__ __forceinline__ void st_tag128(uint4* p, uint32_t a, uint32_t b, uint32_t c, uint32_t tag) {
  asm volatile("{\n.reg .b64 lo, hi;\n.reg .b128 v;\nmov.b64 lo, {%1, %2};\nmov.b64 hi, {%3, %4};\nmov.b128 v, {lo, hi};\nst.relaxed.gpu.global.b128 [%0], v;\n}"
    :: "l"(p), "r"(a), "r"(b), "r"(c), "r"(tag) : "memory");
}
__device__ __forceinline__ void st_tag128_if(bool on, uint4* p, uint32_t a, uint32_t b, uint32_t c, uint32_t tag) {
  asm volatile("{\n.reg .pred q;\n.reg .b64 lo, hi;\n.reg .b128 v;\nsetp.ne.u32 q, %5, 0;\nmov.b64 lo, {%1, %2};\nmov.b64 hi, {%3, %4};\nmov.b128 v, {lo, hi};\n@q st.relaxed.gpu.global.b128 [%0], v;\n}"
    :: "l"(p), "r"(a), "r"(b), "r"(c), "r"(tag), "r"((uint32_t)on) : "memory");
}
__device__ __forceinline__ uint4 ld_tag128(const uint4* p) {
  uint4 v;
  asm volatile("{\n.reg .b64 lo, hi;\n.reg .b128 v;\nld.relaxed.gpu.global.b128 v, [%4];\nmov.b128 {lo, hi}, v;\nmov.b64 {%0, %1}, lo;\nmov.b64 {%2, %3}, hi;\n}"
    : "=r"(v.x), "=r"(v.y), "=r"(v.z), "=r"(v.w) : "l"(p) : "memory");
  return v;
}
__device__ __forceinline__ void st_tag64(uint2* p, float a, uint32_t tag) {
  asm volatile("{\n.reg .b64 v;\nmov.b64 v, {%1, %2};\nst.relaxed.gpu.global.b64 [%0], v;\n}" :: "l"(p), "r"(__float_as_uint(a)), "r"(tag) : "memory");
}
__device__ __forceinline__ uint2 ld_tag64(const uint2* p) {
  uint2 v;
  asm volatile("{\n.reg .b64 v;\nld.relaxed.gpu.global.b64 v, [%2];\nmov.b64 {%0, %1}, v;\n}" : "=r"(v.x), "=r"(v.y) : "l"(p) : "memory");
  return v;
}
__device__ __forceinline__ uint32_t pack_bf16(float lo, float hi) { uint32_t r; asm("cvt.rn.bf16x2.f32 %0, %1, %2;" : "=r"(r) : "f"(hi), "f"(lo)); return r; }
__device__ __forceinline__ uint32_t relu_sq_bf16(float lo, float hi) {
  uint32_t r; asm("{\n.reg .b32 t;\ncvt.rn.relu.bf16x2.f32 t, %1, %2;\nmul.rn.bf16x2 %0, t, t;\n}" : "=r"(r) : "f"(hi), "f"(lo)); return r;
}
__device__ __forceinline__ float bf_lo(uint32_t u) { return __uint_as_float(u << 16); }
__device__ __forceinline__ float bf_hi(uint32_t u) { return __uint_as_float(u & 0xffff0000u); }
__device__ __forceinline__ void stmatrix4(uint32_t addr, uint32_t r0, uint32_t r1, uint32_t r2, uint32_t r3) {
  asm volatile("stmatrix.sync.aligned.m8n8.x4.shared.b16 [%0], {%1, %2, %3, %4};" :: "r"(addr), "r"(r0), "r"(r1), "r"(r2), "r"(r3) : "memory");
}
__device__ __forceinline__ void ldmatrix4(uint32_t addr, uint32_t (&r)[4]) {
  asm volatile("ldmatrix.sync.aligned.m8n8.x4.shared.b16 {%0, %1, %2, %3}, [%4];" : "=r"(r[0]), "=r"(r[1]), "=r"(r[2]), "=r"(r[3]) : "r"(addr) : "memory");
}
__device__ __forceinline__ void stmatrix4_t(uint32_t addr, uint32_t r0, uint32_t r1, uint32_t r2, uint32_t r3) {
  asm volatile("stmatrix.sync.aligned.m8n8.x4.trans.shared.b16 [%0], {%1, %2, %3, %4};" :: "r"(addr), "r"(r0), "r"(r1), "r"(r2), "r"(r3) : "memory");
}
__device__ __forceinline__ void ldmatrix4_t(uint32_t addr, uint32_t (&r)[4]) {
  asm volatile("ldmatrix.sync.aligned.m8n8.x4.trans.shared.b16 {%0, %1, %2, %3}, [%4];" : "=r"(r[0]), "=r"(r[1]), "=r"(r[2]), "=r"(r[3]) : "r"(addr) : "memory");
}
__device__ __forceinline__ uint32_t movmatrix(uint32_t a) { uint32_t d; asm volatile("movmatrix.sync.aligned.m8n8.trans.b16 %0, %1;" : "=r"(d) : "r"(a)); return d; }
__device__ __forceinline__ void mma16816_z(float (&c)[4], uint32_t a0, uint32_t a1, uint32_t a2, uint32_t a3, uint32_t b0, uint32_t b1, const float4& z) {
  asm volatile("mma.sync.aligned.m16n8k16.row.col.f32.bf16.bf16.f32 {%0,%1,%2,%3}, {%4,%5,%6,%7}, {%8,%9}, {%10,%11,%12,%13};"
    : "=f"(c[0]), "=f"(c[1]), "=f"(c[2]), "=f"(c[3]) : "r"(a0), "r"(a1), "r"(a2), "r"(a3), "r"(b0), "r"(b1), "f"(z.x), "f"(z.y), "f"(z.z), "f"(z.w));
}
__device__ __forceinline__ float ex2(float x) { float y; asm("ex2.approx.ftz.f32 %0, %1;" : "=f"(y) : "f"(x)); return y; }
__device__ __forceinline__ float rcp(float x) { float y; asm("rcp.approx.ftz.f32 %0, %1;" : "=f"(y) : "f"(x)); return y; }
__device__ __forceinline__ void mma16816(float (&c)[4], uint32_t a0, uint32_t a1, uint32_t a2, uint32_t a3, uint32_t b0, uint32_t b1) {
  asm volatile("mma.sync.aligned.m16n8k16.row.col.f32.bf16.bf16.f32 {%0,%1,%2,%3}, {%4,%5,%6,%7}, {%8,%9}, {%0,%1,%2,%3};"
    : "+f"(c[0]), "+f"(c[1]), "+f"(c[2]), "+f"(c[3]) : "r"(a0), "r"(a1), "r"(a2), "r"(a3), "r"(b0), "r"(b1));
}
__device__ __forceinline__ void sts128(uint32_t a, uint32_t x, uint32_t y, uint32_t z, uint32_t w) { asm volatile("st.shared.v4.b32 [%0], {%1,%2,%3,%4};" :: "r"(a), "r"(x), "r"(y), "r"(z), "r"(w) : "memory"); }
__device__ __forceinline__ float2 lds64f(uint32_t a) { float2 v; asm volatile("ld.shared.v2.f32 {%0,%1}, [%2];" : "=f"(v.x), "=f"(v.y) : "r"(a) : "memory"); return v; }
__device__ __forceinline__ float4 lds128f(uint32_t a) { float4 v; asm volatile("ld.shared.v4.f32 {%0,%1,%2,%3}, [%4];" : "=f"(v.x), "=f"(v.y), "=f"(v.z), "=f"(v.w) : "r"(a) : "memory"); return v; }
__device__ __forceinline__ void sts32f(uint32_t a, float v) { asm volatile("st.shared.f32 [%0], %1;" :: "r"(a), "f"(v) : "memory"); }
__device__ __forceinline__ void sts64f(uint32_t a, float x, float y) { asm volatile("st.shared.v2.f32 [%0], {%1,%2};" :: "r"(a), "f"(x), "f"(y) : "memory"); }
__device__ __forceinline__ uint32_t lds32(uint32_t a) { uint32_t v; asm volatile("ld.shared.u32 %0, [%1];" : "=r"(v) : "r"(a) : "memory"); return v; }
__device__ __forceinline__ float after(float x, uint32_t d, uint32_t zero) { return __uint_as_float(__float_as_uint(x) | (d & zero)); }
template<int R> __device__ __forceinline__ void reg_alloc() { asm volatile("setmaxnreg.inc.sync.aligned.u32 %0;" :: "n"(R)); }
template<int R> __device__ __forceinline__ void reg_dealloc() { asm volatile("setmaxnreg.dec.sync.aligned.u32 %0;" :: "n"(R)); }

struct Ctx {
  uint32_t sb;
  int m, j, b, rank, wg, w, lane;
};

__device__ __forceinline__ unsigned global_tag() { unsigned v; asm volatile("ld.relaxed.gpu.global.u32 %0, [%1];" : "=r"(v) : "l"(g_epoch + blockIdx.x) : "memory"); return v + 1; }
__device__ __forceinline__ unsigned smem_tag(const Ctx& c) { return lds32(c.sb + OFF_TAG); }

__device__ __forceinline__ int own_kb(const Ctx& c, int step) {
  return step < 4 ? (c.j * 2) ^ step : (((c.j >> 1) * 4 + 2 * step + (step < 10 ? 12 : 0)) & 15) + (step >= 10);
}
__device__ __forceinline__ int kb_order(const Ctx& c, int t, int type, int step) {
  return type == 3 || t == 7 ? own_kb(c, step) : type != 2 || step < 8 ? step : step < 10 ? c.j ^ step : 8 + (((c.j & 6) + step) & 7);
}
struct WTile { const CUtensorMap* mp; int c0, c2; };
__device__ __forceinline__ WTile wtile(const Params& p, int type, int j) {
  WTile w;
  w.mp = type < 2 ? &p.w_qkv : type == 2 ? &p.w_o : type == 3 ? &p.w_1a : type < 6 ? &p.w_1b : &p.w_2;
  w.c0 = type < 2 ? (j + 8 * type) * 64 : 0;
  w.c2 = type < 2 ? 0 : type == 3 ? 3 * j : type == 4 ? 24 + 2 * j : type == 5 ? 40 + 2 * j : 2 * j;
  return w;
}
__device__ __forceinline__ int first_stage(int type) { return (0x2100433 >> (4 * type)) & 7; }

template<int BN, int RES>
__device__ __forceinline__ void mainloop(const Ctx& c, float (&acc)[2][96], int t, int type, int g, int nkb) {
  constexpr int NS = BN == 192 ? 4 : 5, STR = BN == 192 ? 40960 : 32768;
  constexpr int HL = 2;
  int st = first_stage(type);
  const bool own = BN == 192 && (type == 3 || t == 7);
  const uint32_t rel = mapa(c.sb + OFF_EMPTY, c.lane & 1);
  const uint32_t sb = (c.sb & 0x3ffffu) >> 4;
  uint32_t da = DESC_A + (own ? sb + OFF_X / 16 : sb + st * (STR / 16)), db = DESC_B + sb + st * (STR / 16);
  TL(t, 0);
  if (t > 0) bar_sync(BAR_START + c.wg, 256);
  if (RES && type == 2 && EARLY == 0) bar_sync(BAR_P1, 256);
  TL(t, 1);
  mbar_wait(c.sb + OFF_FULL + 8 * (g & 7), (g >> 3) & 1);
  TL(t, 2);
  wgmma_fence();
  wgmma_ss<BN, RES>(acc[0], da, db);
  wgmma_ss<BN, RES>(acc[1], da + 64, db);
  if (HL == 2) { wgmma_ss<BN, 1>(acc[0], da + 2, db + 128); wgmma_ss<BN, 1>(acc[1], da + 66, db + 128); }
  wgmma_commit();
#pragma unroll 1
  for (int kb = 1;; kb++) {
    wgmma_fence();
#pragma unroll
    for (int k = HL; k < 4; k++) {
      if (k == (BN == 128 ? 2 : 3) && kb == nkb && t < 13 && type > 1) bar_arrive(BAR_START + (c.wg ^ 1), 256);
      wgmma_ss<BN, 1>(acc[0], da + k * 2, db + k * 128);
      wgmma_ss<BN, 1>(acc[1], da + (64 + k * 2), db + k * 128);
    }
    wgmma_commit();
    if (kb == nkb) break;
    if (BN == 192 && type == 1 && (kb == PAUSE1 || kb == PAUSE2)) { bar_sync(BAR_P0, 256); bar_sync(BAR_P1, 256); }
    if (RES && type == 2 && kb == EARLY) bar_sync(BAR_P1, 256);
    if (++st == NS) st = 0;
    g++;
    da = DESC_A + sb + (own && kb == 1 ? (OFF_X + A_BYTES) / 16 : RES && type == 2 && kb == 8 ? OFF_STG / 16 : st * (STR / 16)); db = DESC_B + sb + st * (STR / 16);
    mbar_wait(c.sb + OFF_FULL + 8 * (g & 7), (g >> 3) & 1);
    wgmma_fence();
    wgmma_ss<BN, 1>(acc[0], da, db);
    wgmma_ss<BN, 1>(acc[1], da + 64, db);
    if (HL == 2) { wgmma_ss<BN, 1>(acc[0], da + 2, db + 128); wgmma_ss<BN, 1>(acc[1], da + 66, db + 128); }
    wgmma_commit();
    wgmma_wait<1>();
    if (c.lane < 2) mbar_arrive_cluster(rel + 8 * ((g - 1) & 7));
    TK(t, kb);
  }
}
__device__ __forceinline__ void release(const Ctx& c, int slot, int lanes = 2) {
  if (c.lane < lanes) mbar_arrive_cluster(mapa(c.sb + OFF_EMPTY, c.lane & 1) + 8 * slot);
}
__device__ __forceinline__ void finish(const Ctx& c, int t) {
  wgmma_wait<0>();
  release(c, 7);
  TL(t, 3);
}

__device__ __forceinline__ void load_row_stats(const Ctx& c, int ln) {
  const uint4* p = g_stats + (ln * 128 + c.m * 8) * 128 + c.w * 32 + c.lane;
  const unsigned tag = smem_tag(c);
  float s, q;
  for (unsigned it = 0;; it++) {
    uint4 v[8];
#pragma unroll
    for (int i = 0; i < 8; i++) v[i] = ld_tag128(p + i * 128);
    bool ok = true;
    s = 0.f; q = 0.f;
#pragma unroll
    for (int i = 0; i < 8; i++) { ok = ok && v[i].w == tag; s += __uint_as_float(v[i].x); q += __uint_as_float(v[i].y); }
    if (__all_sync(0xffffffffu, ok) || it > SPIN_LIMIT) break;
    __nanosleep(400);
  }
  const float mean = s * (1.0f / D_);
  const float var = fmaxf(q * (1.0f / D_) - mean * mean, 0.0f);
  sts64f(c.sb + OFF_RST + (c.w * 32 + c.lane) * 8, rsqrtf(var + 1e-5f), -mean);
  __syncwarp();
}

__device__ __forceinline__ void put_halo(uint32_t addr, int z, uint32_t a, uint32_t b, uint32_t c, uint32_t d) {
  if (z < 10) stmatrix4(addr + z * 384, a, b, c, d);
  else asm volatile("stmatrix.sync.aligned.m8n8.x2.shared.b16 [%0], {%1, %2};" :: "r"(addr + z * 384), "r"(a), "r"(b) : "memory");
}

__device__ __forceinline__ void fetch_halo(const Ctx& c, unsigned tag, int tile) {
  const int z0 = (c.w & 1) * 5;
  const uint4* src = g_halo + (tile * 128 + c.b - 8) * 352 + z0 * 32 + c.lane;
  uint4 G[6];
#pragma unroll
  for (int z = 0; z < 6; z++) G[z] = make_uint4(0u, 0u, 0u, 0u);
  bar_sync(BAR_HGO, 96);
  for (unsigned it = 0; c.m > 0; it++) {
    bool ok = true;
#pragma unroll
    for (int z = 0; z < 6; z++) { G[z] = ld_tag128(src + z * 32); ok = ok && G[z].w == tag; }
    if (__all_sync(0xffffffffu, ok) || it > SPIN_LIMIT) break;
  }
#pragma unroll
  for (int z = 0; z < 6; z++) put_halo(c.sb + OFF_STG + (z0 - 5) * 384 + c.lane * 16, z + 5, G[z].x, G[z].y, G[z].z, G[z].w);
  if (z0) sts32f(c.sb + OFF_RST - 256 + c.lane * 8, __uint_as_float(G[5].z));
  __syncwarp();
  mbar_arrive_e(c.sb + OFF_HALO);
}

__device__ __forceinline__ void epi_qkv(const Ctx& c, float (&acc)[2][96], int t, int q) {
  const int lane = c.lane, w = c.w, g = lane >> 2, cc = lane & 3;
  const int layer = t >= 7;
  const uint32_t sb = (c.sb & 0x3ffffu) >> 4, par = layer ^ 1;
  uint32_t da = DESC_A + sb + 64, db = DESC_B + sb;
#define MMA(i, n) do { wgmma_ss<192, 1>(acc[i], da, db); \
    asm volatile("add.s32 %0, %0, %2;\nadd.s32 %1, %1, %3;" : "+r"(da), "+r"(db) : "r"((n) == 11 ? -5190 : ((n) & 3) == 3 ? 2554 : 2), "r"((n) == 11 ? -5504 : ((n) & 3) == 3 ? 2176 : 128)); } while (0)
  mbar_wait(c.sb + OFF_FULL + 40, par);
  wgmma_fence();
  MMA(1, 0); MMA(1, 1); MMA(1, 2); MMA(1, 3);
  wgmma_commit();
  wgmma_wait<1>();
  release(c, 4);
  mbar_wait(c.sb + OFF_FULL + 48, par);
  MMA(1, 4); MMA(1, 5);
  bar_sync(BAR_EPI + c.wg, 256);
  MMA(1, 6);
  mbar_wait(c.sb + OFF_TBL + 8 * q, 0);
  MMA(1, 7);
  mbar_wait(c.sb + OFF_FULL + 56, par);
  MMA(1, 8);
  bar_sync(BAR_FREE, 160);
  MMA(1, 9);
  const uint32_t rst = c.sb + OFF_RST + w * 256;
  float mu[4];
#pragma unroll
  for (int r = 0; r < 4; r++) mu[r] = __uint_as_float(lds32(rst + (8 * r + g) * 8 + 4));
  const uint32_t tag = smem_tag(c), rs_l = lds32(rst + lane * 8);
  const uint32_t csb = c.sb + OFF_CSQ + q * 768 + cc * 16;
  const uint32_t stg = c.sb + OFF_STG + w * 4096;
  uint4* const halo = g_halo + ((layer * 2 + q) * 128 + c.b) * 352 + lane;
  const bool send = w == 3 && c.m < 15, nohalo = w == 0 && c.m == 0;
  const int now = q == 1 && w == 0 && !(EXP & 4) ? 0 : 2;
  float4 cs = lds128f(csb + 4 * 64);
  MMA(1, 10); MMA(1, 11);
  wgmma_commit();
  MMA(0, 0);
  wgmma_commit();
  MMA(0, 1);
  wgmma_commit();
  wgmma_wait<2>();
  TL(t, 8);
  uint32_t P[3][2][4][4];
#define CONV(i, np) do { _Pragma("unroll") for (int z = 0; z < 4; z++) { const int nt = 2 * (np) + (z & 1), h = z >> 1; \
    P[nt >> 3][(nt >> 2) & 1][2 * h + (i)][nt & 3] = pack_bf16(fmaf(z & 1 ? cs.z : cs.x, mu[2 * h + (i)], acc[i][4 * nt + 2 * h]), \
                                                              fmaf(z & 1 ? cs.w : cs.y, mu[2 * h + (i)], acc[i][4 * nt + 2 * h + 1])); } } while (0)
#define HW(u) ((u) == 32 ? rs_l : P[1 + (((u) >> 4) & 1)][((u) >> 3) & 1][((u) & 2) + 1][(((u) >> 1) & 2) + ((u) & 1)])
#pragma unroll
  for (int n = 0; n < 12; n++) {
    const int np = (n + 4) % 12;
    if (n == HGO && w == 0) bar_arrive(BAR_HGO, 96);
    if (n == 8) bar_arrive(BAR_START + (c.wg ^ 1), 256);
    if (n < 10) { MMA(0, n + 2); wgmma_commit(); }
    CONV(1, np);
    cs = lds128f(csb + (n < 11 ? (n + 5) % 12 : 0) * 64);
#pragma unroll
    for (int z = 0; z < 11; z++)
      if (n < 8 && z >= 4 * n / 3 && (n == 7 || z < 4 * (n + 1) / 3)) {
        st_tag128_if(send, halo + z * 32, HW(3 * z), HW(3 * z + 1), HW(3 * z + 2), tag);
        put_halo(stg + 4096 + lane * 16, z, HW(3 * z), HW(3 * z + 1), HW(3 * z + 2), tag);
      }
    if (n < 10) wgmma_wait<2>();
    if (n == 3 || n == 7) release(c, 5 + (n >> 2), n == 3 ? 2 : now);
  }
#undef MMA
  wgmma_wait<0>();
  release(c, 7, now);
  TL(t, 3);
#pragma unroll
  for (int np = 0; np < 12; np++) {
    CONV(0, np);
    if (np < 11) cs = lds128f(csb + (np + 1) * 64);
  }
#undef CONV
#pragma unroll
  for (int z = 0; z < 16; z++) P[2][z >> 3][(z >> 1) & 2][z & 3] = movmatrix(P[2][z >> 3][(z >> 1) & 2][z & 3]);
  uint32_t K1[4][4], V1[4][4];
  const uint32_t hl = stg + (lane & 15) * 16 + (lane >> 4) * 512;
#define HZ(z) (((z) >> 1) * 1024 + ((z) & 1) * 256)
  __syncwarp();
#pragma unroll
  for (int z = 0; z < 4; z++) { ldmatrix4(hl + 4096 + HZ(z), K1[z]); ldmatrix4_t(hl + 4096 + 2048 + HZ(z), V1[z]); }
  TL(t, 9);
  bar_sync(BAR_WG + c.wg, 128);
  if (w == 0) mbar_wait(c.sb + OFF_HALO, q);
  release(c, 6, 2 - now); release(c, 7, 2 - now);
#undef HW
  uint32_t HK[4][4], HV[4][4];
#pragma unroll
  for (int z = 0; z < 4; z++) ldmatrix4(hl + HZ(z), HK[z]);
#pragma unroll
  for (int z = 0; z < 4; z++) ldmatrix4_t(hl + 2048 + HZ(z), HV[z]);
#undef HZ
  const bool far0 = 2 * cc > g, far1 = 2 * cc + 1 > g;
  float rk[4][2], sc[4][2];
#pragma unroll
  for (int r = 0; r < 4; r++) {
    const float rq = __uint_as_float(lds32(rst + (8 * r + g) * 8)) * (0.17677669529663687f * 1.4426950408889634f);
    const int back = r & 1 ? 64 : 192;
    rk[r][0] = __uint_as_float(lds32(rst + r * 64 + cc * 16 - (far0 ? back : 0)));
    rk[r][1] = __uint_as_float(lds32(rst + r * 64 + cc * 16 + 8 - (far1 ? back : 0)));
    sc[r][0] = rq * rk[r][0]; sc[r][1] = rq * rk[r][1];
  }
  TL(t, 4);
  float S[4][3][4];
  if (q == 0) bar_sync(BAR_P0, 256);
  float4 zero = lds128f(c.sb + OFF_ZERO);
#pragma unroll
  for (int k = 0; k < 2; k++)
#pragma unroll
    for (int z = 0; z < 4; z++) {
      const uint32_t* qa = P[0][z >> 1][2 * (z & 1)]; const uint32_t* qb = P[0][z >> 1][2 * (z & 1) + 1];
      const uint32_t* kk[3] = {HK[z], P[1][z >> 1][2 * (z & 1)], K1[z]};
#pragma unroll
      for (int n = 0; n < 3; n++) {
        if (k == 0) mma16816_z(S[z][n], qa[0], qb[0], qa[1], qb[1], kk[n][0], kk[n][1], zero);
        else mma16816(S[z][n], qa[2], qb[2], qa[3], qb[3], kk[n][2], kk[n][3]);
      }
    }
  if (q == 0) {
    uint32_t dep = 0;
#pragma unroll
    for (int z = 0; z < 12; z++) dep |= __float_as_uint(S[z / 3][z % 3][0]);
    bar_arrive_after(BAR_P1, dep);
  }
  TL(t, 10);
  const uint32_t fmask = (far0 ? 0xffffu : 0u) | (far1 ? 0xffff0000u : 0u);
  uint32_t pf[4][2], pn[4][2];
#pragma unroll
  for (int z = 0; z < 4; z++)
#pragma unroll
    for (int i = 0; i < 2; i++) {
      const int r = 2 * (z & 1) + i;
      float l0 = (far0 ? S[z][i][2 * i] : S[z][i + 1][2 * i]) * sc[r][0];
      float l1 = (far1 ? S[z][i][2 * i + 1] : S[z][i + 1][2 * i + 1]) * sc[r][1];
      if (i == 0 && nohalo) { const float neg = -1e9f * 1.4426950408889634f; if (far0) l0 = neg; if (far1) l1 = neg; }
      float mx = fmaxf(l0, l1);
      mx = fmaxf(mx, __shfl_xor_sync(0xffffffffu, mx, 1));
      mx = fmaxf(mx, __shfl_xor_sync(0xffffffffu, mx, 2));
      l0 = ex2(l0 - mx); l1 = ex2(l1 - mx);
      float sum = l0 + l1;
      l0 *= rk[r][0]; l1 *= rk[r][1];
      sum += __shfl_xor_sync(0xffffffffu, sum, 1);
      sum += __shfl_xor_sync(0xffffffffu, sum, 2);
      sum = rcp(sum);
      const uint32_t u = pack_bf16(l0 * sum, l1 * sum);
      pf[z][i] = u & fmask; pn[z][i] = u & ~fmask;
    }
  float O[4][2][2][4];
  TL(t, 11);
  if (q == 0) bar_sync_after(BAR_P0, (pn[0][0] | pn[0][1] | pn[1][0]) | (pn[1][1] | pn[2][0] | pn[2][1]) | (pn[3][0] | pn[3][1]));
  zero = lds128f(c.sb + OFF_ZERO);
  TL(t, 12);
#pragma unroll
  for (int z = 0; z < 4; z++)
#pragma unroll
    for (int d = 0; d < 2; d++) {
      const uint32_t* v0 = P[2][z >> 1][2 * (z & 1)] + 2 * d;
      mma16816_z(O[z][0][d], HV[z][2 * d], HV[z][2 * d + 1], v0[0], v0[1], pf[z][0], pn[z][0], zero);
      mma16816_z(O[z][1][d], v0[0], v0[1], V1[z][2 * d], V1[z][2 * d + 1], pf[z][1], pn[z][1], zero);
    }
  {
    uint32_t dep = 0;
#pragma unroll
    for (int z = 0; z < 16; z++) dep |= __float_as_uint(O[z >> 2][(z >> 1) & 1][z & 1][0]);
    bar_arrive_after(BAR_P1, dep);
  }
  TL(t, 5);
#pragma unroll
  for (int nt = 0; nt < 8; nt++) {
    uint32_t u[4];
#pragma unroll
    for (int r = 0; r < 4; r++) { const float* o = O[2 * (nt >> 2) + (r >> 1)][r & 1][(nt >> 1) & 1] + 2 * (nt & 1); u[r] = pack_bf16(o[0], o[1]); }
    stmatrix4_t(stg + lane * 128 + ((nt ^ (lane & 7)) << 4), u[0], u[1], u[2], u[3]);
  }
  fence_async_smem();
  bar_arrive(BAR_READY, 160);
  TL(t, 13);
}

template<int CH>
__device__ __forceinline__ void epi_up(const Ctx& c, float (&acc)[2][96], int type) {
  const int lane = c.lane, w = c.w, g = lane >> 2, cc = lane & 3;
  float rs[4], nm[4];
#pragma unroll
  for (int r = 0; r < 4; r++) { const float2 v = lds64f(c.sb + OFF_RST + (w * 32 + 8 * r + g) * 8); rs[r] = v.x; nm[r] = v.x * v.y; }
  const int loc0 = type == 3 ? 0 : (type == 4 ? 192 : 320);
  const uint32_t cb = c.sb + OFF_UP + loc0 * 8 + cc * 16;
  const uint32_t zero = lds32(c.sb + OFF_ZERO);
  uint32_t d[2] = {0u, 0u};
  const uint32_t stg = c.sb + OFF_STG + w * 4096;
#pragma unroll
  for (int ch = CH; ch < (CH ? 3 : 2); ch++) {
    uint32_t P[8][4];
#pragma unroll
    for (int n8 = 0; n8 < 8; n8++) {
      const int nt = ch * 8 + n8;
      const float4 cv = lds128f(cb + nt * 64);
#pragma unroll
      for (int r = 0; r < 4; r++) {
        const float m = after(nm[r], d[r & 1], zero);
        d[r & 1] = P[n8][r] = relu_sq_bf16(fmaf(acc[r & 1][4 * nt + 2 * (r >> 1)], rs[r], fmaf(cv.x, m, cv.z)),
                                           fmaf(acc[r & 1][4 * nt + 2 * (r >> 1) + 1], rs[r], fmaf(cv.y, m, cv.w)));
      }
    }
    bar_sync(BAR_FREE, 160);
#pragma unroll
    for (int n8 = 0; n8 < 8; n8++)
      stmatrix4(stg + lane * 128 + ((n8 ^ (lane & 7)) << 4), P[n8][0], P[n8][1], P[n8][2], P[n8][3]);
    fence_async_smem();
    bar_arrive(BAR_READY, 160);
  }
}

__device__ __forceinline__ void init_res(const Ctx& c, float (&acc)[2][96], int t, bool bias) {
  if (t <= 2) mbar_wait(c.sb + OFF_XBAR, 0);
  const uint32_t xb = c.sb + OFF_X + c.w * 4096 + c.lane * 128;
#pragma unroll
  for (int nt = 0; nt < 16; nt++) {
    uint32_t u[4];
    ldmatrix4(xb + (nt >> 3) * A_BYTES + (((nt & 7) ^ (c.lane & 7)) << 4), u);
    float2 b = make_float2(0.f, 0.f);
    if (bias) b = lds64f(c.sb + OFF_B2 + nt * 32 + (c.lane & 3) * 8);
#pragma unroll
    for (int r = 0; r < 4; r++) {
      acc[r & 1][4 * nt + 2 * (r >> 1)] = bf_lo(u[r]) + b.x;
      acc[r & 1][4 * nt + 2 * (r >> 1) + 1] = bf_hi(u[r]) + b.y;
    }
  }
}

__device__ __forceinline__ void epi_res(const Ctx& c, float (&acc)[2][96]) {
  const uint32_t xw = c.sb + OFF_X + c.w * 4096 + c.lane * 128;
#pragma unroll
  for (int nt = 0; nt < 16; nt++)
    stmatrix4(xw + (nt >> 3) * A_BYTES + (((nt & 7) ^ (c.lane & 7)) << 4),
              pack_bf16(acc[0][4 * nt], acc[0][4 * nt + 1]), pack_bf16(acc[1][4 * nt], acc[1][4 * nt + 1]),
              pack_bf16(acc[0][4 * nt + 2], acc[0][4 * nt + 3]), pack_bf16(acc[1][4 * nt + 2], acc[1][4 * nt + 3]));
  fence_async_smem();
  bar_arrive(BAR_RES, 192);
}

__device__ __forceinline__ void row_stats(const Ctx& c, float (&acc)[2][96], int ln) {
  const int g = c.lane >> 2, cc = c.lane & 3;
  float sm[4], sq[4];
#pragma unroll
  for (int r = 0; r < 4; r++) {
    float a = 0.f, b = 0.f;
#pragma unroll
    for (int n = 0; n < 32; n++) { const float x = acc[r & 1][4 * (n >> 1) + 2 * (r >> 1) + (n & 1)]; a += x; b = fmaf(x, x, b); }
    a += __shfl_xor_sync(0xffffffffu, a, 1); b += __shfl_xor_sync(0xffffffffu, b, 1);
    a += __shfl_xor_sync(0xffffffffu, a, 2); b += __shfl_xor_sync(0xffffffffu, b, 2);
    sm[r] = a; sq[r] = b;
  }
  const float a = cc == 0 ? sm[0] : cc == 1 ? sm[1] : cc == 2 ? sm[2] : sm[3];
  const float b = cc == 0 ? sq[0] : cc == 1 ? sq[1] : cc == 2 ? sq[2] : sq[3];
  st_tag128(g_stats + (ln * 128 + c.b) * 128 + c.w * 32 + 8 * cc + g, __float_as_uint(a), __float_as_uint(b), 0u, smem_tag(c));
}

__device__ __forceinline__ void load_table(const Ctx& c, const Params& p, int part, unsigned tag) {
  const int i0 = (part < 4 ? part * 192 : 704) + c.lane, n = part < 3 ? 6 : 4;
  const uint2* src = g_cs + c.j * NCS + i0;
  const uint32_t dst = c.sb + OFF_CSQ + (i0 & 1) * 4 + (part < 2 ? (i0 >> 4) * 64 + (i0 & 6) * 8 + (i0 & 8) : 1536 + ((i0 - 384) >> 1) * 16);
  const __nv_bfloat16* bias = p.b1 + (part == 2 ? c.j * 192 : (part == 3 ? 1536 : 2560) + c.j * 128) + c.lane;
  float v[6];
  if (part >= 2) {
#pragma unroll
    for (int k = 0; k < 6; k++) if (k < n) sts32f(dst + k * 256 + 8, __bfloat162float(bias[k * 32]));
  }
  for (unsigned it = 0;; it++) {
    bool ok = true;
#pragma unroll
    for (int k = 0; k < 6; k++) { const uint2 a = ld_tag64(src + (k < n ? k * 32 : 0)); ok = ok && a.y == tag; v[k] = __uint_as_float(a.x); }
    if (__all_sync(0xffffffffu, ok) || it > SPIN_LIMIT) break;
    __nanosleep(400);
  }
#pragma unroll
  for (int k = 0; k < 6; k++) if (k < n) sts32f(dst + k * (part < 2 ? 128 : 256), v[k]);
  __syncwarp();
}

__device__ __forceinline__ void colsum_cta(const Ctx& c, const Params& p) {
  if (c.wg < 2) mbar_init_e(c.sb + OFF_FULL + 32 * c.wg + 8 * c.w, 1);
  sts32f(c.sb + OFF_STG + threadIdx.x * 4, __uint_as_float(0x3f803f80u));
  fence_async_smem();
  __syncthreads();
  if (c.wg == 2) return;
  const unsigned tag = global_tag();
  const int j = (blockIdx.x - 128) * 2 + c.wg;
  const uint32_t ring = c.sb + c.wg * 98304, full = c.sb + OFF_FULL + 32 * c.wg;
  const uint64_t ones = (uint64_t)(((c.sb + OFF_STG) & 0x3ffffu) >> 4) | (8u << 16) | ((uint64_t)16u << 32);
  float d[3][4];
#pragma unroll 1
  for (int n = -4; n < 80; n++) {
    if (n >= 0) {
      mbar_wait(full + 8 * (n & 3), (n >> 2) & 1);
      const uint64_t da = (uint64_t)(((ring + (n & 3) * 24576) & 0x3ffffu) >> 4) | (64u << 16) | ((uint64_t)(64u | (1u << 30)) << 32);
      wgmma_fence();
#pragma unroll
      for (int k = 0; k < 4; k++)
#pragma unroll
        for (int z = 0; z < 3; z++)
          asm volatile("{\n.reg .pred p;\nsetp.ne.b32 p, %6, 0;\nwgmma.mma_async.sync.aligned.m64n8k16.f32.bf16.bf16 {%0,%1,%2,%3}, %4, %5, p, 1, 1, 1, 0;\n}"
            : "+f"(d[z][0]), "+f"(d[z][1]), "+f"(d[z][2]), "+f"(d[z][3]) : "l"(da + z * 512 + k * 128), "l"(ones), "r"((n & 15) | k));
      wgmma_commit();
      wgmma_wait<0>();
      bar_sync(BAR_WG + c.wg, 128);
      if ((n & 15) == 15 && (c.lane & 3) < 2) {
        const int u = n >> 4;
        uint2* out = g_cs + j * NCS + (u < 4 ? u * 192 : 704) + c.w * 16 + (c.lane >> 2) + (c.lane & 1) * 8;
#pragma unroll
        for (int z = 0; z < 3; z++) if (z < 2 || u < 3) st_tag64(out + z * 64, (c.lane & 1) ? d[z][2] : d[z][0], tag);
      }
      __syncwarp();
    }
    if (c.w == 0 && n < 76) {
      const int u = (n + 4) >> 4;
      const WTile w = wtile(p, u + (u >= 2), j);
      mbar_expect_e(full + 8 * (n & 3), u < 3 ? 24576 : 16384);
      tma_ld3_e(ring + (n & 3) * 24576, w.mp, full + 8 * (n & 3), w.c0, ((n + 4) & 15) * 64, w.c2);
    }
  }
  bar_sync(BAR_START, 256);
  if (threadIdx.x == 0) g_epoch[blockIdx.x] = tag;
}

__global__ void __cluster_dims__(2, 1, 1) __launch_bounds__(384, 1) fused_kernel(const __grid_constant__ Params p) {
  extern __shared__ uint8_t smem_raw[];
  Ctx c;
  c.sb = (smem_u32(smem_raw) + 1023) & ~1023u;
  const int tid = threadIdx.x;
  c.wg = __shfl_sync(0xffffffffu, tid >> 7, 0); c.w = __shfl_sync(0xffffffffu, (tid >> 5) & 3, 0); c.lane = tid & 31;
  c.rank = blockIdx.x & 1;
  if (blockIdx.x >= 128) { colsum_cta(c, p); return; }
  uint32_t slot; asm volatile("mov.u32 %0, %%smid;" : "=r"(slot));
  slot = __shfl_sync(0xffffffffu, slot < 120 ? slot >> 1 : 60 + ((slot >> 1) & 3), 0);
#pragma unroll 1
  for (int pass = 0;; pass++) {
    const int gpc = slot < 32 ? slot & 7 : slot < 60 ? 1 + (slot - 32) % 7 : 0;
    c.m = (gpc & 1) * 8 + (slot < 32 ? slot >> 3 : slot < 60 ? 4 + (slot - 32) / 7 : slot - 56);
    c.j = (gpc & 6) + c.rank; c.b = c.m * 8 + c.j;
    const int k = c.wg * 4 + c.w;
    if (k == 9) {
#pragma unroll 1
      for (int s = 0; s < 4; s++) {
        const uint32_t full = c.sb + OFF_FULL + 8 * s, dst = c.sb + ((s + 3) & 3) * 40960;
        if (pass) { mbar_wait(full, 0); asm volatile(ELECT "@p mbarrier.inval.shared::cta.b64 [%0];\n}" :: "r"(full) : "memory"); }
        mbar_init_e(full, 2);
        fence_async_smem();
        mbar_expect_e(full, 40960);
        tma_ld4_e(dst, &p.ld_x, full, s * 64, c.m * 4);
        tma_ld4_e(dst + 8192, &p.ld_x, full, s * 64, c.m * 4 + 2);
        tma_ld3_e(dst + A_BYTES, &p.w_qkv, full, c.j * 64, s * 64, 0);
        mbar_arrive_e(full);
      }
      PTL(14, 8);
    }
    if (pass) { __syncthreads(); break; }
    unsigned tag = 0, old = 0;
    const bool claim = tid == 256 && c.rank == 0;
    if (claim) { old = atomicAdd(g_slot + slot, 1u); tag = global_tag(); }
    __syncwarp();
    if (k < 8) { mbar_init_e(c.sb + OFF_EMPTY + 8 * k, 8); mbar_init_e(c.sb + (k < 4 ? OFF_XBAR : OFF_FULL) + 8 * k, k < 4 ? 1 : 2); }
    if (k == 10) { mbar_init_e(c.sb + OFF_HALO, 2); mbar_init_e(c.sb + OFF_SLOT, 1); mbar_expect_e(c.sb + OFF_SLOT, 8); sts128(c.sb + OFF_ZERO, 0u, 0u, 0u, 0u); }
    asm volatile("fence.mbarrier_init.release.cluster;" ::: "memory");
    asm volatile("barrier.cluster.arrive.relaxed.aligned;\nbarrier.cluster.wait.aligned;" ::: "memory");
    if (claim) {
      uint32_t s = slot;
      for (int it = 0; old + 1 != tag && it < 64; it++) { atomicSub(g_slot + s, 1u); s = (s + 1) & 63; old = atomicAdd(g_slot + s, 1u); }
#pragma unroll
      for (int r = 0; r < 2; r++)
        asm volatile("st.async.weak.shared::cluster.mbarrier::complete_tx::bytes.v2.b32 [%0], {%1, %2}, [%3];"
          :: "r"(mapa(c.sb + OFF_TAG, r)), "r"(tag), "r"(s), "r"(mapa(c.sb + OFF_SLOT, r)) : "memory");
    }
    __syncwarp();
    mbar_wait(c.sb + OFF_SLOT, 0);
    const uint32_t got = __shfl_sync(0xffffffffu, lds32(c.sb + OFF_TAG + 4), 0);
    if (got == slot) break;
    slot = got;
  }
  if (c.wg == 2) {
    reg_dealloc<40>();
    const unsigned tag = smem_tag(c);
    if (c.w < 2) {
      int g = 4;
#pragma unroll 1
      for (int t = 0; t < 14; t++) {
        const int layer = t >= 7, type = t - layer * 7;
        const bool wide = type < 2 || type == 3, own = type == 3 || t == 7;
        const int nkb = type == 6 ? 56 : 16, ns = wide ? 4 : 5, str = wide ? 40960 : 32768;
        const int nshort = type == 0 ? 3 : (type == 2 || type == 4) ? 4 : 0;
        int st = first_stage(type);
        if (c.w == 0) {
          const CUtensorMap* mp = type == 2 || type == 6 ? &p.ld_h : (t < 2 ? &p.ld_x : &p.ld_out);
          const int slab = c.m * 4 + c.rank * 2;
          const unsigned* fp = g_flags + (t * 16 + c.m) * 32 + c.lane;
          unsigned ready = own ? 15u << (c.j >> 1) * 4 : type == 2 ? 0x300u << (c.j & 6) : type == 6 ? 0u : ~0u;
          const int local = own ? 0 : type == 2 ? 8 : 64, nloc = own ? 2 : 1;
#pragma unroll 1
          for (int step = t ? 0 : 4; step < nkb; step++, g++) {
            const int kb = kb_order(c, t, type, step);
            const int piece = type != 6 ? kb : step < 24 ? (step * 43) >> 7 : (step >> 1) - 4;
            for (unsigned it = 0; !((ready >> piece) & 1) && it < SPIN_LIMIT; it++) {
              unsigned v; asm volatile("ld.relaxed.gpu.global.u32 %0, [%1];" : "=r"(v) : "l"(fp) : "memory");
              ready |= __ballot_sync(0xffffffffu, v == tag);
              asm volatile("fence.proxy.async.global;" ::: "memory");
            }
            const int e = g - (step < nshort ? ns - 1 : ns);
            if (e >= 0) mbar_wait(c.sb + OFF_EMPTY + 8 * (e & 7), (e >> 3) & 1);
            const uint32_t full = c.sb + OFF_FULL + 8 * (g & 7);
            if ((unsigned)(step - local) >= nloc) mbar_expect_e(full, A_BYTES);
            if ((unsigned)(step - local) >= 2 * nloc) tma_ld4_mc_e(c.sb + st * str + c.rank * 8192, mp, full, kb * 64, slab);
            else if (step == 9) {
              const uint32_t peer = mapa(c.sb, c.rank ^ 1);
              mbar_wait(c.sb + OFF_FULL, layer ^ 1);
              dsmem_copy_e(peer + 3 * 32768, c.sb + OFF_STG, peer + OFF_FULL + 8);
            }
            if (++st == ns) st = 0;
          }
        } else {
          const WTile w = wtile(p, type, c.j);
#pragma unroll 1
          for (int step = t ? 0 : 4; step < nkb; step++, g++) {
            const int e = g - (step < nshort ? ns - 1 : ns);
            if (e >= 0) mbar_wait(c.sb + OFF_EMPTY + 8 * (e & 7), (e >> 3) & 1);
            const uint32_t full = c.sb + OFF_FULL + 8 * (g & 7);
            const int kb = kb_order(c, t, type, step);
            mbar_expect_e(full, str - A_BYTES);
            tma_ld3_e(c.sb + st * str + A_BYTES, w.mp, full, w.c0, kb * 64, w.c2);
            if ((g & 15) == c.m && g + 16 < 2 * KB_LAYER) {
              const bool nx = step + 16 >= nkb;
              const int s2 = step + 16 - (nx ? nkb : 0);
              const WTile v = wtile(p, nx ? (type == 6 ? 0 : type + 1) : 6, c.j);
              tma_pf3_e(v.mp, v.c0, (nx && (type == 2 || type == 6) ? own_kb(c, s2) : s2) * 64, v.c2);
            }
            if (++st == ns) st = 0;
          }
        }
      }
    } else if (c.w == 2) {
      bar_arrive(BAR_FREE, 160);
#pragma unroll 1
      for (int t = 0; t < 14; t++) {
        const int layer = t >= 7, type = t - layer * 7;
        const int slab = c.m * 4;
        unsigned* flag = g_flags + c.m * 32 + c.j;
        if (type == 2 || type == 6) {
          flag += (t + 1) * 512 + c.j;
          bar_sync(BAR_RES, 192);
          tma_st4_e(&p.st_out, c.sb + OFF_X, c.j * 128, slab);
          if (t < 13) {
            bulk_wait_read_e();
            bar_arrive(BAR_COPY, 64);
            PTL(t, 8);
            publish_e(flag++, tag);
            PTL(t, 9);
          }
          tma_st4_e(&p.st_out, c.sb + OFF_X + A_BYTES, c.j * 128 + 64, slab);
          bulk_wait_read_e();
          PTL(t, 11);
        } else {
          flag += (layer * 7 + (type < 2 ? 2 : 6)) * 512 + (type < 2 ? type : type - 3) * 8;
          const int col = type < 2 ? (c.j + 8 * type) * 64 : type == 3 ? c.j * 192 : (type == 4 ? 1536 : 2560) + c.j * 128;
#pragma unroll 1
          for (int ch = type == 3 ? -1 : 0; ch < (type < 2 ? 1 : 2); ch++) {
            if (type < 2) fetch_halo(c, tag, layer * 2 + type);
            bar_sync(BAR_READY, 160);
            tma_st4_e(&p.st_h, c.sb + OFF_STG, col + (ch < 0 ? 128 : ch * 64), slab);
            if (type == 1) { mbar_wait(c.sb + OFF_FULL, layer); mbar_arrive_e(c.sb + OFF_FULL); }
            bulk_wait_read_e();
            if (t < 12 || ch == 0) bar_arrive(BAR_FREE, 160);
          }
          PTL(t, 14);
        }
        if (t < 13) publish_e(flag, tag);
        PTL(t, 6);
      }
      if (c.lane == 0) g_epoch[blockIdx.x] = tag;
    } else {
      mbar_wait(c.sb + OFF_FULL, 0);
      PTL(14, 14);
      mbar_expect_e(c.sb + OFF_XBAR, 32768);
#pragma unroll
      for (int i = 0; i < 4; i++) tma_ld4_e(c.sb + OFF_X + i * 8192, &p.ld_x, c.sb + OFF_XBAR, c.j * 128 + (i >> 1) * 64, c.m * 4 + (i & 1) * 2);
#pragma unroll
      for (int i = 0; i < 4; i++) sts32f(c.sb + OFF_B2 + i * 128 + c.lane * 4, __bfloat162float(p.b2[c.j * 128 + i * 32 + c.lane]));
      const uint32_t peer = mapa(c.sb, c.rank ^ 1);
      int part = 0;
#pragma unroll 1
      for (int i = 0; i < 3; i++) {
        const int g1 = i == 0 ? 48 : i == 1 ? KB_LAYER : KB_LAYER + 48;
#pragma unroll 1
        for (; part < (i == 0 ? 2 : i == 1 ? 5 : 7); part++) {
          if (part < 5) {
            load_table(c, p, part, tag);
            if (part != 2 && part != 3) mbar_arrive_e(c.sb + OFF_TBL + 8 * (part < 2 ? part : 2));
            PTL(part, 7);
          }
          if (i != 1) fetch_halo(c, tag, i ? part - 3 : part);
        }
        bar_sync(BAR_RES, 192);
        mbar_arrive_e(c.sb + OFF_FULL);
        mbar_arrive_e(c.sb + OFF_FULL + 8);
        mbar_wait(c.sb + OFF_EMPTY + 56, ((g1 - 1) >> 3) & 1);
        bar_sync(BAR_COPY, 64);
        __nanosleep(40);
#pragma unroll
        for (int ch = 0; ch < 2; ch++)
          dsmem_copy_e(peer + ((i == 1 ? 1 : 2) + ch) * 40960, c.sb + OFF_X + ch * A_BYTES, peer + OFF_FULL + 16 + 8 * ch);
        PTL(i == 0 ? 2 : i == 1 ? 6 : 9, 10);
      }
      bar_arrive(BAR_RES, 192);
    }
  } else {
    reg_alloc<232>();
#pragma unroll 1
    for (int t = -c.wg; t < 14; t += 2) {
      const int layer = t >= 7, type = t - layer * 7;
      const int g0 = layer * KB_LAYER + type * 16;
      float acc[2][96];
      if (t < 0 || type == 2 || type == 6) {
        init_res(c, acc, t, type == 6);
        if (t >= 0) {
          const int nkb = type == 6 ? 56 : 16;
          mainloop<128, 1>(c, acc, t, type, g0, nkb);
          finish(c, t);
          if (t == 13) asm volatile("barrier.cluster.arrive.relaxed.aligned;" ::: "memory");
          epi_res(c, acc);
          if (t == 13) break;
        }
        TL(t, 4);
        const int ln = t < 0 ? 0 : layer * 2 + (type == 6 ? 2 : 1);
        row_stats(c, acc, ln);
        load_row_stats(c, ln);
        TL(t, 5);
      } else {
        if (type < 4) {
          mainloop<192, 0>(c, acc, t, type, g0, type < 2 ? 13 : 16);
          if (type < 2) { epi_qkv(c, acc, t, type); goto done; }
          finish(c, t);
          bar_sync(BAR_EPI + c.wg, 256);
          mbar_wait(c.sb + OFF_TBL + 16, 0);
          epi_up<2>(c, acc, type);
        } else {
          mainloop<128, 0>(c, acc, t, type, g0, 16);
          finish(c, t);
          bar_sync(BAR_EPI + c.wg, 256);
        }
        epi_up<0>(c, acc, type);
        TL(t, 4);
      done:;
      }
      if (type != 1 && type != 5) bar_arrive(BAR_EPI + (c.wg ^ 1), 256);
    }
    if (c.wg == 1) {
      asm volatile("barrier.cluster.wait.aligned;" ::: "memory");
    }
  }
}

typedef CUresult (*EncodeFn)(CUtensorMap*, CUtensorMapDataType, cuuint32_t, void*, const cuuint64_t*, const cuuint64_t*,
                             const cuuint32_t*, const cuuint32_t*, CUtensorMapInterleave, CUtensorMapSwizzle,
                             CUtensorMapL2promotion, CUtensorMapFloatOOBfill);

void make_map(EncodeFn fn, CUtensorMap* m, const void* ptr, int rank, const cuuint64_t* dims, const cuuint64_t* strides, const cuuint32_t* box) {
  const cuuint32_t es[4] = {1, 1, 1, 1};
  fn(m, CU_TENSOR_MAP_DATA_TYPE_BFLOAT16, rank, const_cast<void*>(ptr), dims, strides, box, es, CU_TENSOR_MAP_INTERLEAVE_NONE,
     CU_TENSOR_MAP_SWIZZLE_128B, CU_TENSOR_MAP_L2_PROMOTION_L2_128B, CU_TENSOR_MAP_FLOAT_OOB_FILL_NONE);
}
void map_rows(EncodeFn fn, CUtensorMap* m, const void* ptr, int cols, int rows, int box_slabs, bool tokens) {
  const cuuint64_t rb = (cuuint64_t)cols * 2;
  const cuuint64_t dims[4] = {(cuuint64_t)cols, 16, 2, (cuuint64_t)(rows / 32)};
  const cuuint64_t st[3] = {tokens ? 2 * rb : rb, tokens ? rb : 16 * rb, 32 * rb};
  const cuuint32_t box[4] = {64, 16, 2, (cuuint32_t)box_slabs};
  make_map(fn, m, ptr, 4, dims, st, box);
}
void map_w(EncodeFn fn, CUtensorMap* m, const void* ptr, int K, int N, int inner, int nch) {
  const cuuint64_t dims[3] = {(cuuint64_t)inner, (cuuint64_t)K, (cuuint64_t)(N / inner)}, st[2] = {(cuuint64_t)N * 2, (cuuint64_t)inner * 2};
  const cuuint32_t box[3] = {64, 64, (cuuint32_t)nch};
  make_map(fn, m, ptr, 3, dims, st, box);
}

}

extern "C" void kernel_launch(void* const* d_in, const int* in_sizes, int n_in, void* d_out, int out_size) {
  (void)in_sizes; (void)n_in; (void)out_size;
  Params p;
  p.b1 = (const __nv_bfloat16*)d_in[5]; p.b2 = (const __nv_bfloat16*)d_in[7];
  void* fnp = nullptr; cudaDriverEntryPointQueryResult qr;
  cudaGetDriverEntryPoint("cuTensorMapEncodeTiled", &fnp, cudaEnableDefault, &qr);
  EncodeFn fn = (EncodeFn)fnp;
  void* h;
  cudaGetSymbolAddress(&h, g_h);
  map_rows(fn, &p.ld_x, d_in[0], D_, S_, 2, true);
  map_rows(fn, &p.ld_out, d_out, D_, S_, 2, true);
  map_rows(fn, &p.ld_h, h, F_, S_, 2, false);
  map_rows(fn, &p.st_h, h, F_, S_, 4, false);
  map_rows(fn, &p.st_out, d_out, D_, S_, 4, true);
  map_w(fn, &p.w_qkv, d_in[1], D_, 3 * D_, D_, 3);
  map_w(fn, &p.w_o, d_in[2], D_, D_, 64, 2);
  map_w(fn, &p.w_1a, d_in[4], D_, F_, 64, 3);
  map_w(fn, &p.w_1b, d_in[4], D_, F_, 64, 2);
  map_w(fn, &p.w_2, d_in[6], F_, D_, 64, 2);
  cudaFuncSetAttribute(fused_kernel, cudaFuncAttributeMaxDynamicSharedMemorySize, SMEM_BYTES);
  fused_kernel<<<132, 384, SMEM_BYTES>>>(p);
}
```

```cpp
#include <cuda_runtime.h>
#include <cuda_bf16.h>
#include <cuda.h>
#include <stdint.h>

#define EXP 0
namespace {

constexpr int S_ = 2048, D_ = 1024, F_ = 3584;
constexpr int A_BYTES = 16384;
constexpr int OFF_X   = 163840;
constexpr int OFF_STG = OFF_X + 32768;
constexpr int OFF_CSQ = OFF_STG + 20480;
constexpr int OFF_UP  = OFF_CSQ + 1536;
constexpr int OFF_B2  = OFF_UP + 3584;
constexpr int OFF_RST = OFF_B2 + 512 + 256;
constexpr int OFF_FULL = OFF_RST + 1024;
constexpr int OFF_EMPTY = OFF_FULL + 64;
constexpr int OFF_XBAR = OFF_EMPTY + 64;
constexpr int OFF_TBL = OFF_XBAR + 8;
constexpr int OFF_HALO = OFF_XBAR + 40;
constexpr int OFF_SLOT = OFF_XBAR + 48;
constexpr int OFF_ZERO = OFF_XBAR + 64;
constexpr int OFF_TAG = OFF_ZERO + 16;
constexpr int SMEM_BYTES = OFF_TAG + 16 + 1024;
constexpr int KB_LAYER = 6 * 16 + 56;
constexpr int NCS = 384 + 448;
constexpr unsigned SPIN_LIMIT = 1u << 20;
constexpr int PAUSE1 = 5, PAUSE2 = PAUSE1 + 2, EARLY = 0, HGO = 11;
constexpr uint32_t DESC_A = 1u << 16, DESC_B = (512u << 16) + A_BYTES / 16;
enum { BAR_START = 1, BAR_EPI = 3, BAR_WG = 5, BAR_P0 = 7, BAR_P1 = 8, BAR_RES = 9, BAR_READY = 10, BAR_FREE = 11, BAR_COPY = 12, BAR_HGO = 13 };

struct Params {
  CUtensorMap ld_x, ld_out, ld_h, st_h, st_out, w_qkv, w_o, w_1a, w_1b, w_2, s_qkv, s_1;
  const __nv_bfloat16 *b1, *b2;
};

__device__ __align__(1024) __nv_bfloat16 g_h[S_ * F_];
__device__ __align__(128) uint4 g_stats[4 * S_ * 8];
__device__ __align__(128) uint2 g_cs[8 * NCS];
__device__ __align__(128) uint4 g_halo[4 * 128 * 11 * 32];
__device__ __align__(128) unsigned g_flags[14 * 16 * 32];
__device__ unsigned g_epoch[132 + 64];
#define TL(t, e)
#define PTL(t, e)
#if !defined(TIMELINE) || !(EXP & 8)
#undef TK
#define TK(t, k)
#endif

template<int N, int KEEP> __device__ __forceinline__ void wgmma_ss(float (&d)[96], uint32_t da, uint32_t db);
template<> __device__ __forceinline__ void wgmma_ss<128, 0>(float (&d)[96], uint32_t da, uint32_t db) {
  asm volatile("{\n.reg .pred p;\n.reg .b64 a, b;\nsetp.ne.b32 p, 0, 0;\nmov.b64 a, {%64, 0x40000080};\nmov.b64 b, {%65, 0x40000040};\nwgmma.mma_async.sync.aligned.m64n128k16.f32.bf16.bf16 {%0, %1, %2, %3, %4, %5, %6, %7, %8, %9, %10, %11, %12, %13, %14, %15, %16, %17, %18, %19, %20, %21, %22, %23, %24, %25, %26, %27, %28, %29, %30, %31, %32, %33, %34, %35, %36, %37, %38, %39, %40, %41, %42, %43, %44, %45, %46, %47, %48, %49, %50, %51, %52, %53, %54, %55, %56, %57, %58, %59, %60, %61, %62, %63}, a, b, p, 1, 1, 0, 1;\n}"
    : "=f"(d[0]), "=f"(d[1]), "=f"(d[2]), "=f"(d[3]), "=f"(d[4]), "=f"(d[5]), "=f"(d[6]), "=f"(d[7]), "=f"(d[8]), "=f"(d[9]), "=f"(d[10]), "=f"(d[11]), "=f"(d[12]), "=f"(d[13]), "=f"(d[14]), "=f"(d[15]), "=f"(d[16]), "=f"(d[17]), "=f"(d[18]), "=f"(d[19]), "=f"(d[20]), "=f"(d[21]), "=f"(d[22]), "=f"(d[23]), "=f"(d[24]), "=f"(d[25]), "=f"(d[26]), "=f"(d[27]), "=f"(d[28]), "=f"(d[29]), "=f"(d[30]), "=f"(d[31]), "=f"(d[32]), "=f"(d[33]), "=f"(d[34]), "=f"(d[35]), "=f"(d[36]), "=f"(d[37]), "=f"(d[38]), "=f"(d[39]), "=f"(d[40]), "=f"(d[41]), "=f"(d[42]), "=f"(d[43]), "=f"(d[44]), "=f"(d[45]), "=f"(d[46]), "=f"(d[47]), "=f"(d[48]), "=f"(d[49]), "=f"(d[50]), "=f"(d[51]), "=f"(d[52]), "=f"(d[53]), "=f"(d[54]), "=f"(d[55]), "=f"(d[56]), "=f"(d[57]), "=f"(d[58]), "=f"(d[59]), "=f"(d[60]), "=f"(d[61]), "=f"(d[62]), "=f"(d[63])
    : "r"(da), "r"(db));
}
template<> __device__ __forceinline__ void wgmma_ss<128, 1>(float (&d)[96], uint32_t da, uint32_t db) {
  asm volatile("{\n.reg .pred p;\n.reg .b64 a, b;\nsetp.ne.b32 p, 1, 0;\nmov.b64 a, {%64, 0x40000080};\nmov.b64 b, {%65, 0x40000040};\nwgmma.mma_async.sync.aligned.m64n128k16.f32.bf16.bf16 {%0, %1, %2, %3, %4, %5, %6, %7, %8, %9, %10, %11, %12, %13, %14, %15, %16, %17, %18, %19, %20, %21, %22, %23, %24, %25, %26, %27, %28, %29, %30, %31, %32, %33, %34, %35, %36, %37, %38, %39, %40, %41, %42, %43, %44, %45, %46, %47, %48, %49, %50, %51, %52, %53, %54, %55, %56, %57, %58, %59, %60, %61, %62, %63}, a, b, p, 1, 1, 0, 1;\n}"
    : "+f"(d[0]), "+f"(d[1]), "+f"(d[2]), "+f"(d[3]), "+f"(d[4]), "+f"(d[5]), "+f"(d[6]), "+f"(d[7]), "+f"(d[8]), "+f"(d[9]), "+f"(d[10]), "+f"(d[11]), "+f"(d[12]), "+f"(d[13]), "+f"(d[14]), "+f"(d[15]), "+f"(d[16]), "+f"(d[17]), "+f"(d[18]), "+f"(d[19]), "+f"(d[20]), "+f"(d[21]), "+f"(d[22]), "+f"(d[23]), "+f"(d[24]), "+f"(d[25]), "+f"(d[26]), "+f"(d[27]), "+f"(d[28]), "+f"(d[29]), "+f"(d[30]), "+f"(d[31]), "+f"(d[32]), "+f"(d[33]), "+f"(d[34]), "+f"(d[35]), "+f"(d[36]), "+f"(d[37]), "+f"(d[38]), "+f"(d[39]), "+f"(d[40]), "+f"(d[41]), "+f"(d[42]), "+f"(d[43]), "+f"(d[44]), "+f"(d[45]), "+f"(d[46]), "+f"(d[47]), "+f"(d[48]), "+f"(d[49]), "+f"(d[50]), "+f"(d[51]), "+f"(d[52]), "+f"(d[53]), "+f"(d[54]), "+f"(d[55]), "+f"(d[56]), "+f"(d[57]), "+f"(d[58]), "+f"(d[59]), "+f"(d[60]), "+f"(d[61]), "+f"(d[62]), "+f"(d[63])
    : "r"(da), "r"(db));
}
template<> __device__ __forceinline__ void wgmma_ss<192, 0>(float (&d)[96], uint32_t da, uint32_t db) {
  asm volatile("{\n.reg .pred p;\n.reg .b64 a, b;\nsetp.ne.b32 p, 0, 0;\nmov.b64 a, {%96, 0x40000080};\nmov.b64 b, {%97, 0x40000040};\nwgmma.mma_async.sync.aligned.m64n192k16.f32.bf16.bf16 {%0, %1, %2, %3, %4, %5, %6, %7, %8, %9, %10, %11, %12, %13, %14, %15, %16, %17, %18, %19, %20, %21, %22, %23, %24, %25, %26, %27, %28, %29, %30, %31, %32, %33, %34, %35, %36, %37, %38, %39, %40, %41, %42, %43, %44, %45, %46, %47, %48, %49, %50, %51, %52, %53, %54, %55, %56, %57, %58, %59, %60, %61, %62, %63, %64, %65, %66, %67, %68, %69, %70, %71, %72, %73, %74, %75, %76, %77, %78, %79, %80, %81, %82, %83, %84, %85, %86, %87, %88, %89, %90, %91, %92, %93, %94, %95}, a, b, p, 1, 1, 0, 1;\n}"
    : "=f"(d[0]), "=f"(d[1]), "=f"(d[2]), "=f"(d[3]), "=f"(d[4]), "=f"(d[5]), "=f"(d[6]), "=f"(d[7]), "=f"(d[8]), "=f"(d[9]), "=f"(d[10]), "=f"(d[11]), "=f"(d[12]), "=f"(d[13]), "=f"(d[14]), "=f"(d[15]), "=f"(d[16]), "=f"(d[17]), "=f"(d[18]), "=f"(d[19]), "=f"(d[20]), "=f"(d[21]), "=f"(d[22]), "=f"(d[23]), "=f"(d[24]), "=f"(d[25]), "=f"(d[26]), "=f"(d[27]), "=f"(d[28]), "=f"(d[29]), "=f"(d[30]), "=f"(d[31]), "=f"(d[32]), "=f"(d[33]), "=f"(d[34]), "=f"(d[35]), "=f"(d[36]), "=f"(d[37]), "=f"(d[38]), "=f"(d[39]), "=f"(d[40]), "=f"(d[41]), "=f"(d[42]), "=f"(d[43]), "=f"(d[44]), "=f"(d[45]), "=f"(d[46]), "=f"(d[47]), "=f"(d[48]), "=f"(d[49]), "=f"(d[50]), "=f"(d[51]), "=f"(d[52]), "=f"(d[53]), "=f"(d[54]), "=f"(d[55]), "=f"(d[56]), "=f"(d[57]), "=f"(d[58]), "=f"(d[59]), "=f"(d[60]), "=f"(d[61]), "=f"(d[62]), "=f"(d[63]), "=f"(d[64]), "=f"(d[65]), "=f"(d[66]), "=f"(d[67]), "=f"(d[68]), "=f"(d[69]), "=f"(d[70]), "=f"(d[71]), "=f"(d[72]), "=f"(d[73]), "=f"(d[74]), "=f"(d[75]), "=f"(d[76]), "=f"(d[77]), "=f"(d[78]), "=f"(d[79]), "=f"(d[80]), "=f"(d[81]), "=f"(d[82]), "=f"(d[83]), "=f"(d[84]), "=f"(d[85]), "=f"(d[86]), "=f"(d[87]), "=f"(d[88]), "=f"(d[89]), "=f"(d[90]), "=f"(d[91]), "=f"(d[92]), "=f"(d[93]), "=f"(d[94]), "=f"(d[95])
    : "r"(da), "r"(db));
}
template<> __device__ __forceinline__ void wgmma_ss<192, 1>(float (&d)[96], uint32_t da, uint32_t db) {
  asm volatile("{\n.reg .pred p;\n.reg .b64 a, b;\nsetp.ne.b32 p, 1, 0;\nmov.b64 a, {%96, 0x40000080};\nmov.b64 b, {%97, 0x40000040};\nwgmma.mma_async.sync.aligned.m64n192k16.f32.bf16.bf16 {%0, %1, %2, %3, %4, %5, %6, %7, %8, %9, %10, %11, %12, %13, %14, %15, %16, %17, %18, %19, %20, %21, %22, %23, %24, %25, %26, %27, %28, %29, %30, %31, %32, %33, %34, %35, %36, %37, %38, %39, %40, %41, %42, %43, %44, %45, %46, %47, %48, %49, %50, %51, %52, %53, %54, %55, %56, %57, %58, %59, %60, %61, %62, %63, %64, %65, %66, %67, %68, %69, %70, %71, %72, %73, %74, %75, %76, %77, %78, %79, %80, %81, %82, %83, %84, %85, %86, %87, %88, %89, %90, %91, %92, %93, %94, %95}, a, b, p, 1, 1, 0, 1;\n}"
    : "+f"(d[0]), "+f"(d[1]), "+f"(d[2]), "+f"(d[3]), "+f"(d[4]), "+f"(d[5]), "+f"(d[6]), "+f"(d[7]), "+f"(d[8]), "+f"(d[9]), "+f"(d[10]), "+f"(d[11]), "+f"(d[12]), "+f"(d[13]), "+f"(d[14]), "+f"(d[15]), "+f"(d[16]), "+f"(d[17]), "+f"(d[18]), "+f"(d[19]), "+f"(d[20]), "+f"(d[21]), "+f"(d[22]), "+f"(d[23]), "+f"(d[24]), "+f"(d[25]), "+f"(d[26]), "+f"(d[27]), "+f"(d[28]), "+f"(d[29]), "+f"(d[30]), "+f"(d[31]), "+f"(d[32]), "+f"(d[33]), "+f"(d[34]), "+f"(d[35]), "+f"(d[36]), "+f"(d[37]), "+f"(d[38]), "+f"(d[39]), "+f"(d[40]), "+f"(d[41]), "+f"(d[42]), "+f"(d[43]), "+f"(d[44]), "+f"(d[45]), "+f"(d[46]), "+f"(d[47]), "+f"(d[48]), "+f"(d[49]), "+f"(d[50]), "+f"(d[51]), "+f"(d[52]), "+f"(d[53]), "+f"(d[54]), "+f"(d[55]), "+f"(d[56]), "+f"(d[57]), "+f"(d[58]), "+f"(d[59]), "+f"(d[60]), "+f"(d[61]), "+f"(d[62]), "+f"(d[63]), "+f"(d[64]), "+f"(d[65]), "+f"(d[66]), "+f"(d[67]), "+f"(d[68]), "+f"(d[69]), "+f"(d[70]), "+f"(d[71]), "+f"(d[72]), "+f"(d[73]), "+f"(d[74]), "+f"(d[75]), "+f"(d[76]), "+f"(d[77]), "+f"(d[78]), "+f"(d[79]), "+f"(d[80]), "+f"(d[81]), "+f"(d[82]), "+f"(d[83]), "+f"(d[84]), "+f"(d[85]), "+f"(d[86]), "+f"(d[87]), "+f"(d[88]), "+f"(d[89]), "+f"(d[90]), "+f"(d[91]), "+f"(d[92]), "+f"(d[93]), "+f"(d[94]), "+f"(d[95])
    : "r"(da), "r"(db));
}

__device__ __forceinline__ uint32_t smem_u32(const void* p) { return (uint32_t)__cvta_generic_to_shared(p); }
__device__ __forceinline__ void mbar_arrive_cluster(uint32_t bar) { asm volatile("mbarrier.arrive.shared::cluster.b64 _, [%0];" :: "r"(bar) : "memory"); }
__device__ __forceinline__ void mbar_wait(uint32_t bar, uint32_t parity) {
  asm volatile(
    "{\n.reg .pred p;\n.reg .u32 n;\n"
    "mbarrier.try_wait.parity.shared::cta.b64 p, [%0], %1;\n"
    "@p bra.uni WAIT_DONE;\n"
    "mov.u32 n, 0;\n"
    "WAIT_LOOP:\n"
    "mbarrier.try_wait.parity.shared::cta.b64 p, [%0], %1;\n"
    "@p bra.uni WAIT_DONE;\n"
    "add.u32 n, n, 1;\n"
    "setp.lt.u32 p, n, 0x100000;\n"
    "@p bra.uni WAIT_LOOP;\n"
    "trap;\n"
    "WAIT_DONE:\n}" :: "r"(bar), "r"(parity) : "memory");
}
#define ELECT "{\n.reg .pred p;\nelect.sync _|p, 0xffffffff;\n"
__device__ __forceinline__ void mbar_init_e(uint32_t bar, uint32_t cnt) { asm volatile(ELECT "@p mbarrier.init.shared::cta.b64 [%0], %1;\n}" :: "r"(bar), "r"(cnt) : "memory"); }
__device__ __forceinline__ void mbar_arrive_e(uint32_t bar) { asm volatile(ELECT "@p mbarrier.arrive.shared::cta.b64 _, [%0];\n}" :: "r"(bar) : "memory"); }
__device__ __forceinline__ void mbar_expect_e(uint32_t bar, uint32_t bytes) { asm volatile(ELECT "@p mbarrier.arrive.expect_tx.shared::cta.b64 _, [%0], %1;\n}" :: "r"(bar), "r"(bytes) : "memory"); }
__device__ __forceinline__ void tma_ld4_e(uint32_t dst, const CUtensorMap* m, uint32_t bar, int c0, int c3) {
  asm volatile(ELECT "@p cp.async.bulk.tensor.4d.shared::cluster.global.mbarrier::complete_tx::bytes [%0], [%1, {%3, %5, %5, %4}], [%2];\n}"
    :: "r"(dst), "l"(m), "r"(bar), "r"(c0), "r"(c3), "r"(0) : "memory");
}
__device__ __forceinline__ void tma_ld4_mc_e(uint32_t dst, const CUtensorMap* m, uint32_t bar, int c0, int c3) {
  asm volatile(ELECT "@p cp.async.bulk.tensor.4d.shared::cluster.global.mbarrier::complete_tx::bytes.multicast::cluster [%0], [%1, {%3, %5, %5, %4}], [%2], %6;\n}"
    :: "r"(dst), "l"(m), "r"(bar), "r"(c0), "r"(c3), "r"(0), "h"((uint16_t)3) : "memory");
}
__device__ __forceinline__ void tma_ld3_e(uint32_t dst, const CUtensorMap* m, uint32_t bar, int c0, int c1, int c2) {
  asm volatile(ELECT "@p cp.async.bulk.tensor.3d.shared::cluster.global.mbarrier::complete_tx::bytes [%0], [%1, {%3, %4, %5}], [%2];\n}"
    :: "r"(dst), "l"(m), "r"(bar), "r"(c0), "r"(c1), "r"(c2) : "memory");
}
__device__ __forceinline__ void tma_pf3_e(const CUtensorMap* m, int c0, int c1, int c2) {
  asm volatile(ELECT "@p cp.async.bulk.prefetch.tensor.3d.L2.global [%0, {%1, %2, %3}];\n}" :: "l"(m), "r"(c0), "r"(c1), "r"(c2) : "memory");
}
__device__ __forceinline__ void tma_st4_e(const CUtensorMap* m, uint32_t src, int c0, int c3) {
  asm volatile(ELECT "@p cp.async.bulk.tensor.4d.global.shared::cta.bulk_group [%0, {%2, %4, %4, %3}], [%1];\n}"
    :: "l"(m), "r"(src), "r"(c0), "r"(c3), "r"(0) : "memory");
}
__device__ __forceinline__ void dsmem_copy_e(uint32_t dst, uint32_t src, uint32_t bar) {
  asm volatile(ELECT "@p cp.async.bulk.shared::cluster.shared::cta.mbarrier::complete_tx::bytes [%0], [%1], 16384, [%2];\n}"
    :: "r"(dst), "r"(src), "r"(bar) : "memory");
}
__device__ __forceinline__ void bulk_wait_read_e() { asm volatile(ELECT "@p cp.async.bulk.commit_group;\n@p cp.async.bulk.wait_group.read 0;\n}" ::: "memory"); __syncwarp(); }
__device__ __forceinline__ void publish_e(unsigned* flag, unsigned tag) {
  asm volatile(ELECT "@p fence.proxy.async;\n@p st.relaxed.gpu.global.u32 [%0], %1;\n}" :: "l"(flag), "r"(tag) : "memory");
  __syncwarp();
}
__device__ __forceinline__ void fence_async_smem() { asm volatile("fence.proxy.async.shared::cta;" ::: "memory"); }
__device__ __forceinline__ void wgmma_fence() { asm volatile("wgmma.fence.sync.aligned;" ::: "memory"); }
__device__ __forceinline__ void wgmma_commit() { asm volatile("wgmma.commit_group.sync.aligned;" ::: "memory"); }
template<int N> __device__ __forceinline__ void wgmma_wait() { asm volatile("wgmma.wait_group.sync.aligned %0;" :: "n"(N) : "memory"); }
__device__ __forceinline__ void bar_sync(int id, int n) { asm volatile("bar.sync %0, %1;" :: "r"(id), "r"(n) : "memory"); }
__device__ __forceinline__ void bar_arrive(int id, int n) { asm volatile("bar.arrive %0, %1;" :: "r"(id), "r"(n) : "memory"); }
__device__ __forceinline__ void bar_arrive_after(int id, uint32_t dep) {
  asm volatile("{\n.reg .u32 n;\nor.b32 n, %1, 256;\nmin.u32 n, n, 256;\nbar.arrive %0, n;\n}" :: "r"(id), "r"(dep) : "memory");
}
__device__ __forceinline__ void bar_sync_after(int id, uint32_t dep) {
  asm volatile("{\n.reg .u32 n;\nor.b32 n, %1, 256;\nmin.u32 n, n, 256;\nbar.sync %0, n;\n}" :: "r"(id), "r"(dep) : "memory");
}
__device__ __forceinline__ uint32_t mapa(uint32_t a, uint32_t r) { uint32_t d; asm("mapa.shared::cluster.u32 %0, %1, %2;" : "=r"(d) : "r"(a), "r"(r)); return d; }
__device__ __forceinline__ void st_tag128(uint4* p, uint32_t a, uint32_t b, uint32_t c, uint32_t tag) {
  asm volatile("{\n.reg .b64 lo, hi;\n.reg .b128 v;\nmov.b64 lo, {%1, %2};\nmov.b64 hi, {%3, %4};\nmov.b128 v, {lo, hi};\nst.relaxed.gpu.global.b128 [%0], v;\n}"
    :: "l"(p), "r"(a), "r"(b), "r"(c), "r"(tag) : "memory");
}
__device__ __forceinline__ void st_tag128_if(bool on, uint4* p, uint32_t a, uint32_t b, uint32_t c, uint32_t tag) {
  asm volatile("{\n.reg .pred q;\n.reg .b64 lo, hi;\n.reg .b128 v;\nsetp.ne.u32 q, %5, 0;\nmov.b64 lo, {%1, %2};\nmov.b64 hi, {%3, %4};\nmov.b128 v, {lo, hi};\n@q st.relaxed.gpu.global.b128 [%0], v;\n}"
    :: "l"(p), "r"(a), "r"(b), "r"(c), "r"(tag), "r"((uint32_t)on) : "memory");
}
__device__ __forceinline__ uint4 ld_tag128(const uint4* p) {
  uint4 v;
  asm volatile("{\n.reg .b64 lo, hi;\n.reg .b128 v;\nld.relaxed.gpu.global.b128 v, [%4];\nmov.b128 {lo, hi}, v;\nmov.b64 {%0, %1}, lo;\nmov.b64 {%2, %3}, hi;\n}"
    : "=r"(v.x), "=r"(v.y), "=r"(v.z), "=r"(v.w) : "l"(p) : "memory");
  return v;
}
__device__ __forceinline__ void st_tag64(uint2* p, float a, uint32_t tag) {
  asm volatile("{\n.reg .b64 v;\nmov.b64 v, {%1, %2};\nst.relaxed.gpu.global.b64 [%0], v;\n}" :: "l"(p), "r"(__float_as_uint(a)), "r"(tag) : "memory");
}
__device__ __forceinline__ uint2 ld_tag64(const uint2* p) {
  uint2 v;
  asm volatile("{\n.reg .b64 v;\nld.relaxed.gpu.global.b64 v, [%2];\nmov.b64 {%0, %1}, v;\n}" : "=r"(v.x), "=r"(v.y) : "l"(p) : "memory");
  return v;
}
__device__ __forceinline__ uint32_t pack_bf16(float lo, float hi) { uint32_t r; asm("cvt.rn.bf16x2.f32 %0, %1, %2;" : "=r"(r) : "f"(hi), "f"(lo)); return r; }
__device__ __forceinline__ uint32_t relu_sq_bf16(float lo, float hi) {
  uint32_t r; asm("{\n.reg .b32 t;\ncvt.rn.relu.bf16x2.f32 t, %1, %2;\nmul.rn.bf16x2 %0, t, t;\n}" : "=r"(r) : "f"(hi), "f"(lo)); return r;
}
__device__ __forceinline__ float bf_lo(uint32_t u) { return __uint_as_float(u << 16); }
__device__ __forceinline__ float bf_hi(uint32_t u) { return __uint_as_float(u & 0xffff0000u); }
__device__ __forceinline__ void stmatrix4(uint32_t addr, uint32_t r0, uint32_t r1, uint32_t r2, uint32_t r3) {
  asm volatile("stmatrix.sync.aligned.m8n8.x4.shared.b16 [%0], {%1, %2, %3, %4};" :: "r"(addr), "r"(r0), "r"(r1), "r"(r2), "r"(r3) : "memory");
}
__device__ __forceinline__ void ldmatrix4(uint32_t addr, uint32_t (&r)[4]) {
  asm volatile("ldmatrix.sync.aligned.m8n8.x4.shared.b16 {%0, %1, %2, %3}, [%4];" : "=r"(r[0]), "=r"(r[1]), "=r"(r[2]), "=r"(r[3]) : "r"(addr) : "memory");
}
__device__ __forceinline__ void stmatrix4_t(uint32_t addr, uint32_t r0, uint32_t r1, uint32_t r2, uint32_t r3) {
  asm volatile("stmatrix.sync.aligned.m8n8.x4.trans.shared.b16 [%0], {%1, %2, %3, %4};" :: "r"(addr), "r"(r0), "r"(r1), "r"(r2), "r"(r3) : "memory");
}
__device__ __forceinline__ void ldmatrix4_t(uint32_t addr, uint32_t (&r)[4]) {
  asm volatile("ldmatrix.sync.aligned.m8n8.x4.trans.shared.b16 {%0, %1, %2, %3}, [%4];" : "=r"(r[0]), "=r"(r[1]), "=r"(r[2]), "=r"(r[3]) : "r"(addr) : "memory");
}
__device__ __forceinline__ uint32_t movmatrix(uint32_t a) { uint32_t d; asm volatile("movmatrix.sync.aligned.m8n8.trans.b16 %0, %1;" : "=r"(d) : "r"(a)); return d; }
__device__ __forceinline__ void mma16816_z(float (&c)[4], uint32_t a0, uint32_t a1, uint32_t a2, uint32_t a3, uint32_t b0, uint32_t b1, const float4& z) {
  asm volatile("mma.sync.aligned.m16n8k16.row.col.f32.bf16.bf16.f32 {%0,%1,%2,%3}, {%4,%5,%6,%7}, {%8,%9}, {%10,%11,%12,%13};"
    : "=f"(c[0]), "=f"(c[1]), "=f"(c[2]), "=f"(c[3]) : "r"(a0), "r"(a1), "r"(a2), "r"(a3), "r"(b0), "r"(b1), "f"(z.x), "f"(z.y), "f"(z.z), "f"(z.w));
}
__device__ __forceinline__ float ex2(float x) { float y; asm("ex2.approx.ftz.f32 %0, %1;" : "=f"(y) : "f"(x)); return y; }
__device__ __forceinline__ float rcp(float x) { float y; asm("rcp.approx.ftz.f32 %0, %1;" : "=f"(y) : "f"(x)); return y; }
__device__ __forceinline__ void mma16816(float (&c)[4], uint32_t a0, uint32_t a1, uint32_t a2, uint32_t a3, uint32_t b0, uint32_t b1) {
  asm volatile("mma.sync.aligned.m16n8k16.row.col.f32.bf16.bf16.f32 {%0,%1,%2,%3}, {%4,%5,%6,%7}, {%8,%9}, {%0,%1,%2,%3};"
    : "+f"(c[0]), "+f"(c[1]), "+f"(c[2]), "+f"(c[3]) : "r"(a0), "r"(a1), "r"(a2), "r"(a3), "r"(b0), "r"(b1));
}
__device__ __forceinline__ void sts128(uint32_t a, uint32_t x, uint32_t y, uint32_t z, uint32_t w) { asm volatile("st.shared.v4.b32 [%0], {%1,%2,%3,%4};" :: "r"(a), "r"(x), "r"(y), "r"(z), "r"(w) : "memory"); }
__device__ __forceinline__ float2 lds64f(uint32_t a) { float2 v; asm volatile("ld.shared.v2.f32 {%0,%1}, [%2];" : "=f"(v.x), "=f"(v.y) : "r"(a) : "memory"); return v; }
__device__ __forceinline__ float4 lds128f(uint32_t a) { float4 v; asm volatile("ld.shared.v4.f32 {%0,%1,%2,%3}, [%4];" : "=f"(v.x), "=f"(v.y), "=f"(v.z), "=f"(v.w) : "r"(a) : "memory"); return v; }
__device__ __forceinline__ void sts32f(uint32_t a, float v) { asm volatile("st.shared.f32 [%0], %1;" :: "r"(a), "f"(v) : "memory"); }
__device__ __forceinline__ void sts64f(uint32_t a, float x, float y) { asm volatile("st.shared.v2.f32 [%0], {%1,%2};" :: "r"(a), "f"(x), "f"(y) : "memory"); }
__device__ __forceinline__ uint32_t lds32(uint32_t a) { uint32_t v; asm volatile("ld.shared.u32 %0, [%1];" : "=r"(v) : "r"(a) : "memory"); return v; }
__device__ __forceinline__ float after(float x, uint32_t d, uint32_t zero) { return __uint_as_float(__float_as_uint(x) | (d & zero)); }
template<int R> __device__ __forceinline__ void reg_alloc() { asm volatile("setmaxnreg.inc.sync.aligned.u32 %0;" :: "n"(R)); }
template<int R> __device__ __forceinline__ void reg_dealloc() { asm volatile("setmaxnreg.dec.sync.aligned.u32 %0;" :: "n"(R)); }

struct Ctx {
  uint32_t sb;
  int m, j, b, rank, wg, w, lane;
};

__device__ __forceinline__ unsigned smem_tag(const Ctx& c) { return lds32(c.sb + OFF_TAG); }

__device__ __forceinline__ int own_kb(const Ctx& c, int step) {
  return step < 4 ? (c.j * 2) ^ step : (((c.j >> 1) * 4 + 2 * step + (step < 10 ? 12 : 0)) & 15) + (step >= 10);
}
__device__ __forceinline__ int kb_order(const Ctx& c, int t, int type, int step) {
  return type == 3 || t == 7 ? own_kb(c, step) : type != 2 || step < 8 ? step : step < 10 ? c.j ^ step : 8 + (((c.j & 6) + step) & 7);
}
struct WTile { const CUtensorMap* mp; int c0, c2; };
__device__ __forceinline__ WTile wtile(const Params& p, int type, int j) {
  WTile w;
  w.mp = type < 2 ? &p.w_qkv : type == 2 ? &p.w_o : type == 3 ? &p.w_1a : type < 6 ? &p.w_1b : &p.w_2;
  w.c0 = type < 2 ? (j + 8 * type) * 64 : 0;
  w.c2 = type < 2 ? 0 : type == 3 ? 3 * j : type == 4 ? 24 + 2 * j : type == 5 ? 40 + 2 * j : 2 * j;
  return w;
}
__device__ __forceinline__ int first_stage(int type) { return (0x2100433 >> (4 * type)) & 7; }

template<int BN, int RES>
__device__ __forceinline__ void mainloop(const Ctx& c, float (&acc)[2][96], int t, int type, int g, int nkb) {
  constexpr int NS = BN == 192 ? 4 : 5, STR = BN == 192 ? 40960 : 32768;
  constexpr int HL = 2;
  int st = first_stage(type);
  const bool own = BN == 192 && (type == 3 || t == 7);
  const uint32_t rel = mapa(c.sb + OFF_EMPTY, c.lane & 1);
  const uint32_t sb = (c.sb & 0x3ffffu) >> 4;
  uint32_t da = DESC_A + (own ? sb + OFF_X / 16 : sb + st * (STR / 16)), db = DESC_B + sb + st * (STR / 16);
  TL(t, 0);
  if (t > 0) bar_sync(BAR_START + c.wg, 256);
  if (RES && type == 2 && EARLY == 0) bar_sync(BAR_P1, 256);
  TL(t, 1);
  mbar_wait(c.sb + OFF_FULL + 8 * (g & 7), (g >> 3) & 1);
  TL(t, 2);
  wgmma_fence();
  wgmma_ss<BN, RES>(acc[0], da, db);
  wgmma_ss<BN, RES>(acc[1], da + 64, db);
  if (HL == 2) { wgmma_ss<BN, 1>(acc[0], da + 2, db + 128); wgmma_ss<BN, 1>(acc[1], da + 66, db + 128); }
  wgmma_commit();
#pragma unroll 1
  for (int kb = 1;; kb++) {
    wgmma_fence();
#pragma unroll
    for (int k = HL; k < 4; k++) {
      if (k == (BN == 128 ? 2 : 3) && kb == nkb && t < 13 && type > 1) bar_arrive(BAR_START + (c.wg ^ 1), 256);
      wgmma_ss<BN, 1>(acc[0], da + k * 2, db + k * 128);
      wgmma_ss<BN, 1>(acc[1], da + (64 + k * 2), db + k * 128);
    }
    wgmma_commit();
    if (kb == nkb) break;
    if (BN == 192 && type == 1 && (kb == PAUSE1 || kb == PAUSE2)) { bar_sync(BAR_P0, 256); bar_sync(BAR_P1, 256); }
    if (RES && type == 2 && kb == EARLY) bar_sync(BAR_P1, 256);
    if (++st == NS) st = 0;
    g++;
    da = DESC_A + sb + (own && kb == 1 ? (OFF_X + A_BYTES) / 16 : RES && type == 2 && kb == 8 ? OFF_STG / 16 : st * (STR / 16)); db = DESC_B + sb + st * (STR / 16);
    mbar_wait(c.sb + OFF_FULL + 8 * (g & 7), (g >> 3) & 1);
    wgmma_fence();
    wgmma_ss<BN, 1>(acc[0], da, db);
    wgmma_ss<BN, 1>(acc[1], da + 64, db);
    if (HL == 2) { wgmma_ss<BN, 1>(acc[0], da + 2, db + 128); wgmma_ss<BN, 1>(acc[1], da + 66, db + 128); }
    wgmma_commit();
    wgmma_wait<1>();
    if (c.lane < 2) mbar_arrive_cluster(rel + 8 * ((g - 1) & 7));
    TK(t, kb);
  }
}
__device__ __forceinline__ void release(const Ctx& c, int slot, int lanes = 2) {
  if (c.lane < lanes) mbar_arrive_cluster(mapa(c.sb + OFF_EMPTY, c.lane & 1) + 8 * slot);
}
__device__ __forceinline__ void finish(const Ctx& c, int t) {
  wgmma_wait<0>();
  release(c, 7);
  TL(t, 3);
}

__device__ __forceinline__ void load_row_stats(const Ctx& c, int ln) {
  const uint4* p = g_stats + (ln * 128 + c.m * 8) * 128 + c.w * 32 + c.lane;
  const unsigned tag = smem_tag(c);
  float s, q;
  for (unsigned it = 0;; it++) {
    uint4 v[8];
#pragma unroll
    for (int i = 0; i < 8; i++) v[i] = ld_tag128(p + i * 128);
    bool ok = true;
    s = 0.f; q = 0.f;
#pragma unroll
    for (int i = 0; i < 8; i++) { ok = ok && v[i].w == tag; s += __uint_as_float(v[i].x); q += __uint_as_float(v[i].y); }
    if (__all_sync(0xffffffffu, ok) || it > SPIN_LIMIT) break;
    __nanosleep(400);
  }
  const float mean = s * (1.0f / D_);
  const float var = fmaxf(q * (1.0f / D_) - mean * mean, 0.0f);
  sts64f(c.sb + OFF_RST + (c.w * 32 + c.lane) * 8, rsqrtf(var + 1e-5f), -mean);
  __syncwarp();
}

__device__ __forceinline__ void put_halo(uint32_t addr, int z, uint32_t a, uint32_t b, uint32_t c, uint32_t d) {
  if (z < 10) stmatrix4(addr + z * 384, a, b, c, d);
  else asm volatile("stmatrix.sync.aligned.m8n8.x2.shared.b16 [%0], {%1, %2};" :: "r"(addr + z * 384), "r"(a), "r"(b) : "memory");
}

__device__ __forceinline__ void fetch_halo(const Ctx& c, unsigned tag, int tile) {
  const int z0 = (c.w & 1) * 5;
  const uint4* src = g_halo + (tile * 128 + c.b - 8) * 352 + z0 * 32 + c.lane;
  uint4 G[6];
#pragma unroll
  for (int z = 0; z < 6; z++) G[z] = make_uint4(0u, 0u, 0u, 0u);
  bar_sync(BAR_HGO, 96);
  for (unsigned it = 0; c.m > 0; it++) {
    bool ok = true;
#pragma unroll
    for (int z = 0; z < 6; z++) { G[z] = ld_tag128(src + z * 32); ok = ok && G[z].w == tag; }
    if (__all_sync(0xffffffffu, ok) || it > SPIN_LIMIT) break;
  }
#pragma unroll
  for (int z = 0; z < 6; z++) put_halo(c.sb + OFF_STG + (z0 - 5) * 384 + c.lane * 16, z + 5, G[z].x, G[z].y, G[z].z, G[z].w);
  if (z0) sts32f(c.sb + OFF_RST - 256 + c.lane * 8, __uint_as_float(G[5].z));
  __syncwarp();
  mbar_arrive_e(c.sb + OFF_HALO);
}

__device__ __forceinline__ void epi_qkv(const Ctx& c, float (&acc)[2][96], int t, int q) {
  const int lane = c.lane, w = c.w, g = lane >> 2, cc = lane & 3;
  const int layer = t >= 7;
  const uint32_t sb = (c.sb & 0x3ffffu) >> 4, par = layer ^ 1;
  uint32_t da = DESC_A + sb + 64, db = DESC_B + sb;
#define MMA(i, n) do { wgmma_ss<192, 1>(acc[i], da, db); \
    asm volatile("add.s32 %0, %0, %2;\nadd.s32 %1, %1, %3;" : "+r"(da), "+r"(db) : "r"((n) == 11 ? -5190 : ((n) & 3) == 3 ? 2554 : 2), "r"((n) == 11 ? -5504 : ((n) & 3) == 3 ? 2176 : 128)); } while (0)
  mbar_wait(c.sb + OFF_FULL + 40, par);
  wgmma_fence();
  MMA(1, 0); MMA(1, 1); MMA(1, 2); MMA(1, 3);
  wgmma_commit();
  wgmma_wait<1>();
  release(c, 4);
  mbar_wait(c.sb + OFF_FULL + 48, par);
  MMA(1, 4); MMA(1, 5);
  bar_sync(BAR_EPI + c.wg, 256);
  MMA(1, 6);
  mbar_wait(c.sb + OFF_TBL + 16 * q, 0);
  MMA(1, 7);
  mbar_wait(c.sb + OFF_FULL + 56, par);
  MMA(1, 8);
  bar_sync(BAR_FREE, 160);
  MMA(1, 9);
  const uint32_t rst = c.sb + OFF_RST + w * 256;
  float mu[4];
#pragma unroll
  for (int r = 0; r < 4; r++) mu[r] = __uint_as_float(lds32(rst + (8 * r + g) * 8 + 4));
  const uint32_t tag = smem_tag(c), rs_l = lds32(rst + lane * 8);
  const uint32_t csb = c.sb + OFF_CSQ + q * 768 + cc * 16;
  const uint32_t stg = c.sb + OFF_STG + w * 4096;
  uint4* const halo = g_halo + ((layer * 2 + q) * 128 + c.b) * 352 + lane;
  const bool send = w == 3 && c.m < 15, nohalo = w == 0 && c.m == 0;
  const int now = q == 1 && w == 0 ? 0 : 2;
  float4 cs = lds128f(csb + 4 * 64);
  MMA(1, 10); MMA(1, 11);
  wgmma_commit();
  MMA(0, 0);
  wgmma_commit();
  MMA(0, 1);
  wgmma_commit();
  wgmma_wait<2>();
  TL(t, 8);
  uint32_t P[3][2][4][4];
#define CONV(i, np) do { _Pragma("unroll") for (int z = 0; z < 4; z++) { const int nt = 2 * (np) + (z & 1), h = z >> 1; \
    P[nt >> 3][(nt >> 2) & 1][2 * h + (i)][nt & 3] = pack_bf16(fmaf(z & 1 ? cs.z : cs.x, mu[2 * h + (i)], acc[i][4 * nt + 2 * h]), \
                                                              fmaf(z & 1 ? cs.w : cs.y, mu[2 * h + (i)], acc[i][4 * nt + 2 * h + 1])); } } while (0)
#define HW(u) ((u) == 32 ? rs_l : P[1 + (((u) >> 4) & 1)][((u) >> 3) & 1][((u) & 2) + 1][(((u) >> 1) & 2) + ((u) & 1)])
#pragma unroll
  for (int n = 0; n < 12; n++) {
    const int np = (n + 4) % 12;
    if (n == HGO && w == 0) bar_arrive(BAR_HGO, 96);
    if (n == 8) bar_arrive(BAR_START + (c.wg ^ 1), 256);
    if (n < 10) { MMA(0, n + 2); wgmma_commit(); }
    CONV(1, np);
    if (n == 7) mbar_wait(c.sb + OFF_TBL + 8, 0);
    cs = lds128f(csb + (n < 11 ? (n + 5) % 12 : 0) * 64);
#pragma unroll
    for (int z = 0; z < 11; z++)
      if (n < 8 && z >= 4 * n / 3 && (n == 7 || z < 4 * (n + 1) / 3)) {
        st_tag128_if(send, halo + z * 32, HW(3 * z), HW(3 * z + 1), HW(3 * z + 2), tag);
        put_halo(stg + 4096 + lane * 16, z, HW(3 * z), HW(3 * z + 1), HW(3 * z + 2), tag);
      }
    if (n < 10) wgmma_wait<2>();
    if (n == 3 || n == 7) release(c, 5 + (n >> 2), n == 3 ? 2 : now);
  }
#undef MMA
  wgmma_wait<0>();
  release(c, 7, now);
  TL(t, 3);
#pragma unroll
  for (int np = 0; np < 12; np++) {
    CONV(0, np);
    if (np < 11) cs = lds128f(csb + (np + 1) * 64);
  }
#undef CONV
#pragma unroll
  for (int z = 0; z < 16; z++) P[2][z >> 3][(z >> 1) & 2][z & 3] = movmatrix(P[2][z >> 3][(z >> 1) & 2][z & 3]);
  uint32_t K1[4][4], V1[4][4];
  const uint32_t hl = stg + (lane & 15) * 16 + (lane >> 4) * 512;
#define HZ(z) (((z) >> 1) * 1024 + ((z) & 1) * 256)
  __syncwarp();
#pragma unroll
  for (int z = 0; z < 4; z++) { ldmatrix4(hl + 4096 + HZ(z), K1[z]); ldmatrix4_t(hl + 4096 + 2048 + HZ(z), V1[z]); }
  TL(t, 9);
  bar_sync(BAR_WG + c.wg, 128);
  if (w == 0) mbar_wait(c.sb + OFF_HALO, q);
  release(c, 6, 2 - now); release(c, 7, 2 - now);
#undef HW
  uint32_t HK[4][4], HV[4][4];
#pragma unroll
  for (int z = 0; z < 4; z++) ldmatrix4(hl + HZ(z), HK[z]);
#pragma unroll
  for (int z = 0; z < 4; z++) ldmatrix4_t(hl + 2048 + HZ(z), HV[z]);
#undef HZ
  const bool far0 = 2 * cc > g, far1 = 2 * cc + 1 > g;
  float rk[4][2], sc[4][2];
#pragma unroll
  for (int r = 0; r < 4; r++) {
    const float rq = __uint_as_float(lds32(rst + (8 * r + g) * 8)) * (0.17677669529663687f * 1.4426950408889634f);
    const int back = r & 1 ? 64 : 192;
    rk[r][0] = __uint_as_float(lds32(rst + r * 64 + cc * 16 - (far0 ? back : 0)));
    rk[r][1] = __uint_as_float(lds32(rst + r * 64 + cc * 16 + 8 - (far1 ? back : 0)));
    sc[r][0] = rq * rk[r][0]; sc[r][1] = rq * rk[r][1];
  }
  TL(t, 4);
  float S[4][3][4];
  if (q == 0) bar_sync(BAR_P0, 256);
  float4 zero = lds128f(c.sb + OFF_ZERO);
#pragma unroll
  for (int k = 0; k < 2; k++)
#pragma unroll
    for (int z = 0; z < 4; z++) {
      const uint32_t* qa = P[0][z >> 1][2 * (z & 1)]; const uint32_t* qb = P[0][z >> 1][2 * (z & 1) + 1];
      const uint32_t* kk[3] = {HK[z], P[1][z >> 1][2 * (z & 1)], K1[z]};
#pragma unroll
      for (int n = 0; n < 3; n++) {
        if (k == 0) mma16816_z(S[z][n], qa[0], qb[0], qa[1], qb[1], kk[n][0], kk[n][1], zero);
        else mma16816(S[z][n], qa[2], qb[2], qa[3], qb[3], kk[n][2], kk[n][3]);
      }
    }
  if (q == 0) {
    uint32_t dep = 0;
#pragma unroll
    for (int z = 0; z < 12; z++) dep |= __float_as_uint(S[z / 3][z % 3][0]);
    bar_arrive_after(BAR_P1, dep);
  }
  TL(t, 10);
  const uint32_t fmask = (far0 ? 0xffffu : 0u) | (far1 ? 0xffff0000u : 0u);
  uint32_t pf[4][2], pn[4][2];
#pragma unroll
  for (int z = 0; z < 4; z++)
#pragma unroll
    for (int i = 0; i < 2; i++) {
      const int r = 2 * (z & 1) + i;
      float l0 = (far0 ? S[z][i][2 * i] : S[z][i + 1][2 * i]) * sc[r][0];
      float l1 = (far1 ? S[z][i][2 * i + 1] : S[z][i + 1][2 * i + 1]) * sc[r][1];
      if (i == 0 && nohalo) { const float neg = -1e9f * 1.4426950408889634f; if (far0) l0 = neg; if (far1) l1 = neg; }
      float mx = fmaxf(l0, l1);
      mx = fmaxf(mx, __shfl_xor_sync(0xffffffffu, mx, 1));
      mx = fmaxf(mx, __shfl_xor_sync(0xffffffffu, mx, 2));
      l0 = ex2(l0 - mx); l1 = ex2(l1 - mx);
      float sum = l0 + l1;
      l0 *= rk[r][0]; l1 *= rk[r][1];
      sum += __shfl_xor_sync(0xffffffffu, sum, 1);
      sum += __shfl_xor_sync(0xffffffffu, sum, 2);
      sum = rcp(sum);
      const uint32_t u = pack_bf16(l0 * sum, l1 * sum);
      pf[z][i] = u & fmask; pn[z][i] = u & ~fmask;
    }
  float O[4][2][2][4];
  TL(t, 11);
  if (q == 0) bar_sync_after(BAR_P0, (pn[0][0] | pn[0][1] | pn[1][0]) | (pn[1][1] | pn[2][0] | pn[2][1]) | (pn[3][0] | pn[3][1]));
  zero = lds128f(c.sb + OFF_ZERO);
  TL(t, 12);
#pragma unroll
  for (int z = 0; z < 4; z++)
#pragma unroll
    for (int d = 0; d < 2; d++) {
      const uint32_t* v0 = P[2][z >> 1][2 * (z & 1)] + 2 * d;
      mma16816_z(O[z][0][d], HV[z][2 * d], HV[z][2 * d + 1], v0[0], v0[1], pf[z][0], pn[z][0], zero);
      mma16816_z(O[z][1][d], v0[0], v0[1], V1[z][2 * d], V1[z][2 * d + 1], pf[z][1], pn[z][1], zero);
    }
  {
    uint32_t dep = 0;
#pragma unroll
    for (int z = 0; z < 16; z++) dep |= __float_as_uint(O[z >> 2][(z >> 1) & 1][z & 1][0]);
    bar_arrive_after(BAR_P1, dep);
  }
  TL(t, 5);
#pragma unroll
  for (int nt = 0; nt < 8; nt++) {
    uint32_t u[4];
#pragma unroll
    for (int r = 0; r < 4; r++) { const float* o = O[2 * (nt >> 2) + (r >> 1)][r & 1][(nt >> 1) & 1] + 2 * (nt & 1); u[r] = pack_bf16(o[0], o[1]); }
    stmatrix4_t(stg + lane * 128 + ((nt ^ (lane & 7)) << 4), u[0], u[1], u[2], u[3]);
  }
  fence_async_smem();
  bar_arrive(BAR_READY, 160);
  TL(t, 13);
}

template<int CH>
__device__ __forceinline__ void epi_up(const Ctx& c, float (&acc)[2][96], int type) {
  const int lane = c.lane, w = c.w, g = lane >> 2, cc = lane & 3;
  float rs[4], nm[4];
#pragma unroll
  for (int r = 0; r < 4; r++) { const float2 v = lds64f(c.sb + OFF_RST + (w * 32 + 8 * r + g) * 8); rs[r] = v.x; nm[r] = v.x * v.y; }
  const int loc0 = type == 3 ? 0 : (type == 4 ? 192 : 320);
  const uint32_t cb = c.sb + OFF_UP + loc0 * 8 + cc * 16;
  const uint32_t zero = lds32(c.sb + OFF_ZERO);
  uint32_t d[2] = {0u, 0u};
  const uint32_t stg = c.sb + OFF_STG + w * 4096;
#pragma unroll
  for (int ch = CH; ch < (CH ? 3 : 2); ch++) {
    uint32_t P[8][4];
#pragma unroll
    for (int n8 = 0; n8 < 8; n8++) {
      const int nt = ch * 8 + n8;
      const float4 cv = lds128f(cb + nt * 64);
#pragma unroll
      for (int r = 0; r < 4; r++) {
        const float m = after(nm[r], d[r & 1], zero);
        d[r & 1] = P[n8][r] = relu_sq_bf16(fmaf(acc[r & 1][4 * nt + 2 * (r >> 1)], rs[r], fmaf(cv.x, m, cv.z)),
                                           fmaf(acc[r & 1][4 * nt + 2 * (r >> 1) + 1], rs[r], fmaf(cv.y, m, cv.w)));
      }
    }
    bar_sync(BAR_FREE, 160);
#pragma unroll
    for (int n8 = 0; n8 < 8; n8++)
      stmatrix4(stg + lane * 128 + ((n8 ^ (lane & 7)) << 4), P[n8][0], P[n8][1], P[n8][2], P[n8][3]);
    fence_async_smem();
    bar_arrive(BAR_READY, 160);
  }
}

__device__ __forceinline__ void init_res(const Ctx& c, float (&acc)[2][96], int t, bool bias) {
  if (t <= 2) mbar_wait(c.sb + OFF_XBAR, 0);
  const uint32_t xb = c.sb + OFF_X + c.w * 4096 + c.lane * 128;
#pragma unroll
  for (int nt = 0; nt < 16; nt++) {
    uint32_t u[4];
    ldmatrix4(xb + (nt >> 3) * A_BYTES + (((nt & 7) ^ (c.lane & 7)) << 4), u);
    float2 b = make_float2(0.f, 0.f);
    if (bias) b = lds64f(c.sb + OFF_B2 + nt * 32 + (c.lane & 3) * 8);
#pragma unroll
    for (int r = 0; r < 4; r++) {
      acc[r & 1][4 * nt + 2 * (r >> 1)] = bf_lo(u[r]) + b.x;
      acc[r & 1][4 * nt + 2 * (r >> 1) + 1] = bf_hi(u[r]) + b.y;
    }
  }
}

__device__ __forceinline__ void epi_res(const Ctx& c, float (&acc)[2][96]) {
  const uint32_t xw = c.sb + OFF_X + c.w * 4096 + c.lane * 128;
#pragma unroll
  for (int nt = 0; nt < 16; nt++)
    stmatrix4(xw + (nt >> 3) * A_BYTES + (((nt & 7) ^ (c.lane & 7)) << 4),
              pack_bf16(acc[0][4 * nt], acc[0][4 * nt + 1]), pack_bf16(acc[1][4 * nt], acc[1][4 * nt + 1]),
              pack_bf16(acc[0][4 * nt + 2], acc[0][4 * nt + 3]), pack_bf16(acc[1][4 * nt + 2], acc[1][4 * nt + 3]));
  fence_async_smem();
  bar_arrive(BAR_RES, 192);
}

__device__ __forceinline__ void row_stats(const Ctx& c, float (&acc)[2][96], int ln) {
  const int g = c.lane >> 2, cc = c.lane & 3;
  float sm[4], sq[4];
#pragma unroll
  for (int r = 0; r < 4; r++) {
    float a = 0.f, b = 0.f;
#pragma unroll
    for (int n = 0; n < 32; n++) { const float x = acc[r & 1][4 * (n >> 1) + 2 * (r >> 1) + (n & 1)]; a += x; b = fmaf(x, x, b); }
    a += __shfl_xor_sync(0xffffffffu, a, 1); b += __shfl_xor_sync(0xffffffffu, b, 1);
    a += __shfl_xor_sync(0xffffffffu, a, 2); b += __shfl_xor_sync(0xffffffffu, b, 2);
    sm[r] = a; sq[r] = b;
  }
  const float a = cc == 0 ? sm[0] : cc == 1 ? sm[1] : cc == 2 ? sm[2] : sm[3];
  const float b = cc == 0 ? sq[0] : cc == 1 ? sq[1] : cc == 2 ? sq[2] : sq[3];
  st_tag128(g_stats + (ln * 128 + c.b) * 128 + c.w * 32 + 8 * cc + g, __float_as_uint(a), __float_as_uint(b), 0u, smem_tag(c));
}

__device__ __forceinline__ void load_table(const Ctx& c, const Params& p, int part, unsigned tag) {
  const int i0 = ((0xb96301 >> (4 * part)) & 15) * 64 + c.lane, n = (0x446624 >> (4 * part)) & 7;
  const uint2* src = g_cs + c.j * NCS + i0;
  const uint32_t dst = c.sb + OFF_CSQ + (i0 & 1) * 4 + (part < 3 ? (i0 >> 4) * 64 + (i0 & 6) * 8 + (i0 & 8) : 1536 + ((i0 - 384) >> 1) * 16);
  const __nv_bfloat16* bias = p.b1 + (part == 3 ? c.j * 192 : (part == 4 ? 1536 : 2560) + c.j * 128) + c.lane;
  float v[6];
  if (part >= 3) {
#pragma unroll
    for (int k = 0; k < 6; k++) if (k < n) sts32f(dst + k * 256 + 8, __bfloat162float(bias[k * 32]));
  }
  for (unsigned it = 0;; it++) {
    bool ok = true;
#pragma unroll
    for (int k = 0; k < 6; k++) { const uint2 a = ld_tag64(src + (k < n ? k * 32 : 0)); ok = ok && a.y == tag; v[k] = __uint_as_float(a.x); }
    if (__all_sync(0xffffffffu, ok) || it > SPIN_LIMIT) break;
    __nanosleep(200);
  }
#pragma unroll
  for (int k = 0; k < 6; k++) if (k < n) sts32f(dst + k * (part < 3 ? 128 : 256), v[k]);
  __syncwarp();
}

__device__ __forceinline__ void colsum_cta(const Ctx& c, const Params& p, unsigned* epoch) {
  mbar_init_e(c.sb + OFF_FULL + 32 * c.wg + 8 * c.w, 1);
  sts32f(c.sb + OFF_STG + threadIdx.x * 4, __uint_as_float(0x3f803f80u));
  fence_async_smem();
  __syncthreads();
  if (c.wg == 2) return;
  const unsigned tag = *(volatile unsigned*)epoch + 1;
  const int j = (blockIdx.x - 128) * 2 + c.wg;
  const uint32_t ring = c.sb + c.wg * 98304, full = c.sb + OFF_FULL + 48 * c.wg;
  const uint64_t ones = (uint64_t)(((c.sb + OFF_STG) & 0x3ffffu) >> 4) | (8u << 16) | ((uint64_t)16u << 32);
  float d[4];
  int st = 0, ph = 1;
#pragma unroll 1
  for (int n = -6; n < 104; n++) {
    if (n >= 0) {
      mbar_wait(full + 8 * st, ph);
      const uint64_t da = (uint64_t)(((ring + st * 16384) & 0x3ffffu) >> 4) | (64u << 16) | ((uint64_t)(64u | (1u << 30)) << 32);
      wgmma_fence();
#pragma unroll
      for (int k = 0; k < 8; k++)
        asm volatile("{\n.reg .pred p;\nsetp.ne.b32 p, %6, 0;\nwgmma.mma_async.sync.aligned.m64n8k16.f32.bf16.bf16 {%0,%1,%2,%3}, %4, %5, p, 1, 1, 1, 0;\n}"
          : "+f"(d[0]), "+f"(d[1]), "+f"(d[2]), "+f"(d[3]) : "l"(da + k * 128), "l"(ones), "r"((n & 7) | k));
      wgmma_commit();
      wgmma_wait<0>();
      bar_sync(BAR_WG + c.wg, 128);
      if ((n & 7) == 7 && (c.lane & 3) < 2)
        st_tag64(g_cs + j * NCS + (n < 48 ? (0x354021 >> ((n >> 3) * 4)) & 7 : n >> 3) * 64 + c.w * 16 + (c.lane >> 2) + (c.lane & 1) * 8, (c.lane & 1) ? d[2] : d[0], tag);
      __syncwarp();
    }
    if (c.w == 0 && n < 98) {
      const int u = (n + 6) >> 3;
      mbar_expect_e(full + 8 * st, 16384);
      tma_ld3_e(ring + st * 16384, u < 6 ? &p.s_qkv : &p.s_1, full + 8 * st, 0, ((n + 6) & 7) * 128,
                u < 6 ? ((0x153042 >> (u * 4)) & 7) * 8 + j : u < 9 ? 3 * j + u - 6 : 2 * j + u + (u < 11 ? 15 : 29));
    }
    if (++st == 6) { st = 0; ph ^= 1; }
  }
  bar_sync(BAR_START, 256);
  if (threadIdx.x == 0) *epoch = tag;
}

__global__ void __cluster_dims__(2, 1, 1) __launch_bounds__(384, 1) fused_kernel(unsigned* const epochs, const __grid_constant__ Params p) {
  extern __shared__ uint8_t smem_raw[];
  Ctx c;
  c.sb = (smem_u32(smem_raw) + 1023) & ~1023u;
  const int tid = threadIdx.x;
  const int k = __shfl_sync(0xffffffffu, tid >> 5, 0);
  c.wg = k >> 2; c.w = k & 3; c.lane = tid & 31;
  c.rank = blockIdx.x & 1;
  if (blockIdx.x >= 128) { colsum_cta(c, p, epochs + blockIdx.x); return; }
  uint32_t slot; asm volatile("mov.u32 %0, %%smid;" : "=r"(slot));
  slot = __shfl_sync(0xffffffffu, slot < 120 ? slot >> 1 : 60 + ((slot >> 1) & 3), 0);
  const bool claim = tid == 0 && c.rank == 0;
  unsigned epoch, old;
  asm volatile("{\n.reg .pred p;\nsetp.ne.u32 p, %4, 0;\nmov.u32 %0, 0;\nmov.u32 %1, 0;\n@p atom.relaxed.gpu.global.add.u32 %0, [%2], 1;\n@p ld.relaxed.gpu.global.u32 %1, [%3];\n}"
    : "=r"(old), "=r"(epoch) : "l"(epochs + 132 + slot + tid), "l"(epochs + blockIdx.x), "r"((uint32_t)claim) : "memory");
#pragma unroll 1
  for (int pass = 0;; pass++) {
    const int row = slot < 32 ? slot >> 3 : slot < 60 ? ((slot - 4) * 37) >> 8 : slot - 56;
    const int gpc = slot < 60 ? slot - row * (slot < 32 ? 8 : 7) - (slot < 32 ? 0 : 3) : 0;
    c.m = (gpc & 1) * 8 + row;
    c.j = (gpc & 6) + c.rank; c.b = c.m * 8 + c.j;
    if (k == 9) {
      asm volatile(ELECT "@p mbarrier.init.shared::cta.b64 [%0], 2;\n@p mbarrier.init.shared::cta.b64 [%0 + 8], 2;\n"
        "@p mbarrier.init.shared::cta.b64 [%0 + 16], 2;\n@p mbarrier.init.shared::cta.b64 [%0 + 24], 2;\n}" :: "r"(c.sb + OFF_FULL) : "memory");
      fence_async_smem();
      if (!pass) asm volatile("fence.mbarrier_init.release.cluster;\nbarrier.cluster.arrive.relaxed.aligned;" ::: "memory");
#pragma unroll 1
      for (int s = 0; s < 4; s++) {
        const uint32_t full = c.sb + OFF_FULL + 8 * s, dst = c.sb + ((s + 3) & 3) * 40960;
        mbar_expect_e(full, 40960);
        tma_ld4_e(dst, &p.ld_x, full, s * 64, c.m * 4);
        tma_ld4_e(dst + 8192, &p.ld_x, full, s * 64, c.m * 4 + 2);
        tma_ld3_e(dst + A_BYTES, &p.w_qkv, full, c.j * 64, s * 64, 0);
        mbar_arrive_e(full);
      }
    } else if (!pass) {
      if (k < 8) { mbar_init_e(c.sb + OFF_EMPTY + 8 * k, 8); mbar_init_e(c.sb + (k < 4 ? OFF_XBAR : OFF_FULL) + 8 * k, k < 4 ? 1 : 2); }
      if (k == 10) { mbar_init_e(c.sb + OFF_TBL + 24, 1); mbar_init_e(c.sb + OFF_HALO, 2); mbar_init_e(c.sb + OFF_SLOT, 1); mbar_expect_e(c.sb + OFF_SLOT, 8); sts128(c.sb + OFF_ZERO, 0u, 0u, 0u, 0u); }
      asm volatile("fence.mbarrier_init.release.cluster;\nbarrier.cluster.arrive.relaxed.aligned;" ::: "memory");
    }
    if (pass) { __syncthreads(); break; }
    asm volatile("barrier.cluster.wait.aligned;" ::: "memory");
    if (claim) {
      uint32_t s = slot;
      for (int it = 0; old != epoch && it < 64; it++) { atomicSub(epochs + 132 + s, 1u); s = (s + 1) & 63; old = atomicAdd(epochs + 132 + s, 1u); }
#pragma unroll
      for (int r = 0; r < 2; r++)
        asm volatile("{\n.reg .u32 t;\nadd.u32 t, %1, 1;\nst.async.weak.shared::cluster.mbarrier::complete_tx::bytes.v2.b32 [%0], {t, %2}, [%3];\n}"
          :: "r"(mapa(c.sb + OFF_TAG, r)), "r"(old), "r"(s), "r"(mapa(c.sb + OFF_SLOT, r)) : "memory");
    }
    __syncwarp();
    mbar_wait(c.sb + OFF_SLOT, 0);
    const uint32_t got = __shfl_sync(0xffffffffu, lds32(c.sb + OFF_TAG + 4), 0);
    if (got == slot) break;
    slot = got;
    if (k == 9)
      for (int s = 0; s < 4; s++) { mbar_wait(c.sb + OFF_FULL + 8 * s, 0); asm volatile(ELECT "@p mbarrier.inval.shared::cta.b64 [%0];\n}" :: "r"(c.sb + OFF_FULL + 8 * s) : "memory"); }
  }
  if (c.wg == 2) {
    reg_dealloc<40>();
    const unsigned tag = smem_tag(c);
    if (c.w < 2) {
      int g = 4;
#pragma unroll 1
      for (int t = 0; t < 14; t++) {
        const int layer = t >= 7, type = t - layer * 7;
        const bool wide = type < 2 || type == 3, own = type == 3 || t == 7;
        const int nkb = type == 6 ? 56 : 16, ns = wide ? 4 : 5, str = wide ? 40960 : 32768;
        const int nshort = type == 0 ? 3 : (type == 2 || type == 4) ? 4 : 0;
        int st = first_stage(type);
        if (c.w == 0) {
          const CUtensorMap* mp = type == 2 || type == 6 ? &p.ld_h : (t < 2 ? &p.ld_x : &p.ld_out);
          const int slab = c.m * 4 + c.rank * 2;
          const unsigned* fp = g_flags + (t * 16 + c.m) * 32 + c.lane;
          unsigned ready = own ? 15u << (c.j >> 1) * 4 : type == 2 ? 0x300u << (c.j & 6) : type == 6 ? 0u : ~0u;
          const int local = own ? 0 : type == 2 ? 8 : 64, nloc = own ? 2 : 1;
#pragma unroll 1
          for (int step = t ? 0 : 4; step < nkb; step++, g++) {
            const int kb = kb_order(c, t, type, step);
            const int piece = type != 6 ? kb : step < 24 ? (step * 43) >> 7 : (step >> 1) - 4;
            for (unsigned it = 0; !((ready >> piece) & 1) && it < SPIN_LIMIT; it++) {
              unsigned v; asm volatile("ld.relaxed.gpu.global.u32 %0, [%1];" : "=r"(v) : "l"(fp) : "memory");
              ready |= __ballot_sync(0xffffffffu, v == tag);
              asm volatile("fence.proxy.async.global;" ::: "memory");
            }
            const int e = g - (step < nshort ? ns - 1 : ns);
            if (e >= 0) mbar_wait(c.sb + OFF_EMPTY + 8 * (e & 7), (e >> 3) & 1);
            const uint32_t full = c.sb + OFF_FULL + 8 * (g & 7);
            if ((unsigned)(step - local) >= nloc) mbar_expect_e(full, A_BYTES);
            if ((unsigned)(step - local) >= 2 * nloc) tma_ld4_mc_e(c.sb + st * str + c.rank * 8192, mp, full, kb * 64, slab);
            else if (step == 9) {
              const uint32_t peer = mapa(c.sb, c.rank ^ 1);
              mbar_wait(c.sb + OFF_FULL, layer ^ 1);
              dsmem_copy_e(peer + 3 * 32768, c.sb + OFF_STG, peer + OFF_FULL + 8);
            }
            if (++st == ns) st = 0;
          }
        } else {
          const WTile w = wtile(p, type, c.j);
#pragma unroll 1
          for (int step = t ? 0 : 4; step < nkb; step++, g++) {
            const int e = g - (step < nshort ? ns - 1 : ns);
            if (e >= 0) mbar_wait(c.sb + OFF_EMPTY + 8 * (e & 7), (e >> 3) & 1);
            const uint32_t full = c.sb + OFF_FULL + 8 * (g & 7);
            const int kb = kb_order(c, t, type, step);
            mbar_expect_e(full, str - A_BYTES);
            tma_ld3_e(c.sb + st * str + A_BYTES, w.mp, full, w.c0, kb * 64, w.c2);
            if ((g & 15) == c.m && g + 16 < 2 * KB_LAYER) {
              const bool nx = step + 16 >= nkb;
              const int s2 = step + 16 - (nx ? nkb : 0);
              const WTile v = wtile(p, nx ? (type == 6 ? 0 : type + 1) : 6, c.j);
              tma_pf3_e(v.mp, v.c0, (nx && (type == 2 || type == 6) ? own_kb(c, s2) : s2) * 64, v.c2);
            }
            if (++st == ns) st = 0;
          }
        }
      }
    } else if (c.w == 2) {
      bar_arrive(BAR_FREE, 160);
#pragma unroll 1
      for (int t = 0; t < 14; t++) {
        const int layer = t >= 7, type = t - layer * 7;
        const int slab = c.m * 4;
        unsigned* flag = g_flags + c.m * 32 + c.j;
        if (type == 2 || type == 6) {
          flag += (t + 1) * 512 + c.j;
          bar_sync(BAR_RES, 192);
          tma_st4_e(&p.st_out, c.sb + OFF_X, c.j * 128, slab);
          if (t < 13) {
            bulk_wait_read_e();
            bar_arrive(BAR_COPY, 64);
            PTL(t, 8);
            publish_e(flag++, tag);
            PTL(t, 9);
          }
          tma_st4_e(&p.st_out, c.sb + OFF_X + A_BYTES, c.j * 128 + 64, slab);
          bulk_wait_read_e();
          PTL(t, 11);
        } else {
          flag += (layer * 7 + (type < 2 ? 2 : 6)) * 512 + (type < 2 ? type : type - 3) * 8;
          const int col = type < 2 ? (c.j + 8 * type) * 64 : type == 3 ? c.j * 192 : (type == 4 ? 1536 : 2560) + c.j * 128;
#pragma unroll 1
          for (int ch = type == 3 ? -1 : 0; ch < (type < 2 ? 1 : 2); ch++) {
            if (type < 2) fetch_halo(c, tag, layer * 2 + type);
            bar_sync(BAR_READY, 160);
            tma_st4_e(&p.st_h, c.sb + OFF_STG, col + (ch < 0 ? 128 : ch * 64), slab);
            if (type == 1) { mbar_wait(c.sb + OFF_FULL, layer); mbar_arrive_e(c.sb + OFF_FULL); }
            bulk_wait_read_e();
            if (t < 12 || ch == 0) bar_arrive(BAR_FREE, 160);
          }
          PTL(t, 14);
        }
        if (t < 13) publish_e(flag, tag);
        PTL(t, 6);
      }
      if (c.lane == 0) epochs[blockIdx.x] = tag;
    } else {
      mbar_wait(c.sb + OFF_FULL + 0, 0);
      PTL(14, 14);
      mbar_expect_e(c.sb + OFF_XBAR, 32768);
#pragma unroll
      for (int i = 0; i < 4; i++) tma_ld4_e(c.sb + OFF_X + i * 8192, &p.ld_x, c.sb + OFF_XBAR, c.j * 128 + (i >> 1) * 64, c.m * 4 + (i & 1) * 2);
#pragma unroll
      for (int i = 0; i < 4; i++) sts32f(c.sb + OFF_B2 + i * 128 + c.lane * 4, __bfloat162float(p.b2[c.j * 128 + i * 32 + c.lane]));
      const uint32_t peer = mapa(c.sb, c.rank ^ 1);
      int part = 0;
#pragma unroll 1
      for (int i = 0; i < 3; i++) {
        const int g1 = i == 0 ? 48 : i == 1 ? KB_LAYER : KB_LAYER + 48;
#pragma unroll 1
        for (; part < (i == 0 ? 3 : i == 1 ? 6 : 8); part++) {
          if (part < 6) {
            load_table(c, p, part, tag);
            if (part != 3 && part != 4) mbar_arrive_e(c.sb + OFF_TBL + 8 * (part < 3 ? part : 3));
            PTL(part, 7);
          }
          if (i != 1 && part) fetch_halo(c, tag, part - (i ? 4 : 1));
        }
        bar_sync(BAR_RES, 192);
        mbar_arrive_e(c.sb + OFF_FULL);
        mbar_arrive_e(c.sb + OFF_FULL + 8);
        mbar_wait(c.sb + OFF_EMPTY + 56, ((g1 - 1) >> 3) & 1);
        bar_sync(BAR_COPY, 64);
        __nanosleep(40);
#pragma unroll
        for (int ch = 0; ch < 2; ch++)
          dsmem_copy_e(peer + ((i == 1 ? 1 : 2) + ch) * 40960, c.sb + OFF_X + ch * A_BYTES, peer + OFF_FULL + 16 + 8 * ch);
        PTL(i == 0 ? 2 : i == 1 ? 6 : 9, 10);
      }
      bar_arrive(BAR_RES, 192);
    }
  } else {
    reg_alloc<232>();
#pragma unroll 1
    for (int t = -c.wg; t < 14; t += 2) {
      const int layer = t >= 7, type = t - layer * 7;
      const int g0 = layer * KB_LAYER + type * 16;
      float acc[2][96];
      if (t < 0 || type == 2 || type == 6) {
        init_res(c, acc, t, type == 6);
        if (t >= 0) {
          const int nkb = type == 6 ? 56 : 16;
          mainloop<128, 1>(c, acc, t, type, g0, nkb);
          finish(c, t);
          if (t == 13) asm volatile("barrier.cluster.arrive.relaxed.aligned;" ::: "memory");
          epi_res(c, acc);
          if (t == 13) break;
        }
        TL(t, 4);
        const int ln = t < 0 ? 0 : layer * 2 + (type == 6 ? 2 : 1);
        row_stats(c, acc, ln);
        load_row_stats(c, ln);
        TL(t, 5);
      } else {
        if (type < 4) {
          mainloop<192, 0>(c, acc, t, type, g0, type < 2 ? 13 : 16);
          if (type < 2) { epi_qkv(c, acc, t, type); goto done; }
          finish(c, t);
          bar_sync(BAR_EPI + c.wg, 256);
          mbar_wait(c.sb + OFF_TBL + 24, 0);
          epi_up<2>(c, acc, type);
        } else {
          mainloop<128, 0>(c, acc, t, type, g0, 16);
          finish(c, t);
          bar_sync(BAR_EPI + c.wg, 256);
        }
        epi_up<0>(c, acc, type);
        TL(t, 4);
      done:;
      }
      if (type != 1 && type != 5) bar_arrive(BAR_EPI + (c.wg ^ 1), 256);
    }
    if (c.wg == 1) {
      asm volatile("barrier.cluster.wait.aligned;" ::: "memory");
    }
  }
}

typedef CUresult (*EncodeFn)(CUtensorMap*, CUtensorMapDataType, cuuint32_t, void*, const cuuint64_t*, const cuuint64_t*,
                             const cuuint32_t*, const cuuint32_t*, CUtensorMapInterleave, CUtensorMapSwizzle,
                             CUtensorMapL2promotion, CUtensorMapFloatOOBfill);

void make_map(EncodeFn fn, CUtensorMap* m, const void* ptr, int rank, const cuuint64_t* dims, const cuuint64_t* strides, const cuuint32_t* box) {
  const cuuint32_t es[4] = {1, 1, 1, 1};
  fn(m, CU_TENSOR_MAP_DATA_TYPE_BFLOAT16, rank, const_cast<void*>(ptr), dims, strides, box, es, CU_TENSOR_MAP_INTERLEAVE_NONE,
     CU_TENSOR_MAP_SWIZZLE_128B, CU_TENSOR_MAP_L2_PROMOTION_L2_128B, CU_TENSOR_MAP_FLOAT_OOB_FILL_NONE);
}
void map_rows(EncodeFn fn, CUtensorMap* m, const void* ptr, int cols, int rows, int box_slabs, bool tokens) {
  const cuuint64_t rb = (cuuint64_t)cols * 2;
  const cuuint64_t dims[4] = {(cuuint64_t)cols, 16, 2, (cuuint64_t)(rows / 32)};
  const cuuint64_t st[3] = {tokens ? 2 * rb : rb, tokens ? rb : 16 * rb, 32 * rb};
  const cuuint32_t box[4] = {64, 16, 2, (cuuint32_t)box_slabs};
  make_map(fn, m, ptr, 4, dims, st, box);
}
void map_w(EncodeFn fn, CUtensorMap* m, const void* ptr, int K, int N, int inner, int nch, int rows = 64) {
  const cuuint64_t dims[3] = {(cuuint64_t)inner, (cuuint64_t)K, (cuuint64_t)(N / inner)}, st[2] = {(cuuint64_t)N * 2, (cuuint64_t)inner * 2};
  const cuuint32_t box[3] = {64, (cuuint32_t)rows, (cuuint32_t)nch};
  make_map(fn, m, ptr, 3, dims, st, box);
}

}

extern "C" void kernel_launch(void* const* d_in, const int* in_sizes, int n_in, void* d_out, int out_size) {
  (void)in_sizes; (void)n_in; (void)out_size;
  Params p;
  p.b1 = (const __nv_bfloat16*)d_in[5]; p.b2 = (const __nv_bfloat16*)d_in[7];
  void* fnp = nullptr; cudaDriverEntryPointQueryResult qr;
  cudaGetDriverEntryPoint("cuTensorMapEncodeTiled", &fnp, cudaEnableDefault, &qr);
  EncodeFn fn = (EncodeFn)fnp;
  void *h, *epochs;
  cudaGetSymbolAddress(&h, g_h);
  cudaGetSymbolAddress(&epochs, g_epoch);
  map_rows(fn, &p.ld_x, d_in[0], D_, S_, 2, true);
  map_rows(fn, &p.ld_out, d_out, D_, S_, 2, true);
  map_rows(fn, &p.ld_h, h, F_, S_, 2, false);
  map_rows(fn, &p.st_h, h, F_, S_, 4, false);
  map_rows(fn, &p.st_out, d_out, D_, S_, 4, true);
  map_w(fn, &p.w_qkv, d_in[1], D_, 3 * D_, D_, 3);
  map_w(fn, &p.w_o, d_in[2], D_, D_, 64, 2);
  map_w(fn, &p.w_1a, d_in[4], D_, F_, 64, 3);
  map_w(fn, &p.w_1b, d_in[4], D_, F_, 64, 2);
  map_w(fn, &p.w_2, d_in[6], F_, D_, 64, 2);
  map_w(fn, &p.s_qkv, d_in[1], D_, 3 * D_, 64, 1, 128);
  map_w(fn, &p.s_1, d_in[4], D_, F_, 64, 1, 128);
  cudaFuncSetAttribute(fused_kernel, cudaFuncAttributeMaxDynamicSharedMemorySize, SMEM_BYTES);
  fused_kernel<<<132, 384, SMEM_BYTES>>>((unsigned*)epochs, p);
}
```

```cpp
#include <cuda_runtime.h>
#include <cuda_bf16.h>
#include <cuda.h>
#include <stdint.h>

#define EXP 0
namespace {

constexpr int S_ = 2048, D_ = 1024, F_ = 3584;
constexpr int A_BYTES = 16384;
constexpr int OFF_X   = 163840;
constexpr int OFF_STG = OFF_X + 32768;
constexpr int OFF_CSQ = OFF_STG + 20480;
constexpr int OFF_UP  = OFF_CSQ + 1536;
constexpr int OFF_B2  = OFF_UP + 3584;
constexpr int OFF_RST = OFF_B2 + 512 + 256;
constexpr int OFF_FULL = OFF_RST + 1024;
constexpr int OFF_EMPTY = OFF_FULL + 64;
constexpr int OFF_XBAR = OFF_EMPTY + 64;
constexpr int OFF_TBL = OFF_XBAR + 8;
constexpr int OFF_HALO = OFF_XBAR + 32;
constexpr int OFF_SLOT = OFF_XBAR + 40;
constexpr int OFF_ZERO = OFF_XBAR + 48;
constexpr int OFF_TAG = OFF_ZERO + 16;
constexpr int SMEM_BYTES = OFF_TAG + 16 + 1024;
constexpr int KB_LAYER = 6 * 16 + 56;
constexpr int NCS = 384 + 448;
constexpr unsigned SPIN_LIMIT = 1u << 20;
constexpr int PAUSE1 = 6, PAUSE2 = PAUSE1 + 2, EARLY = 0, HGO = 11;
constexpr uint32_t DESC_A = 1u << 16, DESC_B = (512u << 16) + A_BYTES / 16;
enum { BAR_START = 1, BAR_EPI = 3, BAR_WG = 5, BAR_P0 = 7, BAR_P1 = 8, BAR_RES = 9, BAR_READY = 10, BAR_FREE = 11, BAR_COPY = 12, BAR_HGO = 13 };

struct Params {
  CUtensorMap ld_x, ld_out, ld_h, st_h, st_out, w_qkv, w_o, w_1a, w_1b, w_2;
  const __nv_bfloat16 *b1, *b2;
};

__device__ __align__(1024) __nv_bfloat16 g_h[S_ * F_];
__device__ __align__(128) uint4 g_stats[4 * S_ * 8];
__device__ __align__(128) uint2 g_cs[8 * NCS];
__device__ __align__(128) uint4 g_halo[4 * 128 * 11 * 32];
__device__ __align__(128) unsigned g_flags[14 * 16 * 32];
__device__ unsigned g_epoch[132 + 64];
#define TL(t, e)
#define PTL(t, e)
#if !defined(TIMELINE) || !(EXP & 8)
#undef TK
#define TK(t, k)
#endif

template<int N, int KEEP> __device__ __forceinline__ void wgmma_ss(float (&d)[96], uint32_t da, uint32_t db);
template<> __device__ __forceinline__ void wgmma_ss<128, 0>(float (&d)[96], uint32_t da, uint32_t db) {
  asm volatile("{\n.reg .pred p;\n.reg .b64 a, b;\nsetp.ne.b32 p, 0, 0;\nmov.b64 a, {%64, 0x40000080};\nmov.b64 b, {%65, 0x40000040};\nwgmma.mma_async.sync.aligned.m64n128k16.f32.bf16.bf16 {%0, %1, %2, %3, %4, %5, %6, %7, %8, %9, %10, %11, %12, %13, %14, %15, %16, %17, %18, %19, %20, %21, %22, %23, %24, %25, %26, %27, %28, %29, %30, %31, %32, %33, %34, %35, %36, %37, %38, %39, %40, %41, %42, %43, %44, %45, %46, %47, %48, %49, %50, %51, %52, %53, %54, %55, %56, %57, %58, %59, %60, %61, %62, %63}, a, b, p, 1, 1, 0, 1;\n}"
    : "=f"(d[0]), "=f"(d[1]), "=f"(d[2]), "=f"(d[3]), "=f"(d[4]), "=f"(d[5]), "=f"(d[6]), "=f"(d[7]), "=f"(d[8]), "=f"(d[9]), "=f"(d[10]), "=f"(d[11]), "=f"(d[12]), "=f"(d[13]), "=f"(d[14]), "=f"(d[15]), "=f"(d[16]), "=f"(d[17]), "=f"(d[18]), "=f"(d[19]), "=f"(d[20]), "=f"(d[21]), "=f"(d[22]), "=f"(d[23]), "=f"(d[24]), "=f"(d[25]), "=f"(d[26]), "=f"(d[27]), "=f"(d[28]), "=f"(d[29]), "=f"(d[30]), "=f"(d[31]), "=f"(d[32]), "=f"(d[33]), "=f"(d[34]), "=f"(d[35]), "=f"(d[36]), "=f"(d[37]), "=f"(d[38]), "=f"(d[39]), "=f"(d[40]), "=f"(d[41]), "=f"(d[42]), "=f"(d[43]), "=f"(d[44]), "=f"(d[45]), "=f"(d[46]), "=f"(d[47]), "=f"(d[48]), "=f"(d[49]), "=f"(d[50]), "=f"(d[51]), "=f"(d[52]), "=f"(d[53]), "=f"(d[54]), "=f"(d[55]), "=f"(d[56]), "=f"(d[57]), "=f"(d[58]), "=f"(d[59]), "=f"(d[60]), "=f"(d[61]), "=f"(d[62]), "=f"(d[63])
    : "r"(da), "r"(db));
}
template<> __device__ __forceinline__ void wgmma_ss<128, 1>(float (&d)[96], uint32_t da, uint32_t db) {
  asm volatile("{\n.reg .pred p;\n.reg .b64 a, b;\nsetp.ne.b32 p, 1, 0;\nmov.b64 a, {%64, 0x40000080};\nmov.b64 b, {%65, 0x40000040};\nwgmma.mma_async.sync.aligned.m64n128k16.f32.bf16.bf16 {%0, %1, %2, %3, %4, %5, %6, %7, %8, %9, %10, %11, %12, %13, %14, %15, %16, %17, %18, %19, %20, %21, %22, %23, %24, %25, %26, %27, %28, %29, %30, %31, %32, %33, %34, %35, %36, %37, %38, %39, %40, %41, %42, %43, %44, %45, %46, %47, %48, %49, %50, %51, %52, %53, %54, %55, %56, %57, %58, %59, %60, %61, %62, %63}, a, b, p, 1, 1, 0, 1;\n}"
    : "+f"(d[0]), "+f"(d[1]), "+f"(d[2]), "+f"(d[3]), "+f"(d[4]), "+f"(d[5]), "+f"(d[6]), "+f"(d[7]), "+f"(d[8]), "+f"(d[9]), "+f"(d[10]), "+f"(d[11]), "+f"(d[12]), "+f"(d[13]), "+f"(d[14]), "+f"(d[15]), "+f"(d[16]), "+f"(d[17]), "+f"(d[18]), "+f"(d[19]), "+f"(d[20]), "+f"(d[21]), "+f"(d[22]), "+f"(d[23]), "+f"(d[24]), "+f"(d[25]), "+f"(d[26]), "+f"(d[27]), "+f"(d[28]), "+f"(d[29]), "+f"(d[30]), "+f"(d[31]), "+f"(d[32]), "+f"(d[33]), "+f"(d[34]), "+f"(d[35]), "+f"(d[36]), "+f"(d[37]), "+f"(d[38]), "+f"(d[39]), "+f"(d[40]), "+f"(d[41]), "+f"(d[42]), "+f"(d[43]), "+f"(d[44]), "+f"(d[45]), "+f"(d[46]), "+f"(d[47]), "+f"(d[48]), "+f"(d[49]), "+f"(d[50]), "+f"(d[51]), "+f"(d[52]), "+f"(d[53]), "+f"(d[54]), "+f"(d[55]), "+f"(d[56]), "+f"(d[57]), "+f"(d[58]), "+f"(d[59]), "+f"(d[60]), "+f"(d[61]), "+f"(d[62]), "+f"(d[63])
    : "r"(da), "r"(db));
}
template<> __device__ __forceinline__ void wgmma_ss<192, 0>(float (&d)[96], uint32_t da, uint32_t db) {
  asm volatile("{\n.reg .pred p;\n.reg .b64 a, b;\nsetp.ne.b32 p, 0, 0;\nmov.b64 a, {%96, 0x40000080};\nmov.b64 b, {%97, 0x40000040};\nwgmma.mma_async.sync.aligned.m64n192k16.f32.bf16.bf16 {%0, %1, %2, %3, %4, %5, %6, %7, %8, %9, %10, %11, %12, %13, %14, %15, %16, %17, %18, %19, %20, %21, %22, %23, %24, %25, %26, %27, %28, %29, %30, %31, %32, %33, %34, %35, %36, %37, %38, %39, %40, %41, %42, %43, %44, %45, %46, %47, %48, %49, %50, %51, %52, %53, %54, %55, %56, %57, %58, %59, %60, %61, %62, %63, %64, %65, %66, %67, %68, %69, %70, %71, %72, %73, %74, %75, %76, %77, %78, %79, %80, %81, %82, %83, %84, %85, %86, %87, %88, %89, %90, %91, %92, %93, %94, %95}, a, b, p, 1, 1, 0, 1;\n}"
    : "=f"(d[0]), "=f"(d[1]), "=f"(d[2]), "=f"(d[3]), "=f"(d[4]), "=f"(d[5]), "=f"(d[6]), "=f"(d[7]), "=f"(d[8]), "=f"(d[9]), "=f"(d[10]), "=f"(d[11]), "=f"(d[12]), "=f"(d[13]), "=f"(d[14]), "=f"(d[15]), "=f"(d[16]), "=f"(d[17]), "=f"(d[18]), "=f"(d[19]), "=f"(d[20]), "=f"(d[21]), "=f"(d[22]), "=f"(d[23]), "=f"(d[24]), "=f"(d[25]), "=f"(d[26]), "=f"(d[27]), "=f"(d[28]), "=f"(d[29]), "=f"(d[30]), "=f"(d[31]), "=f"(d[32]), "=f"(d[33]), "=f"(d[34]), "=f"(d[35]), "=f"(d[36]), "=f"(d[37]), "=f"(d[38]), "=f"(d[39]), "=f"(d[40]), "=f"(d[41]), "=f"(d[42]), "=f"(d[43]), "=f"(d[44]), "=f"(d[45]), "=f"(d[46]), "=f"(d[47]), "=f"(d[48]), "=f"(d[49]), "=f"(d[50]), "=f"(d[51]), "=f"(d[52]), "=f"(d[53]), "=f"(d[54]), "=f"(d[55]), "=f"(d[56]), "=f"(d[57]), "=f"(d[58]), "=f"(d[59]), "=f"(d[60]), "=f"(d[61]), "=f"(d[62]), "=f"(d[63]), "=f"(d[64]), "=f"(d[65]), "=f"(d[66]), "=f"(d[67]), "=f"(d[68]), "=f"(d[69]), "=f"(d[70]), "=f"(d[71]), "=f"(d[72]), "=f"(d[73]), "=f"(d[74]), "=f"(d[75]), "=f"(d[76]), "=f"(d[77]), "=f"(d[78]), "=f"(d[79]), "=f"(d[80]), "=f"(d[81]), "=f"(d[82]), "=f"(d[83]), "=f"(d[84]), "=f"(d[85]), "=f"(d[86]), "=f"(d[87]), "=f"(d[88]), "=f"(d[89]), "=f"(d[90]), "=f"(d[91]), "=f"(d[92]), "=f"(d[93]), "=f"(d[94]), "=f"(d[95])
    : "r"(da), "r"(db));
}
template<> __device__ __forceinline__ void wgmma_ss<192, 1>(float (&d)[96], uint32_t da, uint32_t db) {
  asm volatile("{\n.reg .pred p;\n.reg .b64 a, b;\nsetp.ne.b32 p, 1, 0;\nmov.b64 a, {%96, 0x40000080};\nmov.b64 b, {%97, 0x40000040};\nwgmma.mma_async.sync.aligned.m64n192k16.f32.bf16.bf16 {%0, %1, %2, %3, %4, %5, %6, %7, %8, %9, %10, %11, %12, %13, %14, %15, %16, %17, %18, %19, %20, %21, %22, %23, %24, %25, %26, %27, %28, %29, %30, %31, %32, %33, %34, %35, %36, %37, %38, %39, %40, %41, %42, %43, %44, %45, %46, %47, %48, %49, %50, %51, %52, %53, %54, %55, %56, %57, %58, %59, %60, %61, %62, %63, %64, %65, %66, %67, %68, %69, %70, %71, %72, %73, %74, %75, %76, %77, %78, %79, %80, %81, %82, %83, %84, %85, %86, %87, %88, %89, %90, %91, %92, %93, %94, %95}, a, b, p, 1, 1, 0, 1;\n}"
    : "+f"(d[0]), "+f"(d[1]), "+f"(d[2]), "+f"(d[3]), "+f"(d[4]), "+f"(d[5]), "+f"(d[6]), "+f"(d[7]), "+f"(d[8]), "+f"(d[9]), "+f"(d[10]), "+f"(d[11]), "+f"(d[12]), "+f"(d[13]), "+f"(d[14]), "+f"(d[15]), "+f"(d[16]), "+f"(d[17]), "+f"(d[18]), "+f"(d[19]), "+f"(d[20]), "+f"(d[21]), "+f"(d[22]), "+f"(d[23]), "+f"(d[24]), "+f"(d[25]), "+f"(d[26]), "+f"(d[27]), "+f"(d[28]), "+f"(d[29]), "+f"(d[30]), "+f"(d[31]), "+f"(d[32]), "+f"(d[33]), "+f"(d[34]), "+f"(d[35]), "+f"(d[36]), "+f"(d[37]), "+f"(d[38]), "+f"(d[39]), "+f"(d[40]), "+f"(d[41]), "+f"(d[42]), "+f"(d[43]), "+f"(d[44]), "+f"(d[45]), "+f"(d[46]), "+f"(d[47]), "+f"(d[48]), "+f"(d[49]), "+f"(d[50]), "+f"(d[51]), "+f"(d[52]), "+f"(d[53]), "+f"(d[54]), "+f"(d[55]), "+f"(d[56]), "+f"(d[57]), "+f"(d[58]), "+f"(d[59]), "+f"(d[60]), "+f"(d[61]), "+f"(d[62]), "+f"(d[63]), "+f"(d[64]), "+f"(d[65]), "+f"(d[66]), "+f"(d[67]), "+f"(d[68]), "+f"(d[69]), "+f"(d[70]), "+f"(d[71]), "+f"(d[72]), "+f"(d[73]), "+f"(d[74]), "+f"(d[75]), "+f"(d[76]), "+f"(d[77]), "+f"(d[78]), "+f"(d[79]), "+f"(d[80]), "+f"(d[81]), "+f"(d[82]), "+f"(d[83]), "+f"(d[84]), "+f"(d[85]), "+f"(d[86]), "+f"(d[87]), "+f"(d[88]), "+f"(d[89]), "+f"(d[90]), "+f"(d[91]), "+f"(d[92]), "+f"(d[93]), "+f"(d[94]), "+f"(d[95])
    : "r"(da), "r"(db));
}

__device__ __forceinline__ uint32_t smem_u32(const void* p) { return (uint32_t)__cvta_generic_to_shared(p); }
__device__ __forceinline__ void mbar_arrive_cluster(uint32_t bar) { asm volatile("mbarrier.arrive.shared::cluster.b64 _, [%0];" :: "r"(bar) : "memory"); }
__device__ __forceinline__ void mbar_wait(uint32_t bar, uint32_t parity) {
  asm volatile(
    "{\n.reg .pred p;\n.reg .u32 n;\n"
    "mbarrier.try_wait.parity.shared::cta.b64 p, [%0], %1;\n"
    "@p bra.uni WAIT_DONE;\n"
    "mov.u32 n, 0;\n"
    "WAIT_LOOP:\n"
    "mbarrier.try_wait.parity.shared::cta.b64 p, [%0], %1;\n"
    "@p bra.uni WAIT_DONE;\n"
    "add.u32 n, n, 1;\n"
    "setp.lt.u32 p, n, 0x100000;\n"
    "@p bra.uni WAIT_LOOP;\n"
    "trap;\n"
    "WAIT_DONE:\n}" :: "r"(bar), "r"(parity) : "memory");
}
#define ELECT "{\n.reg .pred p;\nelect.sync _|p, 0xffffffff;\n"
__device__ __forceinline__ void mbar_init_e(uint32_t bar, uint32_t cnt) { asm volatile(ELECT "@p mbarrier.init.shared::cta.b64 [%0], %1;\n}" :: "r"(bar), "r"(cnt) : "memory"); }
__device__ __forceinline__ void mbar_arrive_e(uint32_t bar) { asm volatile(ELECT "@p mbarrier.arrive.shared::cta.b64 _, [%0];\n}" :: "r"(bar) : "memory"); }
__device__ __forceinline__ void mbar_expect_e(uint32_t bar, uint32_t bytes) { asm volatile(ELECT "@p mbarrier.arrive.expect_tx.shared::cta.b64 _, [%0], %1;\n}" :: "r"(bar), "r"(bytes) : "memory"); }
__device__ __forceinline__ void tma_ld4_e(uint32_t dst, const CUtensorMap* m, uint32_t bar, int c0, int c3) {
  asm volatile(ELECT "@p cp.async.bulk.tensor.4d.shared::cluster.global.mbarrier::complete_tx::bytes [%0], [%1, {%3, %5, %5, %4}], [%2];\n}"
    :: "r"(dst), "l"(m), "r"(bar), "r"(c0), "r"(c3), "r"(0) : "memory");
}
__device__ __forceinline__ void tma_ld4_mc_e(uint32_t dst, const CUtensorMap* m, uint32_t bar, int c0, int c3) {
  asm volatile(ELECT "@p cp.async.bulk.tensor.4d.shared::cluster.global.mbarrier::complete_tx::bytes.multicast::cluster [%0], [%1, {%3, %5, %5, %4}], [%2], %6;\n}"
    :: "r"(dst), "l"(m), "r"(bar), "r"(c0), "r"(c3), "r"(0), "h"((uint16_t)3) : "memory");
}
__device__ __forceinline__ void tma_ld3_e(uint32_t dst, const CUtensorMap* m, uint32_t bar, int c0, int c1, int c2) {
  asm volatile(ELECT "@p cp.async.bulk.tensor.3d.shared::cluster.global.mbarrier::complete_tx::bytes [%0], [%1, {%3, %4, %5}], [%2];\n}"
    :: "r"(dst), "l"(m), "r"(bar), "r"(c0), "r"(c1), "r"(c2) : "memory");
}
__device__ __forceinline__ void tma_pf3_e(const CUtensorMap* m, int c0, int c1, int c2) {
  asm volatile(ELECT "@p cp.async.bulk.prefetch.tensor.3d.L2.global [%0, {%1, %2, %3}];\n}" :: "l"(m), "r"(c0), "r"(c1), "r"(c2) : "memory");
}
__device__ __forceinline__ void tma_st4_e(const CUtensorMap* m, uint32_t src, int c0, int c3) {
  asm volatile(ELECT "@p cp.async.bulk.tensor.4d.global.shared::cta.bulk_group [%0, {%2, %4, %4, %3}], [%1];\n}"
    :: "l"(m), "r"(src), "r"(c0), "r"(c3), "r"(0) : "memory");
}
__device__ __forceinline__ void dsmem_copy_e(uint32_t dst, uint32_t src, uint32_t bar) {
  asm volatile(ELECT "@p cp.async.bulk.shared::cluster.shared::cta.mbarrier::complete_tx::bytes [%0], [%1], 16384, [%2];\n}"
    :: "r"(dst), "r"(src), "r"(bar) : "memory");
}
__device__ __forceinline__ void bulk_wait_read_e() { asm volatile(ELECT "@p cp.async.bulk.commit_group;\n@p cp.async.bulk.wait_group.read 0;\n}" ::: "memory"); __syncwarp(); }
__device__ __forceinline__ void publish_e(unsigned* flag, unsigned tag) {
  asm volatile(ELECT "@p fence.proxy.async;\n@p st.relaxed.gpu.global.u32 [%0], %1;\n}" :: "l"(flag), "r"(tag) : "memory");
  __syncwarp();
}
__device__ __forceinline__ void fence_async_smem() { asm volatile("fence.proxy.async.shared::cta;" ::: "memory"); }
__device__ __forceinline__ void wgmma_fence() { asm volatile("wgmma.fence.sync.aligned;" ::: "memory"); }
__device__ __forceinline__ void wgmma_commit() { asm volatile("wgmma.commit_group.sync.aligned;" ::: "memory"); }
template<int N> __device__ __forceinline__ void wgmma_wait() { asm volatile("wgmma.wait_group.sync.aligned %0;" :: "n"(N) : "memory"); }
__device__ __forceinline__ void bar_sync(int id, int n) { asm volatile("bar.sync %0, %1;" :: "r"(id), "r"(n) : "memory"); }
__device__ __forceinline__ void bar_arrive(int id, int n) { asm volatile("bar.arrive %0, %1;" :: "r"(id), "r"(n) : "memory"); }
__device__ __forceinline__ void bar_arrive_after(int id, uint32_t dep) {
  asm volatile("{\n.reg .u32 n;\nor.b32 n, %1, 256;\nmin.u32 n, n, 256;\nbar.arrive %0, n;\n}" :: "r"(id), "r"(dep) : "memory");
}
__device__ __forceinline__ void bar_sync_after(int id, uint32_t dep) {
  asm volatile("{\n.reg .u32 n;\nor.b32 n, %1, 256;\nmin.u32 n, n, 256;\nbar.sync %0, n;\n}" :: "r"(id), "r"(dep) : "memory");
}
__device__ __forceinline__ uint32_t mapa(uint32_t a, uint32_t r) { uint32_t d; asm("mapa.shared::cluster.u32 %0, %1, %2;" : "=r"(d) : "r"(a), "r"(r)); return d; }
__device__ __forceinline__ void st_tag128(uint4* p, uint32_t a, uint32_t b, uint32_t c, uint32_t tag) {
  asm volatile("{\n.reg .b64 lo, hi;\n.reg .b128 v;\nmov.b64 lo, {%1, %2};\nmov.b64 hi, {%3, %4};\nmov.b128 v, {lo, hi};\nst.relaxed.gpu.global.b128 [%0], v;\n}"
    :: "l"(p), "r"(a), "r"(b), "r"(c), "r"(tag) : "memory");
}
__device__ __forceinline__ void st_tag128_if(bool on, uint4* p, uint32_t a, uint32_t b, uint32_t c, uint32_t tag) {
  asm volatile("{\n.reg .pred q;\n.reg .b64 lo, hi;\n.reg .b128 v;\nsetp.ne.u32 q, %5, 0;\nmov.b64 lo, {%1, %2};\nmov.b64 hi, {%3, %4};\nmov.b128 v, {lo, hi};\n@q st.relaxed.gpu.global.b128 [%0], v;\n}"
    :: "l"(p), "r"(a), "r"(b), "r"(c), "r"(tag), "r"((uint32_t)on) : "memory");
}
__device__ __forceinline__ uint4 ld_tag128(const uint4* p) {
  uint4 v;
  asm volatile("{\n.reg .b64 lo, hi;\n.reg .b128 v;\nld.relaxed.gpu.global.b128 v, [%4];\nmov.b128 {lo, hi}, v;\nmov.b64 {%0, %1}, lo;\nmov.b64 {%2, %3}, hi;\n}"
    : "=r"(v.x), "=r"(v.y), "=r"(v.z), "=r"(v.w) : "l"(p) : "memory");
  return v;
}
__device__ __forceinline__ void st_tag64(uint2* p, float a, uint32_t tag) {
  asm volatile("{\n.reg .b64 v;\nmov.b64 v, {%1, %2};\nst.relaxed.gpu.global.b64 [%0], v;\n}" :: "l"(p), "r"(__float_as_uint(a)), "r"(tag) : "memory");
}
__device__ __forceinline__ uint2 ld_tag64(const uint2* p) {
  uint2 v;
  asm volatile("{\n.reg .b64 v;\nld.relaxed.gpu.global.b64 v, [%2];\nmov.b64 {%0, %1}, v;\n}" : "=r"(v.x), "=r"(v.y) : "l"(p) : "memory");
  return v;
}
__device__ __forceinline__ uint32_t pack_bf16(float lo, float hi) { uint32_t r; asm("cvt.rn.bf16x2.f32 %0, %1, %2;" : "=r"(r) : "f"(hi), "f"(lo)); return r; }
__device__ __forceinline__ uint32_t relu_sq_bf16(float lo, float hi) {
  uint32_t r; asm("{\n.reg .b32 t;\ncvt.rn.relu.bf16x2.f32 t, %1, %2;\nmul.rn.bf16x2 %0, t, t;\n}" : "=r"(r) : "f"(hi), "f"(lo)); return r;
}
__device__ __forceinline__ float bf_lo(uint32_t u) { return __uint_as_float(u << 16); }
__device__ __forceinline__ float bf_hi(uint32_t u) { return __uint_as_float(u & 0xffff0000u); }
__device__ __forceinline__ void stmatrix4(uint32_t addr, uint32_t r0, uint32_t r1, uint32_t r2, uint32_t r3) {
  asm volatile("stmatrix.sync.aligned.m8n8.x4.shared.b16 [%0], {%1, %2, %3, %4};" :: "r"(addr), "r"(r0), "r"(r1), "r"(r2), "r"(r3) : "memory");
}
__device__ __forceinline__ void ldmatrix4(uint32_t addr, uint32_t (&r)[4]) {
  asm volatile("ldmatrix.sync.aligned.m8n8.x4.shared.b16 {%0, %1, %2, %3}, [%4];" : "=r"(r[0]), "=r"(r[1]), "=r"(r[2]), "=r"(r[3]) : "r"(addr) : "memory");
}
__device__ __forceinline__ void stmatrix4_t(uint32_t addr, uint32_t r0, uint32_t r1, uint32_t r2, uint32_t r3) {
  asm volatile("stmatrix.sync.aligned.m8n8.x4.trans.shared.b16 [%0], {%1, %2, %3, %4};" :: "r"(addr), "r"(r0), "r"(r1), "r"(r2), "r"(r3) : "memory");
}
__device__ __forceinline__ void ldmatrix4_t(uint32_t addr, uint32_t (&r)[4]) {
  asm volatile("ldmatrix.sync.aligned.m8n8.x4.trans.shared.b16 {%0, %1, %2, %3}, [%4];" : "=r"(r[0]), "=r"(r[1]), "=r"(r[2]), "=r"(r[3]) : "r"(addr) : "memory");
}
__device__ __forceinline__ uint32_t movmatrix(uint32_t a) { uint32_t d; asm volatile("movmatrix.sync.aligned.m8n8.trans.b16 %0, %1;" : "=r"(d) : "r"(a)); return d; }
__device__ __forceinline__ void mma16816_z(float (&c)[4], uint32_t a0, uint32_t a1, uint32_t a2, uint32_t a3, uint32_t b0, uint32_t b1, const float4& z) {
  asm volatile("mma.sync.aligned.m16n8k16.row.col.f32.bf16.bf16.f32 {%0,%1,%2,%3}, {%4,%5,%6,%7}, {%8,%9}, {%10,%11,%12,%13};"
    : "=f"(c[0]), "=f"(c[1]), "=f"(c[2]), "=f"(c[3]) : "r"(a0), "r"(a1), "r"(a2), "r"(a3), "r"(b0), "r"(b1), "f"(z.x), "f"(z.y), "f"(z.z), "f"(z.w));
}
__device__ __forceinline__ float ex2(float x) { float y; asm("ex2.approx.ftz.f32 %0, %1;" : "=f"(y) : "f"(x)); return y; }
__device__ __forceinline__ float rcp(float x) { float y; asm("rcp.approx.ftz.f32 %0, %1;" : "=f"(y) : "f"(x)); return y; }
__device__ __forceinline__ void mma16816(float (&c)[4], uint32_t a0, uint32_t a1, uint32_t a2, uint32_t a3, uint32_t b0, uint32_t b1) {
  asm volatile("mma.sync.aligned.m16n8k16.row.col.f32.bf16.bf16.f32 {%0,%1,%2,%3}, {%4,%5,%6,%7}, {%8,%9}, {%0,%1,%2,%3};"
    : "+f"(c[0]), "+f"(c[1]), "+f"(c[2]), "+f"(c[3]) : "r"(a0), "r"(a1), "r"(a2), "r"(a3), "r"(b0), "r"(b1));
}
__device__ __forceinline__ void sts128(uint32_t a, uint32_t x, uint32_t y, uint32_t z, uint32_t w) { asm volatile("st.shared.v4.b32 [%0], {%1,%2,%3,%4};" :: "r"(a), "r"(x), "r"(y), "r"(z), "r"(w) : "memory"); }
__device__ __forceinline__ float2 lds64f(uint32_t a) { float2 v; asm volatile("ld.shared.v2.f32 {%0,%1}, [%2];" : "=f"(v.x), "=f"(v.y) : "r"(a) : "memory"); return v; }
__device__ __forceinline__ float4 lds128f(uint32_t a) { float4 v; asm volatile("ld.shared.v4.f32 {%0,%1,%2,%3}, [%4];" : "=f"(v.x), "=f"(v.y), "=f"(v.z), "=f"(v.w) : "r"(a) : "memory"); return v; }
__device__ __forceinline__ void sts32f(uint32_t a, float v) { asm volatile("st.shared.f32 [%0], %1;" :: "r"(a), "f"(v) : "memory"); }
__device__ __forceinline__ void sts64f(uint32_t a, float x, float y) { asm volatile("st.shared.v2.f32 [%0], {%1,%2};" :: "r"(a), "f"(x), "f"(y) : "memory"); }
__device__ __forceinline__ uint32_t lds32(uint32_t a) { uint32_t v; asm volatile("ld.shared.u32 %0, [%1];" : "=r"(v) : "r"(a) : "memory"); return v; }
__device__ __forceinline__ float after(float x, uint32_t d, uint32_t zero) { return __uint_as_float(__float_as_uint(x) | (d & zero)); }
template<int R> __device__ __forceinline__ void reg_alloc() { asm volatile("setmaxnreg.inc.sync.aligned.u32 %0;" :: "n"(R)); }
template<int R> __device__ __forceinline__ void reg_dealloc() { asm volatile("setmaxnreg.dec.sync.aligned.u32 %0;" :: "n"(R)); }

struct Ctx {
  uint32_t sb;
  int m, j, b, rank, wg, w, lane;
};

__device__ __forceinline__ unsigned smem_tag(const Ctx& c) { return lds32(c.sb + OFF_TAG); }

__device__ __forceinline__ int own_kb(const Ctx& c, int step) {
  return step < 4 ? (c.j * 2) ^ step : (((c.j >> 1) * 4 + 2 * step + (step < 10 ? 12 : 0)) & 15) + (step >= 10);
}
__device__ __forceinline__ int kb_order(const Ctx& c, int t, int type, int step) {
  return type == 3 || t == 7 ? own_kb(c, step) : type != 2 || step < 8 ? step : step < 10 ? c.j ^ step : 8 + (((c.j & 6) + step) & 7);
}
struct WTile { const CUtensorMap* mp; int c0, c2; };
__device__ __forceinline__ WTile wtile(const Params& p, int type, int j) {
  WTile w;
  w.mp = type < 2 ? &p.w_qkv : type == 2 ? &p.w_o : type == 3 ? &p.w_1a : type < 6 ? &p.w_1b : &p.w_2;
  w.c0 = type < 2 ? (j + 8 * type) * 64 : 0;
  w.c2 = type < 2 ? 0 : type == 3 ? 3 * j : type == 4 ? 24 + 2 * j : type == 5 ? 40 + 2 * j : 2 * j;
  return w;
}
__device__ __forceinline__ int first_stage(int type) { return (0x2100433 >> (4 * type)) & 7; }

template<int BN, int RES>
__device__ __forceinline__ void mainloop(const Ctx& c, float (&acc)[2][96], int t, int type, int g, int nkb) {
  constexpr int NS = BN == 192 ? 4 : 5, STR = BN == 192 ? 40960 : 32768;
  constexpr int HL = 2;
  int st = first_stage(type);
  const bool own = BN == 192 && (type == 3 || t == 7);
  const uint32_t rel = mapa(c.sb + OFF_EMPTY, c.lane & 1);
  const uint32_t sb = (c.sb & 0x3ffffu) >> 4;
  uint32_t da = DESC_A + (own ? sb + OFF_X / 16 : sb + st * (STR / 16)), db = DESC_B + sb + st * (STR / 16);
  TL(t, 0);
  if (t > 0) bar_sync(BAR_START + c.wg, 256);
  if (RES && type == 2 && EARLY == 0) bar_sync(BAR_P1, 256);
  TL(t, 1);
  mbar_wait(c.sb + OFF_FULL + 8 * (g & 7), (g >> 3) & 1);
  TL(t, 2);
  wgmma_fence();
  wgmma_ss<BN, RES>(acc[0], da, db);
  wgmma_ss<BN, RES>(acc[1], da + 64, db);
  if (HL == 2) { wgmma_ss<BN, 1>(acc[0], da + 2, db + 128); wgmma_ss<BN, 1>(acc[1], da + 66, db + 128); }
  wgmma_commit();
#pragma unroll 1
  for (int kb = 1;; kb++) {
    wgmma_fence();
#pragma unroll
    for (int k = HL; k < 4; k++) {
      if (k == (BN == 128 ? 2 : 3) && kb == nkb && t < 13 && type != 1) bar_arrive(BAR_START + (c.wg ^ 1), 256);
      wgmma_ss<BN, 1>(acc[0], da + k * 2, db + k * 128);
      wgmma_ss<BN, 1>(acc[1], da + (64 + k * 2), db + k * 128);
    }
    wgmma_commit();
    if (kb == nkb) break;
    if (BN == 192 && type == 1 && (kb == PAUSE1 || kb == PAUSE2)) { bar_sync(BAR_P0, 256); bar_sync(BAR_P1, 256); }
    if (RES && type == 2 && kb == EARLY) bar_sync(BAR_P1, 256);
    if (++st == NS) st = 0;
    g++;
    da = DESC_A + sb + (own && kb == 1 ? (OFF_X + A_BYTES) / 16 : RES && type == 2 && kb == 8 ? OFF_STG / 16 : st * (STR / 16)); db = DESC_B + sb + st * (STR / 16);
    mbar_wait(c.sb + OFF_FULL + 8 * (g & 7), (g >> 3) & 1);
    wgmma_fence();
    wgmma_ss<BN, 1>(acc[0], da, db);
    wgmma_ss<BN, 1>(acc[1], da + 64, db);
    if (HL == 2) { wgmma_ss<BN, 1>(acc[0], da + 2, db + 128); wgmma_ss<BN, 1>(acc[1], da + 66, db + 128); }
    wgmma_commit();
    wgmma_wait<1>();
    if (c.lane < 2) mbar_arrive_cluster(rel + 8 * ((g - 1) & 7));
    TK(t, kb);
  }
}
__device__ __forceinline__ void release(const Ctx& c, int slot, int lanes = 2) {
  if (c.lane < lanes) mbar_arrive_cluster(mapa(c.sb + OFF_EMPTY, c.lane & 1) + 8 * slot);
}
__device__ __forceinline__ void finish(const Ctx& c, int t) {
  wgmma_wait<0>();
  release(c, 7);
  TL(t, 3);
}

__device__ __forceinline__ void load_row_stats(const Ctx& c, int ln) {
  const uint4* p = g_stats + (ln * 128 + c.m * 8) * 128 + c.w * 32 + c.lane;
  const unsigned tag = smem_tag(c);
  float s, q;
  for (unsigned it = 0;; it++) {
    uint4 v[8];
#pragma unroll
    for (int i = 0; i < 8; i++) v[i] = ld_tag128(p + i * 128);
    bool ok = true;
    s = 0.f; q = 0.f;
#pragma unroll
    for (int i = 0; i < 8; i++) { ok = ok && v[i].w == tag; s += __uint_as_float(v[i].x); q += __uint_as_float(v[i].y); }
    if (__all_sync(0xffffffffu, ok) || it > SPIN_LIMIT) break;
    __nanosleep(400);
  }
  const float mean = s * (1.0f / D_);
  const float var = fmaxf(q * (1.0f / D_) - mean * mean, 0.0f);
  sts64f(c.sb + OFF_RST + (c.w * 32 + c.lane) * 8, rsqrtf(var + 1e-5f), -mean);
  __syncwarp();
}

__device__ __forceinline__ void put_halo(uint32_t addr, int z, uint32_t a, uint32_t b, uint32_t c, uint32_t d) {
  if (z < 10) stmatrix4(addr + z * 384, a, b, c, d);
  else asm volatile("stmatrix.sync.aligned.m8n8.x2.shared.b16 [%0], {%1, %2};" :: "r"(addr + z * 384), "r"(a), "r"(b) : "memory");
}

__device__ __forceinline__ void fetch_halo(const Ctx& c, unsigned tag, int tile) {
  const int z0 = (c.w & 1) * 5;
  const uint4* src = g_halo + (tile * 128 + c.b - 8) * 352 + z0 * 32 + c.lane;
  uint4 G[6];
#pragma unroll
  for (int z = 0; z < 6; z++) G[z] = make_uint4(0u, 0u, 0u, 0u);
  bar_sync(BAR_HGO, 96);
  for (unsigned it = 0; c.m > 0; it++) {
    bool ok = true;
#pragma unroll
    for (int z = 0; z < 6; z++) { G[z] = ld_tag128(src + z * 32); ok = ok && G[z].w == tag; }
    if (__all_sync(0xffffffffu, ok) || it > SPIN_LIMIT) break;
  }
#pragma unroll
  for (int z = 0; z < 6; z++) put_halo(c.sb + OFF_STG + (z0 - 5) * 384 + c.lane * 16, z + 5, G[z].x, G[z].y, G[z].z, G[z].w);
  if (z0) sts32f(c.sb + OFF_RST - 256 + c.lane * 8, __uint_as_float(G[5].z));
  __syncwarp();
  mbar_arrive_e(c.sb + OFF_HALO);
}

template<int SKEW>
__device__ __forceinline__ void conv_qkv(const Ctx& c, float (&acc)[2][96], uint32_t (&P)[3][2][4][4], int t) {
  const int lane = c.lane, w = c.w, g = lane >> 2, cc = lane & 3;
  const int layer = t >= 7;
  const uint32_t sb = (c.sb & 0x3ffffu) >> 4, par = layer ^ 1;
  uint32_t da = DESC_A + sb + 64, db = DESC_B + sb;
#define MMA(i, n) if (SKEW) do { wgmma_ss<192, 1>(acc[i], da, db); \
    asm volatile("add.s32 %0, %0, %2;\nadd.s32 %1, %1, %3;" : "+r"(da), "+r"(db) : "r"((n) == 11 ? -5190 : ((n) & 3) == 3 ? 2554 : 2), "r"((n) == 11 ? -5504 : ((n) & 3) == 3 ? 2176 : 128)); } while (0)
  if (SKEW) {
    mbar_wait(c.sb + OFF_FULL + 40, par);
    wgmma_fence();
    MMA(1, 0); MMA(1, 1); MMA(1, 2); MMA(1, 3);
    wgmma_commit();
    wgmma_wait<1>();
    release(c, 4);
    mbar_wait(c.sb + OFF_FULL + 48, par);
  } else finish(c, t);
  MMA(1, 4); MMA(1, 5);
  bar_sync(BAR_EPI + c.wg, 256);
  MMA(1, 6);
  mbar_wait(c.sb + OFF_TBL + 8 * SKEW, 0);
  MMA(1, 7);
  if (SKEW) mbar_wait(c.sb + OFF_FULL + 56, par);
  MMA(1, 8);
  bar_sync(BAR_FREE, 160);
  MMA(1, 9);
  const uint32_t rst = c.sb + OFF_RST + w * 256;
  float mu[4];
#pragma unroll
  for (int r = 0; r < 4; r++) mu[r] = __uint_as_float(lds32(rst + (8 * r + g) * 8 + 4));
  const uint32_t tag = smem_tag(c), rs_l = lds32(rst + lane * 8), zero = SKEW ? 0u : lds32(c.sb + OFF_ZERO);
  const uint32_t csb = c.sb + OFF_CSQ + SKEW * 768 + cc * 16;
  const uint32_t stg = c.sb + OFF_STG + w * 4096;
  uint4* const halo = g_halo + ((layer * 2 + SKEW) * 128 + c.b) * 352 + lane;
  const bool send = w == 3 && c.m < 15;
  float4 cs = lds128f(csb + 4 * 64);
  if (SKEW) {
    MMA(1, 10); MMA(1, 11);
    wgmma_commit();
    MMA(0, 0);
    wgmma_commit();
    MMA(0, 1);
    wgmma_commit();
    wgmma_wait<2>();
  }
  TL(t, 8);
  uint32_t d[2] = {0u, 0u};
#define CONV(i, np) do { _Pragma("unroll") for (int z = 0; z < 4; z++) { const int nt = 2 * (np) + (z >> 1), h = z & 1; \
    const float m = SKEW || !(EXP & 4) ? mu[2 * h + (i)] : after(mu[2 * h + (i)], d[h], zero); \
    d[h] = P[nt >> 3][(nt >> 2) & 1][2 * h + (i)][nt & 3] = pack_bf16(fmaf(z >> 1 ? cs.z : cs.x, m, acc[i][4 * nt + 2 * h]), \
                                                                     fmaf(z >> 1 ? cs.w : cs.y, m, acc[i][4 * nt + 2 * h + 1])); } } while (0)
#define HW(u) ((u) == 32 ? rs_l : P[1 + (((u) >> 4) & 1)][((u) >> 3) & 1][((u) & 2) + 1][(((u) >> 1) & 2) + ((u) & 1)])
#pragma unroll
  for (int n = 0; n < 12; n++) {
    const int np = (n + 4) % 12;
    if (n == HGO && w == 0) bar_arrive(BAR_HGO, 96);
    if (SKEW && n == 8) bar_arrive(BAR_START + (c.wg ^ 1), 256);
    if (SKEW && n < 10) { MMA(0, n + 2); wgmma_commit(); }
    CONV(1, np);
    cs = lds128f(csb + (n < 11 ? (n + 5) % 12 : 0) * 64);
#pragma unroll
    for (int z = 0; z < 11; z++)
      if (n < 8 && z >= 4 * n / 3 && (n == 7 || z < 4 * (n + 1) / 3)) {
        st_tag128_if(send, halo + z * 32, HW(3 * z), HW(3 * z + 1), HW(3 * z + 2), tag);
        put_halo(stg + 4096 + lane * 16, z, HW(3 * z), HW(3 * z + 1), HW(3 * z + 2), tag);
      }
    if (SKEW && n < 10) wgmma_wait<2>();
    if (SKEW && (n == 3 || n == 7)) release(c, 5 + (n >> 2), n == 3 || w ? 2 : 0);
  }
#undef MMA
#undef HW
  if (SKEW) {
    wgmma_wait<0>();
    release(c, 7, w ? 2 : 0);
    TL(t, 3);
  }
#pragma unroll
  for (int np = 0; np < 12; np++) {
    CONV(0, np);
    if (np < 11) cs = lds128f(csb + (np + 1) * 64);
  }
#undef CONV
}

__device__ __forceinline__ void epi_qkv(const Ctx& c, float (&acc)[2][96], int t, int q) {
  const int lane = c.lane, w = c.w, g = lane >> 2, cc = lane & 3;
  uint32_t P[3][2][4][4];
  if (q) conv_qkv<1>(c, acc, P, t); else conv_qkv<0>(c, acc, P, t);
  const uint32_t rst = c.sb + OFF_RST + w * 256, stg = c.sb + OFF_STG + w * 4096;
  const bool nohalo = w == 0 && c.m == 0;
#pragma unroll
  for (int z = 0; z < 16; z++) P[2][z >> 3][(z >> 1) & 2][z & 3] = movmatrix(P[2][z >> 3][(z >> 1) & 2][z & 3]);
  uint32_t K1[4][4], V1[4][4];
  const uint32_t hl = stg + (lane & 15) * 16 + (lane >> 4) * 512;
#define HZ(z) (((z) >> 1) * 1024 + ((z) & 1) * 256)
  __syncwarp();
#pragma unroll
  for (int z = 0; z < 4; z++) { ldmatrix4(hl + 4096 + HZ(z), K1[z]); ldmatrix4_t(hl + 4096 + 2048 + HZ(z), V1[z]); }
  TL(t, 9);
  bar_sync(BAR_WG + c.wg, 128);
  if (w == 0) { mbar_wait(c.sb + OFF_HALO, q); release(c, 6, 2 * q); release(c, 7, 2 * q); }
  uint32_t HK[4][4], HV[4][4];
#pragma unroll
  for (int z = 0; z < 4; z++) ldmatrix4(hl + HZ(z), HK[z]);
#pragma unroll
  for (int z = 0; z < 4; z++) ldmatrix4_t(hl + 2048 + HZ(z), HV[z]);
#undef HZ
  const bool far0 = 2 * cc > g, far1 = 2 * cc + 1 > g;
  float rk[4][2], sc[4][2];
#pragma unroll
  for (int r = 0; r < 4; r++) {
    const float rq = __uint_as_float(lds32(rst + (8 * r + g) * 8)) * (0.17677669529663687f * 1.4426950408889634f);
    const int back = r & 1 ? 64 : 192;
    rk[r][0] = __uint_as_float(lds32(rst + r * 64 + cc * 16 - (far0 ? back : 0)));
    rk[r][1] = __uint_as_float(lds32(rst + r * 64 + cc * 16 + 8 - (far1 ? back : 0)));
    sc[r][0] = rq * rk[r][0]; sc[r][1] = rq * rk[r][1];
  }
  TL(t, 4);
  float S[4][3][4];
  if (q == 0) bar_sync(BAR_P0, 256);
  float4 zero = lds128f(c.sb + OFF_ZERO);
#pragma unroll
  for (int k = 0; k < 2; k++)
#pragma unroll
    for (int z = 0; z < 4; z++) {
      const uint32_t* qa = P[0][z >> 1][2 * (z & 1)]; const uint32_t* qb = P[0][z >> 1][2 * (z & 1) + 1];
      const uint32_t* kk[3] = {HK[z], P[1][z >> 1][2 * (z & 1)], K1[z]};
#pragma unroll
      for (int n = 0; n < 3; n++) {
        if (k == 0) mma16816_z(S[z][n], qa[0], qb[0], qa[1], qb[1], kk[n][0], kk[n][1], zero);
        else mma16816(S[z][n], qa[2], qb[2], qa[3], qb[3], kk[n][2], kk[n][3]);
      }
    }
  if (q == 0) {
    uint32_t dep = 0;
#pragma unroll
    for (int z = 0; z < 12; z++) dep |= __float_as_uint(S[z / 3][z % 3][0]);
    bar_arrive_after(BAR_P1, dep);
  }
  TL(t, 10);
  const uint32_t fmask = (far0 ? 0xffffu : 0u) | (far1 ? 0xffff0000u : 0u);
  uint32_t pf[4][2], pn[4][2];
#pragma unroll
  for (int z = 0; z < 4; z++)
#pragma unroll
    for (int i = 0; i < 2; i++) {
      const int r = 2 * (z & 1) + i;
      float l0 = (far0 ? S[z][i][2 * i] : S[z][i + 1][2 * i]) * sc[r][0];
      float l1 = (far1 ? S[z][i][2 * i + 1] : S[z][i + 1][2 * i + 1]) * sc[r][1];
      if (i == 0 && nohalo) { const float neg = -1e9f * 1.4426950408889634f; if (far0) l0 = neg; if (far1) l1 = neg; }
      float mx = fmaxf(l0, l1);
      mx = fmaxf(mx, __shfl_xor_sync(0xffffffffu, mx, 1));
      mx = fmaxf(mx, __shfl_xor_sync(0xffffffffu, mx, 2));
      l0 = ex2(l0 - mx); l1 = ex2(l1 - mx);
      float sum = l0 + l1;
      l0 *= rk[r][0]; l1 *= rk[r][1];
      sum += __shfl_xor_sync(0xffffffffu, sum, 1);
      sum += __shfl_xor_sync(0xffffffffu, sum, 2);
      sum = rcp(sum);
      const uint32_t u = pack_bf16(l0 * sum, l1 * sum);
      pf[z][i] = u & fmask; pn[z][i] = u & ~fmask;
    }
  float O[4][2][2][4];
  TL(t, 11);
  if (q == 0) bar_sync_after(BAR_P0, (pn[0][0] | pn[0][1] | pn[1][0]) | (pn[1][1] | pn[2][0] | pn[2][1]) | (pn[3][0] | pn[3][1]));
  zero = lds128f(c.sb + OFF_ZERO);
  TL(t, 12);
#pragma unroll
  for (int z = 0; z < 4; z++)
#pragma unroll
    for (int d = 0; d < 2; d++) {
      const uint32_t* v0 = P[2][z >> 1][2 * (z & 1)] + 2 * d;
      mma16816_z(O[z][0][d], HV[z][2 * d], HV[z][2 * d + 1], v0[0], v0[1], pf[z][0], pn[z][0], zero);
      mma16816_z(O[z][1][d], v0[0], v0[1], V1[z][2 * d], V1[z][2 * d + 1], pf[z][1], pn[z][1], zero);
    }
  {
    uint32_t dep = 0;
#pragma unroll
    for (int z = 0; z < 16; z++) dep |= __float_as_uint(O[z >> 2][(z >> 1) & 1][z & 1][0]);
    bar_arrive_after(BAR_P1, dep);
  }
  TL(t, 5);
#pragma unroll
  for (int nt = 0; nt < 8; nt++) {
    uint32_t u[4];
#pragma unroll
    for (int r = 0; r < 4; r++) { const float* o = O[2 * (nt >> 2) + (r >> 1)][r & 1][(nt >> 1) & 1] + 2 * (nt & 1); u[r] = pack_bf16(o[0], o[1]); }
    stmatrix4_t(stg + lane * 128 + ((nt ^ (lane & 7)) << 4), u[0], u[1], u[2], u[3]);
  }
  fence_async_smem();
  bar_arrive(BAR_READY, 160);
  TL(t, 13);
}

template<int CH>
__device__ __forceinline__ void epi_up(const Ctx& c, float (&acc)[2][96], int type) {
  const int lane = c.lane, w = c.w, g = lane >> 2, cc = lane & 3;
  float rs[4], nm[4];
#pragma unroll
  for (int r = 0; r < 4; r++) { const float2 v = lds64f(c.sb + OFF_RST + (w * 32 + 8 * r + g) * 8); rs[r] = v.x; nm[r] = v.x * v.y; }
  const int loc0 = type == 3 ? 0 : (type == 4 ? 192 : 320);
  const uint32_t cb = c.sb + OFF_UP + loc0 * 8 + cc * 16;
  const uint32_t zero = lds32(c.sb + OFF_ZERO);
  uint32_t d[2] = {0u, 0u};
  const uint32_t stg = c.sb + OFF_STG + w * 4096;
#pragma unroll
  for (int ch = CH; ch < (CH ? 3 : 2); ch++) {
    uint32_t P[8][4];
#pragma unroll
    for (int n8 = 0; n8 < 8; n8++) {
      const int nt = ch * 8 + n8;
      const float4 cv = lds128f(cb + nt * 64);
#pragma unroll
      for (int r = 0; r < 4; r++) {
        const float m = after(nm[r], d[r & 1], zero);
        d[r & 1] = P[n8][r] = relu_sq_bf16(fmaf(acc[r & 1][4 * nt + 2 * (r >> 1)], rs[r], fmaf(cv.x, m, cv.z)),
                                           fmaf(acc[r & 1][4 * nt + 2 * (r >> 1) + 1], rs[r], fmaf(cv.y, m, cv.w)));
      }
    }
    bar_sync(BAR_FREE, 160);
#pragma unroll
    for (int n8 = 0; n8 < 8; n8++)
      stmatrix4(stg + lane * 128 + ((n8 ^ (lane & 7)) << 4), P[n8][0], P[n8][1], P[n8][2], P[n8][3]);
    fence_async_smem();
    bar_arrive(BAR_READY, 160);
  }
}

__device__ __forceinline__ void init_res(const Ctx& c, float (&acc)[2][96], int t, bool bias) {
  if (t <= 2) mbar_wait(c.sb + OFF_XBAR, 0);
  const uint32_t xb = c.sb + OFF_X + c.w * 4096 + c.lane * 128;
#pragma unroll
  for (int nt = 0; nt < 16; nt++) {
    uint32_t u[4];
    ldmatrix4(xb + (nt >> 3) * A_BYTES + (((nt & 7) ^ (c.lane & 7)) << 4), u);
    float2 b = make_float2(0.f, 0.f);
    if (bias) b = lds64f(c.sb + OFF_B2 + nt * 32 + (c.lane & 3) * 8);
#pragma unroll
    for (int r = 0; r < 4; r++) {
      acc[r & 1][4 * nt + 2 * (r >> 1)] = bf_lo(u[r]) + b.x;
      acc[r & 1][4 * nt + 2 * (r >> 1) + 1] = bf_hi(u[r]) + b.y;
    }
  }
}

__device__ __forceinline__ void epi_res(const Ctx& c, float (&acc)[2][96]) {
  const uint32_t xw = c.sb + OFF_X + c.w * 4096 + c.lane * 128;
#pragma unroll
  for (int nt = 0; nt < 16; nt++)
    stmatrix4(xw + (nt >> 3) * A_BYTES + (((nt & 7) ^ (c.lane & 7)) << 4),
              pack_bf16(acc[0][4 * nt], acc[0][4 * nt + 1]), pack_bf16(acc[1][4 * nt], acc[1][4 * nt + 1]),
              pack_bf16(acc[0][4 * nt + 2], acc[0][4 * nt + 3]), pack_bf16(acc[1][4 * nt + 2], acc[1][4 * nt + 3]));
  fence_async_smem();
  bar_arrive(BAR_RES, 192);
}

__device__ __forceinline__ void row_stats(const Ctx& c, float (&acc)[2][96], int ln) {
  const int g = c.lane >> 2, cc = c.lane & 3;
  float sm[4], sq[4];
#pragma unroll
  for (int r = 0; r < 4; r++) {
    float a = 0.f, b = 0.f;
#pragma unroll
    for (int n = 0; n < 32; n++) { const float x = acc[r & 1][4 * (n >> 1) + 2 * (r >> 1) + (n & 1)]; a += x; b = fmaf(x, x, b); }
    a += __shfl_xor_sync(0xffffffffu, a, 1); b += __shfl_xor_sync(0xffffffffu, b, 1);
    a += __shfl_xor_sync(0xffffffffu, a, 2); b += __shfl_xor_sync(0xffffffffu, b, 2);
    sm[r] = a; sq[r] = b;
  }
  const float a = cc == 0 ? sm[0] : cc == 1 ? sm[1] : cc == 2 ? sm[2] : sm[3];
  const float b = cc == 0 ? sq[0] : cc == 1 ? sq[1] : cc == 2 ? sq[2] : sq[3];
  st_tag128(g_stats + (ln * 128 + c.b) * 128 + c.w * 32 + 8 * cc + g, __float_as_uint(a), __float_as_uint(b), 0u, smem_tag(c));
}

__device__ __forceinline__ void load_table(const Ctx& c, const Params& p, int part, unsigned tag) {
  const int i0 = (part < 4 ? part * 192 : 704) + c.lane, n = part < 3 ? 6 : 4;
  const uint2* src = g_cs + c.j * NCS + i0;
  const uint32_t dst = c.sb + OFF_CSQ + (i0 & 1) * 4 + (part < 2 ? (i0 >> 4) * 64 + (i0 & 6) * 8 + (i0 & 8) : 1536 + ((i0 - 384) >> 1) * 16);
  const __nv_bfloat16* bias = p.b1 + (part == 2 ? c.j * 192 : (part == 3 ? 1536 : 2560) + c.j * 128) + c.lane;
  float v[6];
  if (part >= 2) {
#pragma unroll
    for (int k = 0; k < 6; k++) if (k < n) sts32f(dst + k * 256 + 8, __bfloat162float(bias[k * 32]));
  }
  for (unsigned it = 0;; it++) {
    bool ok = true;
#pragma unroll
    for (int k = 0; k < 6; k++) { const uint2 a = ld_tag64(src + (k < n ? k * 32 : 0)); ok = ok && a.y == tag; v[k] = __uint_as_float(a.x); }
    if (__all_sync(0xffffffffu, ok) || it > SPIN_LIMIT) break;
    __nanosleep(200);
  }
#pragma unroll
  for (int k = 0; k < 6; k++) if (k < n) sts32f(dst + k * (part < 2 ? 128 : 256), v[k]);
  __syncwarp();
}

__device__ __forceinline__ void colsum_cta(const Ctx& c, const Params& p, unsigned* epoch) {
  if (c.wg < 2) mbar_init_e(c.sb + OFF_FULL + 32 * c.wg + 8 * c.w, 1);
  sts32f(c.sb + OFF_STG + threadIdx.x * 4, __uint_as_float(0x3f803f80u));
  fence_async_smem();
  __syncthreads();
  if (c.wg == 2) return;
  const unsigned tag = *(volatile unsigned*)epoch + 1;
  const int j = (blockIdx.x - 128) * 2 + c.wg;
  const uint32_t ring = c.sb + c.wg * 98304, full = c.sb + OFF_FULL + 32 * c.wg;
  const uint64_t ones = (uint64_t)(((c.sb + OFF_STG) & 0x3ffffu) >> 4) | (8u << 16) | ((uint64_t)16u << 32);
  float d[3][4];
#pragma unroll 1
  for (int n = -4; n < 80; n++) {
    if (n >= 0) {
      mbar_wait(full + 8 * (n & 3), (n >> 2) & 1);
      const uint64_t da = (uint64_t)(((ring + (n & 3) * 24576) & 0x3ffffu) >> 4) | (64u << 16) | ((uint64_t)(64u | (1u << 30)) << 32);
      wgmma_fence();
#pragma unroll
      for (int k = 0; k < 4; k++)
#pragma unroll
        for (int z = 0; z < 3; z++)
          asm volatile("{\n.reg .pred p;\nsetp.ne.b32 p, %6, 0;\nwgmma.mma_async.sync.aligned.m64n8k16.f32.bf16.bf16 {%0,%1,%2,%3}, %4, %5, p, 1, 1, 1, 0;\n}"
            : "+f"(d[z][0]), "+f"(d[z][1]), "+f"(d[z][2]), "+f"(d[z][3]) : "l"(da + z * 512 + k * 128), "l"(ones), "r"((n & 15) | k));
      wgmma_commit();
      wgmma_wait<0>();
      bar_sync(BAR_WG + c.wg, 128);
      if ((n & 15) == 15 && (c.lane & 3) < 2) {
        const int u = n >> 4;
        uint2* out = g_cs + j * NCS + (u < 4 ? u * 192 : 704) + c.w * 16 + (c.lane >> 2) + (c.lane & 1) * 8;
#pragma unroll
        for (int z = 0; z < 3; z++) if (z < 2 || u < 3) st_tag64(out + z * 64, (c.lane & 1) ? d[z][2] : d[z][0], tag);
      }
      __syncwarp();
    }
    if (c.w == 0 && n < 76) {
      const int u = (n + 4) >> 4;
      const WTile w = wtile(p, u + (u >= 2), j);
      mbar_expect_e(full + 8 * (n & 3), u < 3 ? 24576 : 16384);
      tma_ld3_e(ring + (n & 3) * 24576, w.mp, full + 8 * (n & 3), w.c0, ((n + 4) & 15) * 64, w.c2);
    }
  }
  bar_sync(BAR_START, 256);
  if (threadIdx.x == 0) *epoch = tag;
}

__global__ void __cluster_dims__(2, 1, 1) __launch_bounds__(384, 1) fused_kernel(unsigned* const epochs, const __grid_constant__ Params p) {
  extern __shared__ uint8_t smem_raw[];
  Ctx c;
  c.sb = (smem_u32(smem_raw) + 1023) & ~1023u;
  const int tid = threadIdx.x;
  const int k = __shfl_sync(0xffffffffu, tid >> 5, 0);
  c.wg = k >> 2; c.w = k & 3; c.lane = tid & 31;
  c.rank = blockIdx.x & 1;
  if (blockIdx.x >= 128) { colsum_cta(c, p, epochs + blockIdx.x); return; }
  uint32_t slot; asm volatile("mov.u32 %0, %%smid;" : "=r"(slot));
  slot = __shfl_sync(0xffffffffu, slot < 120 ? slot >> 1 : 60 + ((slot >> 1) & 3), 0);
  const bool claim = tid == 0 && c.rank == 0;
  unsigned epoch, old;
  asm volatile("{\n.reg .pred p;\nsetp.ne.u32 p, %4, 0;\nmov.u32 %0, 0;\nmov.u32 %1, 0;\n@p atom.relaxed.gpu.global.add.u32 %0, [%2], 1;\n@p ld.relaxed.gpu.global.u32 %1, [%3];\n}"
    : "=r"(old), "=r"(epoch) : "l"(epochs + 132 + slot + tid), "l"(epochs + blockIdx.x), "r"((uint32_t)claim) : "memory");
#pragma unroll 1
  for (int pass = 0;; pass++) {
    const int row = slot < 32 ? slot >> 3 : slot < 60 ? ((slot - 4) * 37) >> 8 : slot - 56;
    const int gpc = slot < 60 ? slot - row * (slot < 32 ? 8 : 7) - (slot < 32 ? 0 : 3) : 0;
    c.m = (gpc & 1) * 8 + row;
    c.j = (gpc & 6) + c.rank; c.b = c.m * 8 + c.j;
    if (k == 9) {
      asm volatile(ELECT "@p mbarrier.init.shared::cta.b64 [%0], 2;\n@p mbarrier.init.shared::cta.b64 [%0 + 8], 2;\n"
        "@p mbarrier.init.shared::cta.b64 [%0 + 16], 2;\n@p mbarrier.init.shared::cta.b64 [%0 + 24], 2;\n}" :: "r"(c.sb + OFF_FULL) : "memory");
      fence_async_smem();
      if (!pass) asm volatile("fence.mbarrier_init.release.cluster;\nbarrier.cluster.arrive.relaxed.aligned;" ::: "memory");
#pragma unroll 1
      for (int s = 0; s < 4; s++) {
        const uint32_t full = c.sb + OFF_FULL + 8 * s, dst = c.sb + ((s + 3) & 3) * 40960;
        mbar_expect_e(full, 40960);
        tma_ld4_e(dst, &p.ld_x, full, s * 64, c.m * 4);
        tma_ld4_e(dst + 8192, &p.ld_x, full, s * 64, c.m * 4 + 2);
        tma_ld3_e(dst + A_BYTES, &p.w_qkv, full, c.j * 64, s * 64, 0);
        mbar_arrive_e(full);
      }
    } else if (!pass) {
      if (k < 8) { mbar_init_e(c.sb + OFF_EMPTY + 8 * k, 8); mbar_init_e(c.sb + (k < 4 ? OFF_XBAR : OFF_FULL) + 8 * k, k < 4 ? 1 : 2); }
      if (k == 10) { mbar_init_e(c.sb + OFF_HALO, 2); mbar_init_e(c.sb + OFF_SLOT, 1); mbar_expect_e(c.sb + OFF_SLOT, 8); sts128(c.sb + OFF_ZERO, 0u, 0u, 0u, 0u); }
      asm volatile("fence.mbarrier_init.release.cluster;\nbarrier.cluster.arrive.relaxed.aligned;" ::: "memory");
    }
    if (pass) { __syncthreads(); break; }
    asm volatile("barrier.cluster.wait.aligned;" ::: "memory");
    if (claim) {
      uint32_t s = slot;
      for (int it = 0; old != epoch && it < 64; it++) { atomicSub(epochs + 132 + s, 1u); s = (s + 1) & 63; old = atomicAdd(epochs + 132 + s, 1u); }
#pragma unroll
      for (int r = 0; r < 2; r++)
        asm volatile("{\n.reg .u32 t;\nadd.u32 t, %1, 1;\nst.async.weak.shared::cluster.mbarrier::complete_tx::bytes.v2.b32 [%0], {t, %2}, [%3];\n}"
          :: "r"(mapa(c.sb + OFF_TAG, r)), "r"(old), "r"(s), "r"(mapa(c.sb + OFF_SLOT, r)) : "memory");
    }
    __syncwarp();
    mbar_wait(c.sb + OFF_SLOT, 0);
    const uint32_t got = __shfl_sync(0xffffffffu, lds32(c.sb + OFF_TAG + 4), 0);
    if (got == slot) break;
    slot = got;
    if (k == 9)
      for (int s = 0; s < 4; s++) { mbar_wait(c.sb + OFF_FULL + 8 * s, 0); asm volatile(ELECT "@p mbarrier.inval.shared::cta.b64 [%0];\n}" :: "r"(c.sb + OFF_FULL + 8 * s) : "memory"); }
  }
  if (c.wg == 2) {
    reg_dealloc<40>();
    const unsigned tag = smem_tag(c);
    if (c.w < 2) {
      int g = 4;
#pragma unroll 1
      for (int t = 0; t < 14; t++) {
        const int layer = t >= 7, type = t - layer * 7;
        const bool wide = type < 2 || type == 3, own = type == 3 || t == 7;
        const int nkb = type == 6 ? 56 : 16, ns = wide ? 4 : 5, str = wide ? 40960 : 32768;
        const int nshort = type == 0 ? 3 : (type == 2 || type == 4) ? 4 : 0;
        int st = first_stage(type);
        if (c.w == 0) {
          const CUtensorMap* mp = type == 2 || type == 6 ? &p.ld_h : (t < 2 ? &p.ld_x : &p.ld_out);
          const int slab = c.m * 4 + c.rank * 2;
          const unsigned* fp = g_flags + (t * 16 + c.m) * 32 + c.lane;
          unsigned ready = own ? 15u << (c.j >> 1) * 4 : type == 2 ? 0x300u << (c.j & 6) : type == 6 ? 0u : ~0u;
          const int local = own ? 0 : type == 2 ? 8 : 64, nloc = own ? 2 : 1;
#pragma unroll 1
          for (int step = t ? 0 : 4; step < nkb; step++, g++) {
            const int kb = kb_order(c, t, type, step);
            const int piece = type != 6 ? kb : step < 24 ? (step * 43) >> 7 : (step >> 1) - 4;
            for (unsigned it = 0; !((ready >> piece) & 1) && it < SPIN_LIMIT; it++) {
              unsigned v; asm volatile("ld.relaxed.gpu.global.u32 %0, [%1];" : "=r"(v) : "l"(fp) : "memory");
              ready |= __ballot_sync(0xffffffffu, v == tag);
              asm volatile("fence.proxy.async.global;" ::: "memory");
            }
            const int e = g - (step < nshort ? ns - 1 : ns);
            if (e >= 0) mbar_wait(c.sb + OFF_EMPTY + 8 * (e & 7), (e >> 3) & 1);
            const uint32_t full = c.sb + OFF_FULL + 8 * (g & 7);
            if ((unsigned)(step - local) >= nloc) mbar_expect_e(full, A_BYTES);
            if ((unsigned)(step - local) >= 2 * nloc) tma_ld4_mc_e(c.sb + st * str + c.rank * 8192, mp, full, kb * 64, slab);
            else if (step == 9) {
              const uint32_t peer = mapa(c.sb, c.rank ^ 1);
              mbar_wait(c.sb + OFF_FULL, layer ^ 1);
              dsmem_copy_e(peer + 3 * 32768, c.sb + OFF_STG, peer + OFF_FULL + 8);
            }
            if (++st == ns) st = 0;
          }
        } else {
          const WTile w = wtile(p, type, c.j);
#pragma unroll 1
          for (int step = t ? 0 : 4; step < nkb; step++, g++) {
            const int e = g - (step < nshort ? ns - 1 : ns);
            if (e >= 0) mbar_wait(c.sb + OFF_EMPTY + 8 * (e & 7), (e >> 3) & 1);
            const uint32_t full = c.sb + OFF_FULL + 8 * (g & 7);
            const int kb = kb_order(c, t, type, step);
            mbar_expect_e(full, str - A_BYTES);
            tma_ld3_e(c.sb + st * str + A_BYTES, w.mp, full, w.c0, kb * 64, w.c2);
            if ((g & 15) == c.m && g + 16 < 2 * KB_LAYER) {
              const bool nx = step + 16 >= nkb;
              const int s2 = step + 16 - (nx ? nkb : 0);
              const WTile v = wtile(p, nx ? (type == 6 ? 0 : type + 1) : 6, c.j);
              tma_pf3_e(v.mp, v.c0, (nx && (type == 2 || type == 6) ? own_kb(c, s2) : s2) * 64, v.c2);
            }
            if (++st == ns) st = 0;
          }
        }
      }
    } else if (c.w == 2) {
      bar_arrive(BAR_FREE, 160);
#pragma unroll 1
      for (int t = 0; t < 14; t++) {
        const int layer = t >= 7, type = t - layer * 7;
        const int slab = c.m * 4;
        unsigned* flag = g_flags + c.m * 32 + c.j;
        if (type == 2 || type == 6) {
          flag += (t + 1) * 512 + c.j;
          bar_sync(BAR_RES, 192);
          tma_st4_e(&p.st_out, c.sb + OFF_X, c.j * 128, slab);
          if (t < 13) {
            bulk_wait_read_e();
            bar_arrive(BAR_COPY, 64);
            PTL(t, 8);
            publish_e(flag++, tag);
            PTL(t, 9);
          }
          tma_st4_e(&p.st_out, c.sb + OFF_X + A_BYTES, c.j * 128 + 64, slab);
          bulk_wait_read_e();
          PTL(t, 11);
        } else {
          flag += (layer * 7 + (type < 2 ? 2 : 6)) * 512 + (type < 2 ? type : type - 3) * 8;
          const int col = type < 2 ? (c.j + 8 * type) * 64 : type == 3 ? c.j * 192 : (type == 4 ? 1536 : 2560) + c.j * 128;
#pragma unroll 1
          for (int ch = type == 3 ? -1 : 0; ch < (type < 2 ? 1 : 2); ch++) {
            if (type < 2) fetch_halo(c, tag, layer * 2 + type);
            bar_sync(BAR_READY, 160);
            tma_st4_e(&p.st_h, c.sb + OFF_STG, col + (ch < 0 ? 128 : ch * 64), slab);
            if (type == 1) { mbar_wait(c.sb + OFF_FULL, layer); mbar_arrive_e(c.sb + OFF_FULL); }
            bulk_wait_read_e();
            if (t < 12 || ch == 0) bar_arrive(BAR_FREE, 160);
          }
          PTL(t, 14);
        }
        if (t < 13) publish_e(flag, tag);
        PTL(t, 6);
      }
      if (c.lane == 0) epochs[blockIdx.x] = tag;
    } else {
      mbar_wait(c.sb + OFF_FULL + 0, 0);
      PTL(14, 14);
      mbar_expect_e(c.sb + OFF_XBAR, 32768);
#pragma unroll
      for (int i = 0; i < 4; i++) tma_ld4_e(c.sb + OFF_X + i * 8192, &p.ld_x, c.sb + OFF_XBAR, c.j * 128 + (i >> 1) * 64, c.m * 4 + (i & 1) * 2);
#pragma unroll
      for (int i = 0; i < 4; i++) sts32f(c.sb + OFF_B2 + i * 128 + c.lane * 4, __bfloat162float(p.b2[c.j * 128 + i * 32 + c.lane]));
      const uint32_t peer = mapa(c.sb, c.rank ^ 1);
      int part = 0;
#pragma unroll 1
      for (int i = 0; i < 3; i++) {
        const int g1 = i == 0 ? 48 : i == 1 ? KB_LAYER : KB_LAYER + 48;
#pragma unroll 1
        for (; part < (i == 0 ? 2 : i == 1 ? 5 : 7); part++) {
          if (part < 5) {
            load_table(c, p, part, tag);
            if (part != 2 && part != 3) mbar_arrive_e(c.sb + OFF_TBL + 8 * (part < 2 ? part : 2));
            PTL(part, 7);
          }
          if (i != 1) fetch_halo(c, tag, i ? part - 3 : part);
        }
        bar_sync(BAR_RES, 192);
        mbar_arrive_e(c.sb + OFF_FULL);
        mbar_arrive_e(c.sb + OFF_FULL + 8);
        mbar_wait(c.sb + OFF_EMPTY + 56, ((g1 - 1) >> 3) & 1);
        bar_sync(BAR_COPY, 64);
        __nanosleep(40);
#pragma unroll
        for (int ch = 0; ch < 2; ch++)
          dsmem_copy_e(peer + ((i == 1 ? 1 : 2) + ch) * 40960, c.sb + OFF_X + ch * A_BYTES, peer + OFF_FULL + 16 + 8 * ch);
        PTL(i == 0 ? 2 : i == 1 ? 6 : 9, 10);
      }
      bar_arrive(BAR_RES, 192);
    }
  } else {
    reg_alloc<232>();
#pragma unroll 1
    for (int t = -c.wg; t < 14; t += 2) {
      const int layer = t >= 7, type = t - layer * 7;
      const int g0 = layer * KB_LAYER + type * 16;
      float acc[2][96];
      if (t < 0 || type == 2 || type == 6) {
        init_res(c, acc, t, type == 6);
        if (t >= 0) {
          const int nkb = type == 6 ? 56 : 16;
          mainloop<128, 1>(c, acc, t, type, g0, nkb);
          finish(c, t);
          if (t == 13) asm volatile("barrier.cluster.arrive.relaxed.aligned;" ::: "memory");
          epi_res(c, acc);
          if (t == 13) break;
        }
        TL(t, 4);
        const int ln = t < 0 ? 0 : layer * 2 + (type == 6 ? 2 : 1);
        row_stats(c, acc, ln);
        load_row_stats(c, ln);
        TL(t, 5);
      } else {
        if (type < 4) {
          mainloop<192, 0>(c, acc, t, type, g0, type == 1 ? 13 : 16);
          if (type < 2) { epi_qkv(c, acc, t, type); goto done; }
          finish(c, t);
          bar_sync(BAR_EPI + c.wg, 256);
          mbar_wait(c.sb + OFF_TBL + 16, 0);
          epi_up<2>(c, acc, type);
        } else {
          mainloop<128, 0>(c, acc, t, type, g0, 16);
          finish(c, t);
          bar_sync(BAR_EPI + c.wg, 256);
        }
        epi_up<0>(c, acc, type);
        TL(t, 4);
      done:;
      }
      if (type != 1 && type != 5) bar_arrive(BAR_EPI + (c.wg ^ 1), 256);
    }
    if (c.wg == 1) {
      asm volatile("barrier.cluster.wait.aligned;" ::: "memory");
    }
  }
}

typedef CUresult (*EncodeFn)(CUtensorMap*, CUtensorMapDataType, cuuint32_t, void*, const cuuint64_t*, const cuuint64_t*,
                             const cuuint32_t*, const cuuint32_t*, CUtensorMapInterleave, CUtensorMapSwizzle,
                             CUtensorMapL2promotion, CUtensorMapFloatOOBfill);

void make_map(EncodeFn fn, CUtensorMap* m, const void* ptr, int rank, const cuuint64_t* dims, const cuuint64_t* strides, const cuuint32_t* box) {
  const cuuint32_t es[4] = {1, 1, 1, 1};
  fn(m, CU_TENSOR_MAP_DATA_TYPE_BFLOAT16, rank, const_cast<void*>(ptr), dims, strides, box, es, CU_TENSOR_MAP_INTERLEAVE_NONE,
     CU_TENSOR_MAP_SWIZZLE_128B, CU_TENSOR_MAP_L2_PROMOTION_L2_128B, CU_TENSOR_MAP_FLOAT_OOB_FILL_NONE);
}
void map_rows(EncodeFn fn, CUtensorMap* m, const void* ptr, int cols, int rows, int box_slabs, bool tokens) {
  const cuuint64_t rb = (cuuint64_t)cols * 2;
  const cuuint64_t dims[4] = {(cuuint64_t)cols, 16, 2, (cuuint64_t)(rows / 32)};
  const cuuint64_t st[3] = {tokens ? 2 * rb : rb, tokens ? rb : 16 * rb, 32 * rb};
  const cuuint32_t box[4] = {64, 16, 2, (cuuint32_t)box_slabs};
  make_map(fn, m, ptr, 4, dims, st, box);
}
void map_w(EncodeFn fn, CUtensorMap* m, const void* ptr, int K, int N, int inner, int nch) {
  const cuuint64_t dims[3] = {(cuuint64_t)inner, (cuuint64_t)K, (cuuint64_t)(N / inner)}, st[2] = {(cuuint64_t)N * 2, (cuuint64_t)inner * 2};
  const cuuint32_t box[3] = {64, 64, (cuuint32_t)nch};
  make_map(fn, m, ptr, 3, dims, st, box);
}

}

extern "C" void kernel_launch(void* const* d_in, const int* in_sizes, int n_in, void* d_out, int out_size) {
  (void)in_sizes; (void)n_in; (void)out_size;
  Params p;
  p.b1 = (const __nv_bfloat16*)d_in[5]; p.b2 = (const __nv_bfloat16*)d_in[7];
  void* fnp = nullptr; cudaDriverEntryPointQueryResult qr;
  cudaGetDriverEntryPoint("cuTensorMapEncodeTiled", &fnp, cudaEnableDefault, &qr);
  EncodeFn fn = (EncodeFn)fnp;
  void *h, *epochs;
  cudaGetSymbolAddress(&h, g_h);
  cudaGetSymbolAddress(&epochs, g_epoch);
  map_rows(fn, &p.ld_x, d_in[0], D_, S_, 2, true);
  map_rows(fn, &p.ld_out, d_out, D_, S_, 2, true);
  map_rows(fn, &p.ld_h, h, F_, S_, 2, false);
  map_rows(fn, &p.st_h, h, F_, S_, 4, false);
  map_rows(fn, &p.st_out, d_out, D_, S_, 4, true);
  map_w(fn, &p.w_qkv, d_in[1], D_, 3 * D_, D_, 3);
  map_w(fn, &p.w_o, d_in[2], D_, D_, 64, 2);
  map_w(fn, &p.w_1a, d_in[4], D_, F_, 64, 3);
  map_w(fn, &p.w_1b, d_in[4], D_, F_, 64, 2);
  map_w(fn, &p.w_2, d_in[6], F_, D_, 64, 2);
  cudaFuncSetAttribute(fused_kernel, cudaFuncAttributeMaxDynamicSharedMemorySize, SMEM_BYTES);
  fused_kernel<<<132, 384, SMEM_BYTES>>>((unsigned*)epochs, p);
}
```

```cpp
#include <cuda_runtime.h>
#include <cuda_bf16.h>
#include <cuda.h>
#include <stdint.h>

#define EXP 0
namespace {

constexpr int S_ = 2048, D_ = 1024, F_ = 3584;
constexpr int A_BYTES = 16384;
constexpr int OFF_X   = 163840;
constexpr int OFF_STG = OFF_X + 32768;
constexpr int OFF_CSQ = OFF_STG + 20480;
constexpr int OFF_UP  = OFF_CSQ + 1536;
constexpr int OFF_B2  = OFF_UP + 3584;
constexpr int OFF_RST = OFF_B2 + 512 + 256;
constexpr int OFF_FULL = OFF_RST + 1024;
constexpr int OFF_EMPTY = OFF_FULL + 64;
constexpr int OFF_XBAR = OFF_EMPTY + 64;
constexpr int OFF_TBL = OFF_XBAR + 8;
constexpr int OFF_HALO = OFF_XBAR + 48;
constexpr int OFF_SLOT = OFF_XBAR + 88;
constexpr int OFF_PEER = OFF_XBAR + 64;
constexpr int OFF_PRE = OFF_XBAR + 72;
constexpr int OFF_ZERO = OFF_XBAR + 96;
constexpr int OFF_TAG = OFF_ZERO + 16;
constexpr int OFF_PLAN = OFF_TAG + 16, PLAN_BYTES = 5120;
constexpr int SMEM_BYTES = OFF_PLAN + PLAN_BYTES + 48 + 1024;
constexpr int KB_LAYER = 6 * 16 + 56;
constexpr int NCS = 384 + 448;
constexpr unsigned SPIN_LIMIT = 1u << 20;
constexpr int PC = 1, NS = 12, NP = 8, SA = 7, SB = 11, S1 = (EXP & 32) ? 5 : (EXP & 16) ? 6 : 4;
constexpr int SPL = 1, REL = 1, PAUSE1 = 7, PAUSE2 = 8, EARLY = 0, HGK = 8, HGO = 11;
constexpr uint32_t DESC_A = 1u << 16, DESC_B = (512u << 16) + A_BYTES / 16;
enum { BAR_START = 1, BAR_EPI = 3, BAR_WG = 5, BAR_P0 = 7, BAR_P1 = 8, BAR_RES = 9, BAR_READY = 10, BAR_FREE = 11, BAR_COPY = 12, BAR_RES2 = 13, BAR_HGO = 14 };

struct Params {
  CUtensorMap ld_x, ld_out, ld_h, st_h, st_out, w_qkv, w_o, w_1a, w_1b, w_2;
  const __nv_bfloat16 *b1, *b2;
};

__device__ __align__(1024) __nv_bfloat16 g_h[S_ * F_];
__device__ __align__(128) uint4 g_stats[4 * S_ * 8];
__device__ __align__(128) uint2 g_cs[8 * NCS];
__device__ __align__(128) uint4 g_halo[4 * 128 * 11 * 32];
__device__ __align__(128) unsigned g_flags[14 * 16 * 32];
#define TL(t, e)
#define PTL(t, e)
#if !defined(TIMELINE) || !(EXP & 8)
#undef TK
#define TK(t, k)
#endif

template<int N, int KEEP> __device__ __forceinline__ void wgmma_ss(float (&d)[96], uint32_t da, uint32_t db);
template<> __device__ __forceinline__ void wgmma_ss<128, 0>(float (&d)[96], uint32_t da, uint32_t db) {
  asm volatile("{\n.reg .pred p;\n.reg .b64 a, b;\nsetp.ne.b32 p, 0, 0;\nmov.b64 a, {%64, 0x40000080};\nmov.b64 b, {%65, 0x40000040};\nwgmma.mma_async.sync.aligned.m64n128k16.f32.bf16.bf16 {%0, %1, %2, %3, %4, %5, %6, %7, %8, %9, %10, %11, %12, %13, %14, %15, %16, %17, %18, %19, %20, %21, %22, %23, %24, %25, %26, %27, %28, %29, %30, %31, %32, %33, %34, %35, %36, %37, %38, %39, %40, %41, %42, %43, %44, %45, %46, %47, %48, %49, %50, %51, %52, %53, %54, %55, %56, %57, %58, %59, %60, %61, %62, %63}, a, b, p, 1, 1, 0, 1;\n}"
    : "=f"(d[0]), "=f"(d[1]), "=f"(d[2]), "=f"(d[3]), "=f"(d[4]), "=f"(d[5]), "=f"(d[6]), "=f"(d[7]), "=f"(d[8]), "=f"(d[9]), "=f"(d[10]), "=f"(d[11]), "=f"(d[12]), "=f"(d[13]), "=f"(d[14]), "=f"(d[15]), "=f"(d[16]), "=f"(d[17]), "=f"(d[18]), "=f"(d[19]), "=f"(d[20]), "=f"(d[21]), "=f"(d[22]), "=f"(d[23]), "=f"(d[24]), "=f"(d[25]), "=f"(d[26]), "=f"(d[27]), "=f"(d[28]), "=f"(d[29]), "=f"(d[30]), "=f"(d[31]), "=f"(d[32]), "=f"(d[33]), "=f"(d[34]), "=f"(d[35]), "=f"(d[36]), "=f"(d[37]), "=f"(d[38]), "=f"(d[39]), "=f"(d[40]), "=f"(d[41]), "=f"(d[42]), "=f"(d[43]), "=f"(d[44]), "=f"(d[45]), "=f"(d[46]), "=f"(d[47]), "=f"(d[48]), "=f"(d[49]), "=f"(d[50]), "=f"(d[51]), "=f"(d[52]), "=f"(d[53]), "=f"(d[54]), "=f"(d[55]), "=f"(d[56]), "=f"(d[57]), "=f"(d[58]), "=f"(d[59]), "=f"(d[60]), "=f"(d[61]), "=f"(d[62]), "=f"(d[63])
    : "r"(da), "r"(db));
}
template<> __device__ __forceinline__ void wgmma_ss<128, 1>(float (&d)[96], uint32_t da, uint32_t db) {
  asm volatile("{\n.reg .pred p;\n.reg .b64 a, b;\nsetp.ne.b32 p, 1, 0;\nmov.b64 a, {%64, 0x40000080};\nmov.b64 b, {%65, 0x40000040};\nwgmma.mma_async.sync.aligned.m64n128k16.f32.bf16.bf16 {%0, %1, %2, %3, %4, %5, %6, %7, %8, %9, %10, %11, %12, %13, %14, %15, %16, %17, %18, %19, %20, %21, %22, %23, %24, %25, %26, %27, %28, %29, %30, %31, %32, %33, %34, %35, %36, %37, %38, %39, %40, %41, %42, %43, %44, %45, %46, %47, %48, %49, %50, %51, %52, %53, %54, %55, %56, %57, %58, %59, %60, %61, %62, %63}, a, b, p, 1, 1, 0, 1;\n}"
    : "+f"(d[0]), "+f"(d[1]), "+f"(d[2]), "+f"(d[3]), "+f"(d[4]), "+f"(d[5]), "+f"(d[6]), "+f"(d[7]), "+f"(d[8]), "+f"(d[9]), "+f"(d[10]), "+f"(d[11]), "+f"(d[12]), "+f"(d[13]), "+f"(d[14]), "+f"(d[15]), "+f"(d[16]), "+f"(d[17]), "+f"(d[18]), "+f"(d[19]), "+f"(d[20]), "+f"(d[21]), "+f"(d[22]), "+f"(d[23]), "+f"(d[24]), "+f"(d[25]), "+f"(d[26]), "+f"(d[27]), "+f"(d[28]), "+f"(d[29]), "+f"(d[30]), "+f"(d[31]), "+f"(d[32]), "+f"(d[33]), "+f"(d[34]), "+f"(d[35]), "+f"(d[36]), "+f"(d[37]), "+f"(d[38]), "+f"(d[39]), "+f"(d[40]), "+f"(d[41]), "+f"(d[42]), "+f"(d[43]), "+f"(d[44]), "+f"(d[45]), "+f"(d[46]), "+f"(d[47]), "+f"(d[48]), "+f"(d[49]), "+f"(d[50]), "+f"(d[51]), "+f"(d[52]), "+f"(d[53]), "+f"(d[54]), "+f"(d[55]), "+f"(d[56]), "+f"(d[57]), "+f"(d[58]), "+f"(d[59]), "+f"(d[60]), "+f"(d[61]), "+f"(d[62]), "+f"(d[63])
    : "r"(da), "r"(db));
}
template<> __device__ __forceinline__ void wgmma_ss<192, 0>(float (&d)[96], uint32_t da, uint32_t db) {
  asm volatile("{\n.reg .pred p;\n.reg .b64 a, b;\nsetp.ne.b32 p, 0, 0;\nmov.b64 a, {%96, 0x40000080};\nmov.b64 b, {%97, 0x40000040};\nwgmma.mma_async.sync.aligned.m64n192k16.f32.bf16.bf16 {%0, %1, %2, %3, %4, %5, %6, %7, %8, %9, %10, %11, %12, %13, %14, %15, %16, %17, %18, %19, %20, %21, %22, %23, %24, %25, %26, %27, %28, %29, %30, %31, %32, %33, %34, %35, %36, %37, %38, %39, %40, %41, %42, %43, %44, %45, %46, %47, %48, %49, %50, %51, %52, %53, %54, %55, %56, %57, %58, %59, %60, %61, %62, %63, %64, %65, %66, %67, %68, %69, %70, %71, %72, %73, %74, %75, %76, %77, %78, %79, %80, %81, %82, %83, %84, %85, %86, %87, %88, %89, %90, %91, %92, %93, %94, %95}, a, b, p, 1, 1, 0, 1;\n}"
    : "=f"(d[0]), "=f"(d[1]), "=f"(d[2]), "=f"(d[3]), "=f"(d[4]), "=f"(d[5]), "=f"(d[6]), "=f"(d[7]), "=f"(d[8]), "=f"(d[9]), "=f"(d[10]), "=f"(d[11]), "=f"(d[12]), "=f"(d[13]), "=f"(d[14]), "=f"(d[15]), "=f"(d[16]), "=f"(d[17]), "=f"(d[18]), "=f"(d[19]), "=f"(d[20]), "=f"(d[21]), "=f"(d[22]), "=f"(d[23]), "=f"(d[24]), "=f"(d[25]), "=f"(d[26]), "=f"(d[27]), "=f"(d[28]), "=f"(d[29]), "=f"(d[30]), "=f"(d[31]), "=f"(d[32]), "=f"(d[33]), "=f"(d[34]), "=f"(d[35]), "=f"(d[36]), "=f"(d[37]), "=f"(d[38]), "=f"(d[39]), "=f"(d[40]), "=f"(d[41]), "=f"(d[42]), "=f"(d[43]), "=f"(d[44]), "=f"(d[45]), "=f"(d[46]), "=f"(d[47]), "=f"(d[48]), "=f"(d[49]), "=f"(d[50]), "=f"(d[51]), "=f"(d[52]), "=f"(d[53]), "=f"(d[54]), "=f"(d[55]), "=f"(d[56]), "=f"(d[57]), "=f"(d[58]), "=f"(d[59]), "=f"(d[60]), "=f"(d[61]), "=f"(d[62]), "=f"(d[63]), "=f"(d[64]), "=f"(d[65]), "=f"(d[66]), "=f"(d[67]), "=f"(d[68]), "=f"(d[69]), "=f"(d[70]), "=f"(d[71]), "=f"(d[72]), "=f"(d[73]), "=f"(d[74]), "=f"(d[75]), "=f"(d[76]), "=f"(d[77]), "=f"(d[78]), "=f"(d[79]), "=f"(d[80]), "=f"(d[81]), "=f"(d[82]), "=f"(d[83]), "=f"(d[84]), "=f"(d[85]), "=f"(d[86]), "=f"(d[87]), "=f"(d[88]), "=f"(d[89]), "=f"(d[90]), "=f"(d[91]), "=f"(d[92]), "=f"(d[93]), "=f"(d[94]), "=f"(d[95])
    : "r"(da), "r"(db));
}
template<> __device__ __forceinline__ void wgmma_ss<192, 1>(float (&d)[96], uint32_t da, uint32_t db) {
  asm volatile("{\n.reg .pred p;\n.reg .b64 a, b;\nsetp.ne.b32 p, 1, 0;\nmov.b64 a, {%96, 0x40000080};\nmov.b64 b, {%97, 0x40000040};\nwgmma.mma_async.sync.aligned.m64n192k16.f32.bf16.bf16 {%0, %1, %2, %3, %4, %5, %6, %7, %8, %9, %10, %11, %12, %13, %14, %15, %16, %17, %18, %19, %20, %21, %22, %23, %24, %25, %26, %27, %28, %29, %30, %31, %32, %33, %34, %35, %36, %37, %38, %39, %40, %41, %42, %43, %44, %45, %46, %47, %48, %49, %50, %51, %52, %53, %54, %55, %56, %57, %58, %59, %60, %61, %62, %63, %64, %65, %66, %67, %68, %69, %70, %71, %72, %73, %74, %75, %76, %77, %78, %79, %80, %81, %82, %83, %84, %85, %86, %87, %88, %89, %90, %91, %92, %93, %94, %95}, a, b, p, 1, 1, 0, 1;\n}"
    : "+f"(d[0]), "+f"(d[1]), "+f"(d[2]), "+f"(d[3]), "+f"(d[4]), "+f"(d[5]), "+f"(d[6]), "+f"(d[7]), "+f"(d[8]), "+f"(d[9]), "+f"(d[10]), "+f"(d[11]), "+f"(d[12]), "+f"(d[13]), "+f"(d[14]), "+f"(d[15]), "+f"(d[16]), "+f"(d[17]), "+f"(d[18]), "+f"(d[19]), "+f"(d[20]), "+f"(d[21]), "+f"(d[22]), "+f"(d[23]), "+f"(d[24]), "+f"(d[25]), "+f"(d[26]), "+f"(d[27]), "+f"(d[28]), "+f"(d[29]), "+f"(d[30]), "+f"(d[31]), "+f"(d[32]), "+f"(d[33]), "+f"(d[34]), "+f"(d[35]), "+f"(d[36]), "+f"(d[37]), "+f"(d[38]), "+f"(d[39]), "+f"(d[40]), "+f"(d[41]), "+f"(d[42]), "+f"(d[43]), "+f"(d[44]), "+f"(d[45]), "+f"(d[46]), "+f"(d[47]), "+f"(d[48]), "+f"(d[49]), "+f"(d[50]), "+f"(d[51]), "+f"(d[52]), "+f"(d[53]), "+f"(d[54]), "+f"(d[55]), "+f"(d[56]), "+f"(d[57]), "+f"(d[58]), "+f"(d[59]), "+f"(d[60]), "+f"(d[61]), "+f"(d[62]), "+f"(d[63]), "+f"(d[64]), "+f"(d[65]), "+f"(d[66]), "+f"(d[67]), "+f"(d[68]), "+f"(d[69]), "+f"(d[70]), "+f"(d[71]), "+f"(d[72]), "+f"(d[73]), "+f"(d[74]), "+f"(d[75]), "+f"(d[76]), "+f"(d[77]), "+f"(d[78]), "+f"(d[79]), "+f"(d[80]), "+f"(d[81]), "+f"(d[82]), "+f"(d[83]), "+f"(d[84]), "+f"(d[85]), "+f"(d[86]), "+f"(d[87]), "+f"(d[88]), "+f"(d[89]), "+f"(d[90]), "+f"(d[91]), "+f"(d[92]), "+f"(d[93]), "+f"(d[94]), "+f"(d[95])
    : "r"(da), "r"(db));
}

__device__ __forceinline__ uint32_t smem_u32(const void* p) { return (uint32_t)__cvta_generic_to_shared(p); }
__device__ __forceinline__ void mbar_arrive_cluster(uint32_t bar) { asm volatile("mbarrier.arrive.shared::cluster.b64 _, [%0];" :: "r"(bar) : "memory"); }
__device__ __forceinline__ void mbar_wait(uint32_t bar, uint32_t parity) {
  asm volatile(
    "{\n.reg .pred p;\n.reg .u32 n;\n"
    "mbarrier.try_wait.parity.shared::cta.b64 p, [%0], %1;\n"
    "@p bra.uni WAIT_DONE;\n"
    "mov.u32 n, 0;\n"
    "WAIT_LOOP:\n"
    "mbarrier.try_wait.parity.shared::cta.b64 p, [%0], %1;\n"
    "@p bra.uni WAIT_DONE;\n"
    "add.u32 n, n, 1;\n"
    "setp.lt.u32 p, n, 0x100000;\n"
    "@p bra.uni WAIT_LOOP;\n"
    "trap;\n"
    "WAIT_DONE:\n}" :: "r"(bar), "r"(parity) : "memory");
}
__device__ __forceinline__ void mbar_pace(uint32_t bar, uint32_t parity) {
  asm volatile(
    "{\n.reg .pred p;\n.reg .u32 n;\nmov.u32 n, 0;\n"
    "PACE_LOOP:\n"
    "mbarrier.try_wait.parity.shared::cta.b64 p, [%0], %1, 1000;\n"
    "add.u32 n, n, 1;\n"
    "setp.lt.and.u32 p, n, 16, !p;\n"
    "@p bra.uni PACE_LOOP;\n}" :: "r"(bar), "r"(parity) : "memory");
}
__device__ __forceinline__ uint32_t mbar_test(uint32_t bar, uint32_t parity) {
  uint32_t ok;
  asm volatile("{\n.reg .pred p;\nmbarrier.test_wait.parity.shared::cta.b64 p, [%1], %2;\nselp.u32 %0, 1, 0, p;\n}" : "=r"(ok) : "r"(bar), "r"(parity) : "memory");
  return ok;
}
#define ELECT "{\n.reg .pred p;\nelect.sync _|p, 0xffffffff;\n"
__device__ __forceinline__ void mbar_init_e(uint32_t bar, uint32_t cnt) { asm volatile(ELECT "@p mbarrier.init.shared::cta.b64 [%0], %1;\n}" :: "r"(bar), "r"(cnt) : "memory"); }
__device__ __forceinline__ void mbar_arrive_e(uint32_t bar) { asm volatile(ELECT "@p mbarrier.arrive.shared::cta.b64 _, [%0];\n}" :: "r"(bar) : "memory"); }
__device__ __forceinline__ void mbar_expect_e(uint32_t bar, uint32_t bytes) { asm volatile(ELECT "@p mbarrier.arrive.expect_tx.shared::cta.b64 _, [%0], %1;\n}" :: "r"(bar), "r"(bytes) : "memory"); }
__device__ __forceinline__ void tma_ld4_e(uint32_t dst, const CUtensorMap* m, uint32_t bar, int c0, int c3) {
  asm volatile(ELECT "@p cp.async.bulk.tensor.4d.shared::cluster.global.mbarrier::complete_tx::bytes [%0], [%1, {%3, %5, %5, %4}], [%2];\n}"
    :: "r"(dst), "l"(m), "r"(bar), "r"(c0), "r"(c3), "r"(0) : "memory");
}
__device__ __forceinline__ void tma_ld4_mc_e(uint32_t dst, const CUtensorMap* m, uint32_t bar, int c0, int c3, uint16_t mask = 3) {
  asm volatile(ELECT "@p cp.async.bulk.tensor.4d.shared::cluster.global.mbarrier::complete_tx::bytes.multicast::cluster [%0], [%1, {%3, %5, %5, %4}], [%2], %6;\n}"
    :: "r"(dst), "l"(m), "r"(bar), "r"(c0), "r"(c3), "r"(0), "h"(mask) : "memory");
}
__device__ __forceinline__ void tma_ld3_e(uint32_t dst, const CUtensorMap* m, uint32_t bar, int c0, int c1, int c2) {
  asm volatile(ELECT "@p cp.async.bulk.tensor.3d.shared::cluster.global.mbarrier::complete_tx::bytes [%0], [%1, {%3, %4, %5}], [%2];\n}"
    :: "r"(dst), "l"(m), "r"(bar), "r"(c0), "r"(c1), "r"(c2) : "memory");
}
__device__ __forceinline__ void tma_st4_e(const CUtensorMap* m, uint32_t src, int c0, int c3) {
  asm volatile(ELECT "@p cp.async.bulk.tensor.4d.global.shared::cta.bulk_group [%0, {%2, %4, %4, %3}], [%1];\n}"
    :: "l"(m), "r"(src), "r"(c0), "r"(c3), "r"(0) : "memory");
}
__device__ __forceinline__ void dsmem_copy_e(uint32_t dst, uint32_t src, uint32_t bar) {
  asm volatile(ELECT "@p cp.async.bulk.shared::cluster.shared::cta.mbarrier::complete_tx::bytes [%0], [%1], 16384, [%2];\n}"
    :: "r"(dst), "r"(src), "r"(bar) : "memory");
}
__device__ __forceinline__ void bulk_wait_read_e() { asm volatile(ELECT "@p cp.async.bulk.commit_group;\n@p cp.async.bulk.wait_group.read 0;\n}" ::: "memory"); __syncwarp(); }
__device__ __forceinline__ void publish_e(unsigned* flag, unsigned tag) {
  asm volatile(ELECT "@p fence.proxy.async;\n@p st.relaxed.gpu.global.u32 [%0], %1;\n}" :: "l"(flag), "r"(tag) : "memory");
  __syncwarp();
}
__device__ __forceinline__ void fence_async_smem() { asm volatile("fence.proxy.async.shared::cta;" ::: "memory"); }
__device__ __forceinline__ void wgmma_fence() { asm volatile("wgmma.fence.sync.aligned;" ::: "memory"); }
__device__ __forceinline__ void wgmma_commit() { asm volatile("wgmma.commit_group.sync.aligned;" ::: "memory"); }
template<int N> __device__ __forceinline__ void wgmma_wait() { asm volatile("wgmma.wait_group.sync.aligned %0;" :: "n"(N) : "memory"); }
__device__ __forceinline__ void bar_sync(int id, int n) { asm volatile("bar.sync %0, %1;" :: "r"(id), "r"(n) : "memory"); }
__device__ __forceinline__ void bar_arrive(int id, int n) { asm volatile("bar.arrive %0, %1;" :: "r"(id), "r"(n) : "memory"); }
__device__ __forceinline__ void bar_arrive_after(int id, uint32_t dep) {
  asm volatile("{\n.reg .u32 n;\nor.b32 n, %1, 256;\nmin.u32 n, n, 256;\nbar.arrive %0, n;\n}" :: "r"(id), "r"(dep) : "memory");
}
__device__ __forceinline__ void bar_arrive_here(int id, float dep, float zero) {
  asm volatile("{\n.reg .pred p;\n.reg .u32 n;\nsetp.ne.u32 p, %2, 0;\nor.b32 n, %1, 256;\nmin.u32 n, n, 256;\nAGAIN:\nbar.arrive %0, n;\n@p bra.uni AGAIN;\n}"
    :: "r"(id), "r"(__float_as_uint(dep)), "r"(__float_as_uint(zero)) : "memory");
}
__device__ __forceinline__ void bar_sync_after(int id, uint32_t dep) {
  asm volatile("{\n.reg .u32 n;\nor.b32 n, %1, 256;\nmin.u32 n, n, 256;\nbar.sync %0, n;\n}" :: "r"(id), "r"(dep) : "memory");
}
__device__ __forceinline__ uint32_t mapa(uint32_t a, uint32_t r) { uint32_t d; asm("mapa.shared::cluster.u32 %0, %1, %2;" : "=r"(d) : "r"(a), "r"(r)); return d; }
__device__ __forceinline__ void st_tag128(uint4* p, uint32_t a, uint32_t b, uint32_t c, uint32_t tag) {
  asm volatile("{\n.reg .b64 lo, hi;\n.reg .b128 v;\nmov.b64 lo, {%1, %2};\nmov.b64 hi, {%3, %4};\nmov.b128 v, {lo, hi};\nst.relaxed.gpu.global.b128 [%0], v;\n}"
    :: "l"(p), "r"(a), "r"(b), "r"(c), "r"(tag) : "memory");
}
__device__ __forceinline__ void st_tag128_if(bool on, uint4* p, uint32_t a, uint32_t b, uint32_t c, uint32_t tag) {
  asm volatile("{\n.reg .pred q;\n.reg .b64 lo, hi;\n.reg .b128 v;\nsetp.ne.u32 q, %5, 0;\nmov.b64 lo, {%1, %2};\nmov.b64 hi, {%3, %4};\nmov.b128 v, {lo, hi};\n@q st.relaxed.gpu.global.b128 [%0], v;\n}"
    :: "l"(p), "r"(a), "r"(b), "r"(c), "r"(tag), "r"((uint32_t)on) : "memory");
}
__device__ __forceinline__ uint4 ld_tag128(const uint4* p) {
  uint4 v;
  asm volatile("{\n.reg .b64 lo, hi;\n.reg .b128 v;\nld.relaxed.gpu.global.b128 v, [%4];\nmov.b128 {lo, hi}, v;\nmov.b64 {%0, %1}, lo;\nmov.b64 {%2, %3}, hi;\n}"
    : "=r"(v.x), "=r"(v.y), "=r"(v.z), "=r"(v.w) : "l"(p) : "memory");
  return v;
}
__device__ __forceinline__ void st_tag64(uint2* p, float a, uint32_t tag) {
  asm volatile("{\n.reg .b64 v;\nmov.b64 v, {%1, %2};\nst.relaxed.gpu.global.b64 [%0], v;\n}" :: "l"(p), "r"(__float_as_uint(a)), "r"(tag) : "memory");
}
__device__ __forceinline__ uint2 ld_tag64(const uint2* p) {
  uint2 v;
  asm volatile("{\n.reg .b64 v;\nld.relaxed.gpu.global.b64 v, [%2];\nmov.b64 {%0, %1}, v;\n}" : "=r"(v.x), "=r"(v.y) : "l"(p) : "memory");
  return v;
}
__device__ __forceinline__ uint32_t pack_bf16(float lo, float hi) { uint32_t r; asm("cvt.rn.bf16x2.f32 %0, %1, %2;" : "=r"(r) : "f"(hi), "f"(lo)); return r; }
__device__ __forceinline__ uint32_t relu_sq_bf16(float lo, float hi) {
  uint32_t r; asm("{\n.reg .b32 t;\ncvt.rn.relu.bf16x2.f32 t, %1, %2;\nmul.rn.bf16x2 %0, t, t;\n}" : "=r"(r) : "f"(hi), "f"(lo)); return r;
}
__device__ __forceinline__ float bf_lo(uint32_t u) { return __uint_as_float(u << 16); }
__device__ __forceinline__ float bf_hi(uint32_t u) { return __uint_as_float(u & 0xffff0000u); }
__device__ __forceinline__ void stmatrix4(uint32_t addr, uint32_t r0, uint32_t r1, uint32_t r2, uint32_t r3) {
  asm volatile("stmatrix.sync.aligned.m8n8.x4.shared.b16 [%0], {%1, %2, %3, %4};" :: "r"(addr), "r"(r0), "r"(r1), "r"(r2), "r"(r3) : "memory");
}
__device__ __forceinline__ void ldmatrix4(uint32_t addr, uint32_t (&r)[4]) {
  asm volatile("ldmatrix.sync.aligned.m8n8.x4.shared.b16 {%0, %1, %2, %3}, [%4];" : "=r"(r[0]), "=r"(r[1]), "=r"(r[2]), "=r"(r[3]) : "r"(addr) : "memory");
}
__device__ __forceinline__ void stmatrix4_t(uint32_t addr, uint32_t r0, uint32_t r1, uint32_t r2, uint32_t r3) {
  asm volatile("stmatrix.sync.aligned.m8n8.x4.trans.shared.b16 [%0], {%1, %2, %3, %4};" :: "r"(addr), "r"(r0), "r"(r1), "r"(r2), "r"(r3) : "memory");
}
__device__ __forceinline__ void ldmatrix4_t(uint32_t addr, uint32_t (&r)[4]) {
  asm volatile("ldmatrix.sync.aligned.m8n8.x4.trans.shared.b16 {%0, %1, %2, %3}, [%4];" : "=r"(r[0]), "=r"(r[1]), "=r"(r[2]), "=r"(r[3]) : "r"(addr) : "memory");
}
__device__ __forceinline__ uint32_t movmatrix(uint32_t a) { uint32_t d; asm volatile("movmatrix.sync.aligned.m8n8.trans.b16 %0, %1;" : "=r"(d) : "r"(a)); return d; }
__device__ __forceinline__ void mma16816_z(float (&c)[4], uint32_t a0, uint32_t a1, uint32_t a2, uint32_t a3, uint32_t b0, uint32_t b1, const float4& z) {
  asm volatile("mma.sync.aligned.m16n8k16.row.col.f32.bf16.bf16.f32 {%0,%1,%2,%3}, {%4,%5,%6,%7}, {%8,%9}, {%10,%11,%12,%13};"
    : "=f"(c[0]), "=f"(c[1]), "=f"(c[2]), "=f"(c[3]) : "r"(a0), "r"(a1), "r"(a2), "r"(a3), "r"(b0), "r"(b1), "f"(z.x), "f"(z.y), "f"(z.z), "f"(z.w));
}
__device__ __forceinline__ float ex2(float x) { float y; asm("ex2.approx.ftz.f32 %0, %1;" : "=f"(y) : "f"(x)); return y; }
__device__ __forceinline__ float rcp(float x) { float y; asm("rcp.approx.ftz.f32 %0, %1;" : "=f"(y) : "f"(x)); return y; }
__device__ __forceinline__ void mma16816(float (&c)[4], uint32_t a0, uint32_t a1, uint32_t a2, uint32_t a3, uint32_t b0, uint32_t b1) {
  asm volatile("mma.sync.aligned.m16n8k16.row.col.f32.bf16.bf16.f32 {%0,%1,%2,%3}, {%4,%5,%6,%7}, {%8,%9}, {%0,%1,%2,%3};"
    : "+f"(c[0]), "+f"(c[1]), "+f"(c[2]), "+f"(c[3]) : "r"(a0), "r"(a1), "r"(a2), "r"(a3), "r"(b0), "r"(b1));
}
__device__ __forceinline__ void sts128(uint32_t a, uint32_t x, uint32_t y, uint32_t z, uint32_t w) { asm volatile("st.shared.v4.b32 [%0], {%1,%2,%3,%4};" :: "r"(a), "r"(x), "r"(y), "r"(z), "r"(w) : "memory"); }
__device__ __forceinline__ float2 lds64f(uint32_t a) { float2 v; asm volatile("ld.shared.v2.f32 {%0,%1}, [%2];" : "=f"(v.x), "=f"(v.y) : "r"(a) : "memory"); return v; }
__device__ __forceinline__ float4 lds128f(uint32_t a) { float4 v; asm volatile("ld.shared.v4.f32 {%0,%1,%2,%3}, [%4];" : "=f"(v.x), "=f"(v.y), "=f"(v.z), "=f"(v.w) : "r"(a) : "memory"); return v; }
__device__ __forceinline__ void sts32f(uint32_t a, float v) { asm volatile("st.shared.f32 [%0], %1;" :: "r"(a), "f"(v) : "memory"); }
__device__ __forceinline__ void sts64f(uint32_t a, float x, float y) { asm volatile("st.shared.v2.f32 [%0], {%1,%2};" :: "r"(a), "f"(x), "f"(y) : "memory"); }
__device__ __forceinline__ uint32_t lds32(uint32_t a) { uint32_t v; asm volatile("ld.shared.u32 %0, [%1];" : "=r"(v) : "r"(a) : "memory"); return v; }
__device__ __forceinline__ float after(float x, uint32_t d, uint32_t zero) { return __uint_as_float(__float_as_uint(x) | (d & zero)); }
template<int R> __device__ __forceinline__ void reg_alloc() { asm volatile("setmaxnreg.inc.sync.aligned.u32 %0;" :: "n"(R)); }
template<int R> __device__ __forceinline__ void reg_dealloc() { asm volatile("setmaxnreg.dec.sync.aligned.u32 %0;" :: "n"(R)); }

struct Ctx {
  uint32_t sb;
  int m, j, b, rank, wg, w, lane;
};

__device__ __forceinline__ unsigned smem_tag(const Ctx& c) { return lds32(c.sb + OFF_TAG); }
__device__ __forceinline__ int smem_block(const Ctx& c) { return lds32(c.sb + OFF_TAG + 8); }

struct WTile { int map, c0, c2; };
__host__ __device__ constexpr WTile wtile(int type, int j) {
  return WTile{128 * (type < 2 ? 5 : type < 5 ? type + 4 : type + 3), type < 2 ? (j + 8 * type) * 64 : 0,
               type < 2 ? 0 : type == 3 ? 3 * j : type == 4 ? 24 + 2 * j : type == 5 ? 40 + 2 * j : 2 * j};
}
__host__ __device__ constexpr int first_stage(int type, int part) { return ((part == 0 ? 0x2000422 : part == 1 ? 0x2 : 0x2002) >> (4 * type)) & 7; }

enum { A_NEW = 1 << 9, A_QUIET = 1 << 10, A_NONE = 1 << 11, A_PAIR = 2 << 11, A_COPY = 3 << 11 };
struct Plan {
  unsigned epoch[256];
  uint32_t v[8][PLAN_BYTES / 4];
};
constexpr Plan make_plan() {
  Plan plan{};
  for (int j = 0; j < 8; j++)
    for (int g = 4; g < 2 * KB_LAYER; g++) {
      const int layer = g >= KB_LAYER, r = g - layer * KB_LAYER;
      const bool split = (r >= 48 && r < 80) || (layer && r < 32);
      const int q = r - (r >= 48 ? 48 : 0);
      const bool head = split && q < 4, second = split && (head ? q >= 2 : q >= 18), lead = split && !second;
      const int type = split ? (r >= 48 ? 3 : 0) + second : r < 96 ? r >> 4 : 6, t = layer * 7 + type;
      const int step = !split ? r - 16 * type : head ? q & 1 : q - (second ? 16 : 2), n = step - (split && !head ? 2 : 0);
      const bool wide = type < 2 || type == 3;
      const int ns = wide || head ? 4 : 5, lag = type == 2 ? 3 : 4;
      const int e = g - (n + 1 > ns ? ns : n + 1 > lag ? n + 1 : lag);
      const int v = (int)(0xfb7d95ea6c842310ull >> (4 * (step & 15))) & 15;
      const int kb = split ? (v < 4 ? (j * 2) ^ v : ((j >> 1) * 4 + v) & 15) : type != 2 || step < 8 ? step : step < 10 ? j ^ step : 8 + (((j & 6) + step) & 7);
      const uint32_t x = ((e >> 3) & 1) + (e & 7) * 8 + kb * 64 + (first_stage(type, head ? 1 : 2 * split) + n) % ns * (163840 / ns);
      const bool local = type == 2 && (step >> 1) == 4;
      const int act = split && step < 4 ? (head || lead ? A_NONE : A_PAIR) : local ? (step == 8 ? A_NONE : A_COPY) : 0;
      const uint32_t piece = type == 6 ? (step < 24 ? step / 3 : (step >> 1) - 4) : (type == 2 ? !local : lead ? step >= 4 : second && step == 2) ? kb : 31;
      const WTile w = wtile(type, j);
      uint32_t* d = plan.v[j] + (g - 4) * 4;
      d[0] = x + (act ? 0 : (j & 1) * 8192) + (piece << 27);
      d[1] = (!head ? A_BYTES : lead ? 4 : 0) + (type == 2 || type == 6 ? 256 : t < 2 ? 0 : 128) + act + (n == 0 && !second ? A_NEW : 0) +
             (step == (local ? 8 : lead ? 2 : -1) ? A_QUIET : 0) + ((uint32_t)(t - second) << 27);
      d[2] = x + (head && !wide ? 0 : A_BYTES) + ((uint32_t)w.c2 << 26);
      d[3] = w.c0 + (wide ? 24576 : 16384) + (w.map << 16);
    }
  return plan;
}
__device__ __align__(128) Plan g_plan = make_plan();

template<int NL>
__device__ __forceinline__ void row_stats(const Ctx& c, int t) {
  const int ln = t / 3;
  const unsigned tag = smem_tag(c);
  const int row = c.w * 32 + c.lane + lds32(c.sb + OFF_ZERO);
  float s = 0.f, q = 0.f;
  const uint32_t xr = c.sb + OFF_X + row * 128 + (row & 7) * 16;
#pragma unroll 1
  for (int i = 0; i < 128; i += 16) {
    const float4 v = lds128f(xr ^ i), w = lds128f((xr ^ i) + A_BYTES);
    const float u[8] = {v.x, v.y, v.z, v.w, w.x, w.y, w.z, w.w};
#pragma unroll
    for (int z = 0; z < 16; z++) { const float x = z & 1 ? bf_hi(__float_as_uint(u[z >> 1])) : bf_lo(__float_as_uint(u[z >> 1])); s += x; q = fmaf(x, x, q); }
  }
  if (NL == 8) TL(-1, 6);
  if (NL == 4) mbar_pace(c.sb + OFF_FULL + 8 * SA, ln >> 1);
  const int b = smem_block(c);
  st_tag128(g_stats + (ln * 128 + b) * 128 + row, __float_as_uint(s), __float_as_uint(q), 0u, tag);
  mbar_pace(c.sb + (NL == 4 ? OFF_FULL + 8 * (SB & 7) : OFF_EMPTY + 16), (ln >> 1) ^ 1);
  const uint4* p = g_stats + (ln * 128 + (b & ~7)) * 128 + row;
  for (unsigned it = 0;; it++) {
    bool ok = true;
    s = 0.f; q = 0.f;
#pragma unroll 1
    for (int h = 0; h < 8; h += NL) {
      uint4 v[NL];
#pragma unroll
      for (int i = 0; i < NL; i++) v[i] = ld_tag128(p + (h + i) * 128);
#pragma unroll
      for (int i = 0; i < NL; i++) { ok = ok && v[i].w == tag; s += __uint_as_float(v[i].x); q += __uint_as_float(v[i].y); }
    }
    if (__all_sync(0xffffffffu, ok) || it > SPIN_LIMIT) break;
    __nanosleep(NL == 4 ? 400 : 100);
  }
  const float mean = s * (1.0f / D_);
  const float var = fmaxf(q * (1.0f / D_) - mean * mean, 0.0f);
  sts64f(c.sb + OFF_RST + row * 8, rsqrtf(var + 1e-5f), -mean);
  if ((EXP & 256) && NL == 8) sts32f(c.sb + OFF_TAG + 12, __int_as_float(row + 77));
  if ((EXP & 512) && NL == 4) sts32f(c.sb + OFF_TAG + 12, __int_as_float(row + 77));
  bar_arrive(BAR_EPI + (c.wg ^ 1), 256);
  TL(t - 2, 5);
}

template<int BN, int RES>
__device__ __forceinline__ void mainloop(const Ctx& c, float (&acc)[2][96], int t, int type, int g, int nkb) {
  constexpr int NS = BN == 192 ? 4 : 5, STR = BN == 192 ? 40960 : 32768;
  constexpr int HL = 2;
  const bool split = !RES && (BN == 192 ? t > 1 : type == 4), second = BN == 128 || type == 1;
  int st = first_stage(type, split);
  if (split && second) g -= 14;
  const uint32_t rel = mapa(c.sb + OFF_EMPTY, c.lane & 1);
  const uint32_t sb = (c.sb & 0x3ffffu) >> 4;
  uint32_t da = DESC_A + sb + (split ? OFF_X / 16 : st * (STR / 16)), db = DESC_B + sb + (BN == 128 && split ? -1024 : st * (STR / 16));
  TL(t, 0);
  bar_sync(BAR_START + c.wg, 256);
  if (RES && type == 2 && EARLY == 0) bar_sync(BAR_P1, 256);
  TL(t, 1);
  mbar_wait(c.sb + OFF_FULL + 8 * (g & 7), (g >> 3) & 1);
  TL(t, 2);
  wgmma_fence();
  wgmma_ss<BN, RES>(acc[0], da, db);
  wgmma_ss<BN, RES>(acc[1], da + 64, db);
  if (HL == 2) { wgmma_ss<BN, 1>(acc[0], da + 2, db + 128); wgmma_ss<BN, 1>(acc[1], da + 66, db + 128); }
  wgmma_commit();
  wgmma_fence();
#pragma unroll
  for (int k = HL; k < 4; k++) { wgmma_ss<BN, 1>(acc[0], da + k * 2, db + k * 128); wgmma_ss<BN, 1>(acc[1], da + (64 + k * 2), db + k * 128); }
  wgmma_commit();
  const int pause = BN == 192 && type == 1 ? (split ? PAUSE2 : PAUSE1) : RES && type == 2 && EARLY ? EARLY : nkb;
  int kb = 1, lim = split ? 2 : pause, pass = split ? 2 : t < 13 && type != 1 ? nkb : 0;
  uint32_t other = BAR_START + (c.wg ^ 1), prev = c.lane < 2 ? rel + 8 * (g & 7) : 0;
  asm volatile("" : "+r"(other));
  if (++st == NS) st = 0;
  g++;
  da = DESC_A + sb + (split ? (OFF_X + A_BYTES) / 16 : st * (STR / 16));
  db = DESC_B + sb + (BN == 128 && split ? 1536 : st * (STR / 16));
#pragma unroll 1
  for (;;) {
    mbar_wait(c.sb + OFF_FULL + 8 * (g & 7), (g >> 3) & 1);
    bool more;
#pragma unroll 1
    do {
      wgmma_fence();
      wgmma_ss<BN, 1>(acc[0], da, db);
      wgmma_ss<BN, 1>(acc[1], da + 64, db);
      wgmma_ss<BN, 1>(acc[0], da + 2, db + 128); wgmma_ss<BN, 1>(acc[1], da + 66, db + 128);
      wgmma_commit();
      wgmma_wait<1>();
      if (prev) mbar_arrive_cluster(prev);
      TK(t, kb);
      prev = c.lane < 2 ? rel + 8 * (g & 7) : 0;
      kb++; g++;
      if (++st == NS) st = 0;
      wgmma_fence();
      if (BN == 128 && kb == pass) bar_arrive(other, 256);
      wgmma_ss<BN, 1>(acc[0], da + 4, db + 256); wgmma_ss<BN, 1>(acc[1], da + 68, db + 256);
      if (BN == 192 && kb == pass) bar_arrive(other, 256);
      const uint32_t ok = mbar_test(c.sb + OFF_FULL + 8 * (g & 7), (g >> 3) & 1);
      wgmma_ss<BN, 1>(acc[0], da + 6, db + 384); wgmma_ss<BN, 1>(acc[1], da + 70, db + 384);
      wgmma_commit();
      more = __all_sync(0xffffffffu, ok) && kb != lim;
      da = DESC_A + sb + (RES && type == 2 && kb == 8 ? OFF_STG / 16 : st * (STR / 16));
      db = DESC_B + sb + st * (STR / 16);
    } while (more);
    if (kb != lim) continue;
    if ((RES && !EARLY) || kb == nkb) break;
    if (RES) { bar_sync(BAR_P1, 256); lim = nkb; }
    else if (BN == 128 || kb == 2) {
      wgmma_wait<0>();
      if (prev) mbar_arrive_cluster(prev);
      TK(t, 16);
      if (second) row_stats<4>(c, t);
      g += second ? 14 : 2;
      st = first_stage(type, 2);
      da = DESC_A + sb + st * (STR / 16); db = DESC_B + sb + st * (STR / 16);
      lim = pause; pass = type != 1 ? nkb : 0; prev = 0;
      bar_sync(BAR_START + c.wg, 256);
    } else {
      bar_sync(BAR_P0, 256); bar_sync(BAR_P1, 256);
      lim = kb == pause ? pause + 2 : nkb;
    }
  }
}
__device__ __forceinline__ void release(const Ctx& c, int slot, int lanes = 2) {
  if (c.lane < lanes) mbar_arrive_cluster(mapa(c.sb + OFF_EMPTY, c.lane & 1) + 8 * slot);
}
__device__ __forceinline__ void finish(const Ctx& c, int t, int slot) {
  wgmma_wait<0>();
  release(c, slot);
  TL(t, 3);
}

__device__ __forceinline__ void put_halo(uint32_t addr, bool last, uint32_t a, uint32_t b, uint32_t c, uint32_t d) {
  if (!last) stmatrix4(addr, a, b, c, d);
  else asm volatile("stmatrix.sync.aligned.m8n8.x2.shared.b16 [%0], {%1, %2};\nstmatrix.sync.aligned.m8n8.x1.shared.b16 [%0 + 256], {%3};" :: "r"(addr), "r"(a), "r"(b), "r"(c) : "memory");
}

__device__ __forceinline__ void fetch_halo(const Ctx& c, unsigned tag, int tile) {
  const int v = c.w & 1;
  const uint4* src = g_halo + (tile * 128 + c.b - 8) * 352 + v * 160 + c.lane;
  uint4 G[6];
#pragma unroll
  for (int z = 0; z < 6; z++) G[z] = make_uint4(0u, 0u, 0u, 0u);
  bar_sync(BAR_HGO + v, 64);
  for (unsigned it = 0; c.m > 0; it++) {
    bool ok = true;
#pragma unroll
    for (int z = 0; z < 6; z++) { G[z] = ld_tag128(src + z * 32); ok = ok && G[z].w == tag; }
    if (__all_sync(0xffffffffu, ok) || it > SPIN_LIMIT) break;
  }
#pragma unroll
  for (int z = 0; z < 6; z++) put_halo(c.sb + OFF_STG + c.lane * 16 + (z ? (v * 5 + z) * 384 - 128 : v * 1792), z == 5, G[z].x, G[z].y, G[z].z, G[z].w);
  if (!v) sts32f(c.sb + OFF_RST - 256 + c.lane * 8, __uint_as_float(G[0].z));
  __syncwarp();
  mbar_arrive_e(c.sb + OFF_HALO + 8 * v);
}

template<int SKEW>
__device__ __forceinline__ void conv_qkv(const Ctx& c, float (&acc)[2][96], uint32_t (&P)[3][2][4][4], int t) {
  const int lane = c.lane, w = c.w, g = lane >> 2, cc = lane & 3;
  const int layer = t >= 7;
  const uint32_t sb = (c.sb & 0x3ffffu) >> 4, par = layer ^ 1;
  uint32_t da = DESC_A + sb + 7680 + 64, db = DESC_B + sb + 7680;
#define MMA(i, n) if (SKEW) do { wgmma_ss<192, 1>(acc[i], da, db); \
    asm volatile("add.s32 %0, %0, %2;\nadd.s32 %1, %1, %3;" : "+r"(da), "+r"(db) : "r"((n) == 11 ? 5050 : (n) == 7 ? 2554 : (n) == 3 ? -7686 : 2), "r"((n) == 11 ? 4736 : (n) == 7 ? 2176 : (n) == 3 ? -8064 : 128)); } while (0)
  if (SKEW) {
    mbar_wait(c.sb + OFF_FULL + 40, par);
    wgmma_fence();
    MMA(1, 0); MMA(1, 1); MMA(1, 2); MMA(1, 3);
    wgmma_commit();
    wgmma_wait<1>();
    release(c, 4);
    mbar_wait(c.sb + OFF_FULL + 48, par);
  } else finish(c, t, layer ? 1 : 7);
  MMA(1, 4); MMA(1, 5);
  bar_sync(BAR_EPI + c.wg, 256);
  MMA(1, 6);
  mbar_wait(c.sb + OFF_TBL + 8 * SKEW, 0);
  MMA(1, 7);
  if (SKEW) mbar_wait(c.sb + OFF_FULL + 56, par);
  MMA(1, 8);
  bar_sync(BAR_FREE, 160);
  MMA(1, 9);
  const uint32_t rst = c.sb + OFF_RST + w * 256;
  float mu[4];
#pragma unroll
  for (int r = 0; r < 4; r++) mu[r] = __uint_as_float(lds32(rst + (8 * r + g) * 8 + 4));
  const uint32_t tag = smem_tag(c), rs_l = lds32(rst + lane * 8), zero = SKEW ? 0u : lds32(c.sb + OFF_ZERO);
  const uint32_t csb = c.sb + OFF_CSQ + SKEW * 768 + cc * 16;
  const uint32_t stg = c.sb + OFF_STG + w * 4096;
  const int b = smem_block(c);
  uint4* const halo = g_halo + ((layer * 2 + SKEW) * 128 + b) * 352 + lane;
  const bool send = w == 3 && b < 120;
  float4 cs = lds128f(csb + 4 * 64);
  if (SKEW) {
    MMA(1, 10); MMA(1, 11);
    wgmma_commit();
    MMA(0, 0);
    wgmma_commit();
    MMA(0, 1);
    wgmma_commit();
    wgmma_wait<2>();
  }
  uint32_t d[2] = {0u, 0u};
#define CONV(i, np) do { _Pragma("unroll") for (int z = 0; z < 4; z++) { const int nt = 2 * (np) + (z >> 1), h = z & 1; \
    const float m = 1 ? mu[2 * h + (i)] : after(mu[2 * h + (i)], d[h], zero); \
    d[h] = P[nt >> 3][(nt >> 2) & 1][2 * h + (i)][nt & 3] = pack_bf16(fmaf(z >> 1 ? cs.z : cs.x, m, acc[i][4 * nt + 2 * h]), \
                                                                     fmaf(z >> 1 ? cs.w : cs.y, m, acc[i][4 * nt + 2 * h + 1])); } } while (0)
#define HM(u) P[1 + (((u) >> 4) & 1)][((u) >> 3) & 1][((u) & 2) + 1][(((u) >> 1) & 2) + ((u) & 1)]
#define HW(u) ((u) == 2 ? rs_l : HM((u) - ((u) > 2)))
#pragma unroll
  for (int n = 0; n < 12; n++) {
    const int np = (n + 4) % 12;
    if (n == (SKEW ? HGK : HGO) && w == 0) bar_arrive(BAR_HGO, 64);
    if (n == HGO && w == 0) bar_arrive(BAR_HGO + 1, 64);
    if (SKEW && n == 8) bar_arrive(BAR_START + (c.wg ^ 1), 256);
    if (SKEW && n < 10) { MMA(0, n + 2); wgmma_commit(); }
    CONV(1, np);
    cs = lds128f(csb + (n < 11 ? (n + 5) % 12 : 0) * 64);
#pragma unroll
    for (int z = 0; z < 11; z++)
      if ((3 * z + 1) / 4 == n) {
        st_tag128_if(send, halo + z * 32, HW(3 * z), HW(3 * z + 1), HW(3 * z + 2), tag);
        put_halo(stg + 4096 + lane * 16 + (z ? z * 384 - 128 : 0), z == 10, HW(3 * z), HW(3 * z + 1), HW(3 * z + 2), tag);
      }
    if (SKEW && n < 10) wgmma_wait<2>();
    if (SKEW && (n == 3 || n == 7)) release(c, 5 + (n >> 2));
  }
#undef MMA
#undef HW
#undef HM
  if (SKEW) {
    wgmma_wait<0>();
    release(c, 7, w || !REL ? 2 : 0);
    TL(t, 3);
  }
#pragma unroll
  for (int np = 0; np < 12; np++) {
    CONV(0, np);
    if (np < 11) cs = lds128f(csb + (np + 1) * 64);
  }
#undef CONV
}

__device__ __forceinline__ void epi_qkv(const Ctx& c, float (&acc)[2][96], int t, int q) {
  const int lane = c.lane, w = c.w, g = lane >> 2, cc = lane & 3;
  uint32_t P[3][2][4][4];
  if (q) conv_qkv<1>(c, acc, P, t); else conv_qkv<0>(c, acc, P, t);
  const uint32_t rst = c.sb + OFF_RST + w * 256, stg = c.sb + OFF_STG + w * 4096;
  const bool nohalo = w == 0 && smem_block(c) < 8;
#pragma unroll
  for (int z = 0; z < 16; z++) P[2][z >> 3][(z >> 1) & 2][z & 3] = movmatrix(P[2][z >> 3][(z >> 1) & 2][z & 3]);
  uint32_t K1[4][4], V1[4][4];
  const uint32_t hl = stg + (lane & 15) * 16 + (lane >> 4) * 512;
#define HZ(z) (((z) >> 1) * 1024 + ((z) & 1) * 256)
  __syncwarp();
#pragma unroll
  for (int z = 0; z < 4; z++) { ldmatrix4(hl + 4096 + HZ(z), K1[z]); ldmatrix4_t(hl + 4096 + 2048 + HZ(z), V1[z]); }
  TL(t, 9);
  bar_sync(BAR_WG + c.wg, 128);
  if (w == 0) { TL(t, 8); mbar_wait(c.sb + OFF_HALO, q); if (!SPL) mbar_wait(c.sb + OFF_HALO + 8, q); if (REL == 1) release(c, 7, 2 * q); }
  uint32_t HK[4][4], HV[4][4];
#pragma unroll
  for (int z = 0; z < 4; z++) ldmatrix4(hl + HZ(z), HK[z]);
#pragma unroll
  for (int z = 0; z < 4; z++) if (!SPL) ldmatrix4_t(hl + 2048 + HZ(z), HV[z]);
  const bool far0 = 2 * cc > g, far1 = 2 * cc + 1 > g;
  float rk[4][2], sc[4][2];
#pragma unroll
  for (int r = 0; r < 4; r++) {
    const float rq = __uint_as_float(lds32(rst + (8 * r + g) * 8)) * (0.17677669529663687f * 1.4426950408889634f);
    const int back = r & 1 ? 64 : 192;
    rk[r][0] = __uint_as_float(lds32(rst + r * 64 + cc * 16 - (far0 ? back : 0)));
    rk[r][1] = __uint_as_float(lds32(rst + r * 64 + cc * 16 + 8 - (far1 ? back : 0)));
    sc[r][0] = rq * rk[r][0]; sc[r][1] = rq * rk[r][1];
  }
  TL(t, 4);
  float S[4][3][4];
  if (q == 0) bar_sync(BAR_P0, 256);
  float4 zero = lds128f(c.sb + OFF_ZERO);
#pragma unroll
  for (int k = 0; k < 2; k++)
#pragma unroll
    for (int z = 0; z < 4; z++) {
      const uint32_t* qa = P[0][z >> 1][2 * (z & 1)]; const uint32_t* qb = P[0][z >> 1][2 * (z & 1) + 1];
      const uint32_t* kk[3] = {HK[z], P[1][z >> 1][2 * (z & 1)], K1[z]};
#pragma unroll
      for (int n = 0; n < 3; n++) {
        if (k == 0) mma16816_z(S[z][n], qa[0], qb[0], qa[1], qb[1], kk[n][0], kk[n][1], zero);
        else mma16816(S[z][n], qa[2], qb[2], qa[3], qb[3], kk[n][2], kk[n][3]);
        if (NS && q == 0 && k * 12 + z * 3 + n + 1 == NS) bar_arrive_here(BAR_P1, S[NS > 12 ? 3 : 0][0][0], zero.x);
      }
    }
  if (q == 0 && !NS) {
    uint32_t dep = 0;
#pragma unroll
    for (int z = 0; z < 12; z++) dep |= __float_as_uint(S[z / 3][z % 3][0]);
    bar_arrive_after(BAR_P1, dep);
  }
  TL(t, 10);
  const uint32_t fmask = (far0 ? 0xffffu : 0u) | (far1 ? 0xffff0000u : 0u);
  uint32_t pf[4][2], pn[4][2];
#pragma unroll
  for (int z = 0; z < 4; z++)
#pragma unroll
    for (int i = 0; i < 2; i++) {
      const int r = 2 * (z & 1) + i;
      float l0 = (far0 ? S[z][i][2 * i] : S[z][i + 1][2 * i]) * sc[r][0];
      float l1 = (far1 ? S[z][i][2 * i + 1] : S[z][i + 1][2 * i + 1]) * sc[r][1];
      if (i == 0 && nohalo) { const float neg = -1e9f * 1.4426950408889634f; if (far0) l0 = neg; if (far1) l1 = neg; }
      float mx = fmaxf(l0, l1);
      mx = fmaxf(mx, __shfl_xor_sync(0xffffffffu, mx, 1));
      mx = fmaxf(mx, __shfl_xor_sync(0xffffffffu, mx, 2));
      l0 = ex2(l0 - mx); l1 = ex2(l1 - mx);
      float sum = l0 + l1;
      l0 *= rk[r][0]; l1 *= rk[r][1];
      sum += __shfl_xor_sync(0xffffffffu, sum, 1);
      sum += __shfl_xor_sync(0xffffffffu, sum, 2);
      sum = rcp(sum);
      const uint32_t u = pack_bf16(l0 * sum, l1 * sum);
      pf[z][i] = u & fmask; pn[z][i] = u & ~fmask;
    }
  float O[4][2][2][4];
  TL(t, 11);
  if (SPL && w == 0) { mbar_wait(c.sb + OFF_HALO + 8, q); if (REL == 2) release(c, 7, 2 * q); TL(t, 12); }
#pragma unroll
  for (int z = 0; z < 4; z++) if (SPL) ldmatrix4_t(hl + 2048 + HZ(z), HV[z]);
#undef HZ
  if (q == 0) bar_sync_after(BAR_P0, (pn[0][0] | pn[0][1] | pn[1][0]) | (pn[1][1] | pn[2][0] | pn[2][1]) | (pn[3][0] | pn[3][1]));
  zero = lds128f(c.sb + OFF_ZERO);
#pragma unroll
  for (int z = 0; z < 4; z++)
#pragma unroll
    for (int d = 0; d < 2; d++) {
      const uint32_t* v0 = P[2][z >> 1][2 * (z & 1)] + 2 * d;
      mma16816_z(O[z][0][d], HV[z][2 * d], HV[z][2 * d + 1], v0[0], v0[1], pf[z][0], pn[z][0], zero);
      mma16816_z(O[z][1][d], v0[0], v0[1], V1[z][2 * d], V1[z][2 * d + 1], pf[z][1], pn[z][1], zero);
      if (z * 4 + d * 2 + 2 == NP) bar_arrive_here(BAR_P1, O[0][0][0][0], zero.x);
    }
  if (!NP) {
    uint32_t dep = 0;
#pragma unroll
    for (int z = 0; z < 16; z++) dep |= __float_as_uint(O[z >> 2][(z >> 1) & 1][z & 1][0]);
    bar_arrive_after(BAR_P1, dep);
  }
  TL(t, 5);
#pragma unroll
  for (int nt = 0; nt < 8; nt++) {
    uint32_t u[4];
#pragma unroll
    for (int r = 0; r < 4; r++) { const float* o = O[2 * (nt >> 2) + (r >> 1)][r & 1][(nt >> 1) & 1] + 2 * (nt & 1); u[r] = pack_bf16(o[0], o[1]); }
    stmatrix4_t(stg + lane * 128 + ((nt ^ (lane & 7)) << 4), u[0], u[1], u[2], u[3]);
  }
  fence_async_smem();
  bar_arrive(BAR_READY, 160);
  TL(t, 13);
}

template<int CH>
__device__ __forceinline__ void epi_up(const Ctx& c, float (&acc)[2][96], int type) {
  const int lane = c.lane, w = c.w, g = lane >> 2, cc = lane & 3;
  float rs[4], nm[4];
#pragma unroll
  for (int r = 0; r < 4; r++) { const float2 v = lds64f(c.sb + OFF_RST + (w * 32 + 8 * r + g) * 8); rs[r] = v.x; nm[r] = v.x * v.y; }
  const int loc0 = type == 3 ? 0 : (type == 4 ? 192 : 320);
  const uint32_t cb = c.sb + OFF_UP + loc0 * 8 + cc * 16;
  const uint32_t zero = lds32(c.sb + OFF_ZERO);
  uint32_t d[2] = {0u, 0u};
  const uint32_t stg = c.sb + OFF_STG + w * 4096;
#pragma unroll
  for (int ch = CH; ch < (CH ? 3 : 2); ch++) {
    uint32_t P[8][4];
#pragma unroll
    for (int n8 = 0; n8 < 8; n8++) {
      const int nt = ch * 8 + n8;
      const float4 cv = lds128f(cb + nt * 64);
#pragma unroll
      for (int r = 0; r < 4; r++) {
        const float m = after(nm[r], d[r & 1], zero);
        d[r & 1] = P[n8][r] = relu_sq_bf16(fmaf(acc[r & 1][4 * nt + 2 * (r >> 1)], rs[r], fmaf(cv.x, m, cv.z)),
                                           fmaf(acc[r & 1][4 * nt + 2 * (r >> 1) + 1], rs[r], fmaf(cv.y, m, cv.w)));
      }
    }
    bar_sync(BAR_FREE, 160);
#pragma unroll
    for (int n8 = 0; n8 < 8; n8++)
      stmatrix4(stg + lane * 128 + ((n8 ^ (lane & 7)) << 4), P[n8][0], P[n8][1], P[n8][2], P[n8][3]);
    fence_async_smem();
    bar_arrive(BAR_READY, 160);
  }
}

__device__ __forceinline__ void init_res(const Ctx& c, float (&acc)[2][96], int t, bool bias) {
  if (t == 2) mbar_wait(c.sb + OFF_XBAR, 0);
  const uint32_t xb = c.sb + OFF_X + c.w * 4096 + c.lane * 128;
#pragma unroll
  for (int nt = 0; nt < 16; nt++) {
    uint32_t u[4];
    ldmatrix4(xb + (nt >> 3) * A_BYTES + (((nt & 7) ^ (c.lane & 7)) << 4), u);
    float2 b = make_float2(0.f, 0.f);
    if (bias) b = lds64f(c.sb + OFF_B2 + nt * 32 + (c.lane & 3) * 8);
#pragma unroll
    for (int r = 0; r < 4; r++) {
      acc[r & 1][4 * nt + 2 * (r >> 1)] = bf_lo(u[r]) + b.x;
      acc[r & 1][4 * nt + 2 * (r >> 1) + 1] = bf_hi(u[r]) + b.y;
      asm volatile("" : "+f"(acc[r & 1][4 * nt + 2 * (r >> 1)]), "+f"(acc[r & 1][4 * nt + 2 * (r >> 1) + 1]));
    }
  }
}

__device__ __forceinline__ void epi_res(const Ctx& c, float (&acc)[2][96]) {
  const uint32_t xw = c.sb + OFF_X + c.w * 4096 + c.lane * 128;
#pragma unroll
  for (int nt = 0; nt < 16; nt++) {
    stmatrix4(xw + (nt >> 3) * A_BYTES + (((nt & 7) ^ (c.lane & 7)) << 4),
              pack_bf16(acc[0][4 * nt], acc[0][4 * nt + 1]), pack_bf16(acc[1][4 * nt], acc[1][4 * nt + 1]),
              pack_bf16(acc[0][4 * nt + 2], acc[0][4 * nt + 3]), pack_bf16(acc[1][4 * nt + 2], acc[1][4 * nt + 3]));
    if ((nt & 7) == 7) {
      fence_async_smem();
      __syncwarp();
      asm volatile(ELECT "@p mbarrier.complete_tx.relaxed.cta.shared::cta.b64 [%0], 1;\n}" :: "r"(c.sb + OFF_FULL + (nt & 8)) : "memory");
      bar_arrive(nt < 8 ? BAR_RES : BAR_RES2, 160);
    }
  }
}

__device__ __forceinline__ void load_table(const Ctx& c, const Params& p, int part, unsigned tag) {
  const int i0 = (part < 4 ? part * 192 : 704) + c.lane, n = part < 3 ? 6 : 4;
  const uint2* src = g_cs + c.j * NCS + i0;
  const uint32_t dst = c.sb + OFF_CSQ + (i0 & 1) * 4 + (part < 2 ? (i0 >> 4) * 64 + (i0 & 6) * 8 + (i0 & 8) : 1536 + ((i0 - 384) >> 1) * 16);
  const __nv_bfloat16* bias = p.b1 + (part == 2 ? c.j * 192 : (part == 3 ? 1536 : 2560) + c.j * 128) + c.lane;
  float v[6];
  if (part >= 2) {
#pragma unroll
    for (int k = 0; k < 6; k++) if (k < n) sts32f(dst + k * 256 + 8, __bfloat162float(bias[k * 32]));
  }
  for (unsigned it = 0;; it++) {
    bool ok = true;
#pragma unroll
    for (int k = 0; k < 6; k++) { const uint2 a = ld_tag64(src + (k < n ? k * 32 : 0)); ok = ok && a.y == tag; v[k] = __uint_as_float(a.x); }
    if (__all_sync(0xffffffffu, ok) || it > SPIN_LIMIT) break;
    __nanosleep(200);
  }
#pragma unroll
  for (int k = 0; k < 6; k++) if (k < n) sts32f(dst + k * (part < 2 ? 128 : 256), v[k]);
  __syncwarp();
}

__device__ __forceinline__ void colsum_cta(const Ctx& c, const Params& p, unsigned* epoch) {
  if (c.wg < 2) mbar_init_e(c.sb + OFF_FULL + 32 * c.wg + 8 * c.w, 1);
  sts32f(c.sb + OFF_STG + threadIdx.x * 4, __uint_as_float(0x3f803f80u));
  fence_async_smem();
  __syncthreads();
  if (c.wg == 2) return;
  const unsigned tag = *(volatile unsigned*)epoch + 1;
  const int j = (blockIdx.x - 128) * 2 + c.wg;
  const uint32_t ring = c.sb + c.wg * 98304, full = c.sb + OFF_FULL + 32 * c.wg;
  const uint64_t ones = (uint64_t)(((c.sb + OFF_STG) & 0x3ffffu) >> 4) | (8u << 16) | ((uint64_t)16u << 32);
  float d[3][4];
#pragma unroll 1
  for (int n = -4; n < 80; n++) {
    if (n >= 0) {
      mbar_wait(full + 8 * (n & 3), (n >> 2) & 1);
      const uint64_t da = (uint64_t)(((ring + (n & 3) * 24576) & 0x3ffffu) >> 4) | (64u << 16) | ((uint64_t)(64u | (1u << 30)) << 32);
      wgmma_fence();
#pragma unroll
      for (int k = 0; k < 4; k++)
#pragma unroll
        for (int z = 0; z < 3; z++)
          asm volatile("{\n.reg .pred p;\nsetp.ne.b32 p, %6, 0;\nwgmma.mma_async.sync.aligned.m64n8k16.f32.bf16.bf16 {%0,%1,%2,%3}, %4, %5, p, 1, 1, 1, 0;\n}"
            : "+f"(d[z][0]), "+f"(d[z][1]), "+f"(d[z][2]), "+f"(d[z][3]) : "l"(da + z * 512 + k * 128), "l"(ones), "r"((n & 15) | k));
      wgmma_commit();
      wgmma_wait<0>();
      bar_sync(BAR_WG + c.wg, 128);
      if ((n & 15) == 15 && (c.lane & 3) < 2) {
        const int u = n >> 4;
        uint2* out = g_cs + j * NCS + (u < 4 ? u * 192 : 704) + c.w * 16 + (c.lane >> 2) + (c.lane & 1) * 8;
#pragma unroll
        for (int z = 0; z < 3; z++) if (z < 2 || u < 3) st_tag64(out + z * 64, (c.lane & 1) ? d[z][2] : d[z][0], tag);
      }
      __syncwarp();
    }
    if (c.w == 0 && n < 76) {
      const int u = (n + 4) >> 4;
      const WTile w = wtile(u + (u >= 2), j);
      mbar_expect_e(full + 8 * (n & 3), u < 3 ? 24576 : 16384);
      tma_ld3_e(ring + (n & 3) * 24576, (const CUtensorMap*)((const char*)&p + w.map), full + 8 * (n & 3), w.c0, ((n + 4) & 15) * 64, w.c2);
    }
  }
  bar_sync(BAR_START, 256);
  if (threadIdx.x == 0) *epoch = tag;
}

__device__ __forceinline__ void place(Ctx& c, uint32_t slot) {
  const int row = slot < 32 ? slot >> 3 : slot < 60 ? ((slot - 4) * 37) >> 8 : slot - 56;
  const int gpc = slot < 60 ? slot - row * (slot < 32 ? 8 : 7) - (slot < 32 ? 0 : 3) : 0;
  c.m = (gpc & 1) * 8 + row;
  c.j = (gpc & 6) + c.rank; c.b = c.m * 8 + c.j;
}

__global__ void __cluster_dims__(2, 1, 1) __launch_bounds__(384, 1) fused_kernel(unsigned* const epochs, const char* const x0, const char* const w0, const __grid_constant__ Params p) {
  extern __shared__ uint8_t smem_raw[];
  const int tid = threadIdx.x;
  Ctx c;
  c.sb = (smem_u32(smem_raw) + 1023) & ~1023u;
  const int k = __shfl_sync(0xffffffffu, tid >> 5, 0);
  c.wg = k >> 2; c.w = k & 3; c.lane = tid & 31;
  c.rank = blockIdx.x & 1;
  if (blockIdx.x >= 128) { colsum_cta(c, p, epochs + blockIdx.x); return; }
  uint32_t slot; asm volatile("mov.u32 %0, %%smid;" : "=r"(slot));
  slot = __shfl_sync(0xffffffffu, slot < 120 ? slot >> 1 : 60 + ((slot >> 1) & 3), 0);
  if (c.wg == 2) {
    const bool claim = tid == 320 && c.rank == 0;
    unsigned epoch, old;
    asm volatile("{\n.reg .pred p;\nsetp.ne.u32 p, %4, 0;\nmov.u32 %0, 0;\nmov.u32 %1, 0;\n@p atom.relaxed.gpu.global.add.u32 %0, [%2], 1;\n@p ld.relaxed.gpu.global.u32 %1, [%3];\n}"
      : "=r"(old), "=r"(epoch) : "l"(epochs + 132 + slot + c.lane), "l"(epochs + blockIdx.x), "r"((uint32_t)claim) : "memory");
    reg_dealloc<40>();
#pragma unroll 1
    for (int pass = 0;; pass++) {
      place(c, slot);
      if (c.w == 1) {
        asm volatile(ELECT "@p mbarrier.init.shared::cta.b64 [%0], 2;\n@p mbarrier.init.shared::cta.b64 [%0 + 8], 2;\n"
          "@p mbarrier.init.shared::cta.b64 [%0 + 16], 2;\n@p mbarrier.init.shared::cta.b64 [%0 + 24], 2;\n}" :: "r"(c.sb + OFF_FULL) : "memory");
        fence_async_smem();
        if (!pass) asm volatile("fence.mbarrier_init.release.cluster;\nbarrier.cluster.arrive.relaxed.aligned;" ::: "memory");
#pragma unroll 1
        for (int s = pass ? 0 : 2; s < 4; s++) {
          const uint32_t full = c.sb + OFF_FULL + 8 * s, dst = c.sb + (s ^ 2) * 40960;
          mbar_expect_e(full, 40960);
          tma_ld4_e(dst, &p.ld_x, full, s * 64, c.m * 4);
          tma_ld4_e(dst + 8192, &p.ld_x, full, s * 64, c.m * 4 + 2);
          tma_ld3_e(dst + A_BYTES, &p.w_qkv, full, c.j * 64, s * 64, 0);
          mbar_arrive_e(full);
        }
      } else if (!pass) {
        if (c.w == 2) { mbar_init_e(c.sb + OFF_SLOT, 1); mbar_expect_e(c.sb + OFF_SLOT, 8); }
        asm volatile("fence.mbarrier_init.release.cluster;\nbarrier.cluster.arrive.relaxed.aligned;" ::: "memory");
      }
      if (c.w == 0) {
        asm volatile("cp.async.wait_all;" ::: "memory");
#pragma unroll
        for (int i = 0; i < PLAN_BYTES; i += 512)
          asm volatile("cp.async.cg.shared.global [%0], [%1], 16;" :: "r"(c.sb + OFF_PLAN + c.lane * 16 + i), "l"(epochs + 256 + c.j * (PLAN_BYTES / 4) + c.lane * 4 + i / 4) : "memory");
      }
      if (c.w == 3) sts32f(c.sb + OFF_TAG + 8, __int_as_float(c.b));
      if (pass) { bar_sync(BAR_START, 256); break; }
      asm volatile("barrier.cluster.wait.aligned;" ::: "memory");
      if (claim) {
        uint32_t s = slot;
        for (int it = 0; old != epoch && it < 64; it++) { atomicSub(epochs + 132 + s, 1u); s = (s + 1) & 63; old = atomicAdd(epochs + 132 + s, 1u); }
#pragma unroll
        for (int r = 0; r < 2; r++)
          asm volatile("{\n.reg .u32 t;\nadd.u32 t, %1, 1;\nst.async.weak.shared::cluster.mbarrier::complete_tx::bytes.v2.b32 [%0], {t, %2}, [%3];\n}"
            :: "r"(mapa(c.sb + OFF_TAG, r)), "r"(old), "r"(s), "r"(mapa(c.sb + OFF_SLOT, r)) : "memory");
      }
      __syncwarp();
      mbar_wait(c.sb + OFF_SLOT, 0);
      const uint32_t got = __shfl_sync(0xffffffffu, lds32(c.sb + OFF_TAG + 4), 0);
      if (got == slot) {
        bar_arrive(BAR_START, 256);
#pragma unroll 1
        for (int s = 0; s < 16 && c.w == 3; s += 8) {
          mbar_wait(c.sb + OFF_PRE + s, 0);
          PTL(12, 12 + s / 8);
          fence_async_smem();
          if (c.lane < 2) asm volatile("mbarrier.arrive.shared::cta.b64 _, [%0];" :: "r"(c.sb + OFF_FULL + s) : "memory");
        }
        break;
      }
      slot = got;
      if (c.w == 1)
#pragma unroll 1
        for (int s = 0; s < 4; s++) { mbar_wait(c.sb + (s < 2 ? OFF_PRE : OFF_FULL) + 8 * s, 0); asm volatile(ELECT "@p mbarrier.inval.shared::cta.b64 [%0];\n}" :: "r"(c.sb + OFF_FULL + 8 * s) : "memory"); }
    }
    const unsigned tag = smem_tag(c);
    if (c.w < 2) { asm volatile("cp.async.wait_all;" ::: "memory"); bar_sync(BAR_COPY, 64); PTL(14, 13); }
    if (c.w == 0) {
      const char* fp = (const char*)(g_flags + c.m * 32 + c.lane);
      unsigned ready = 1u << 31;
      float2 nx = lds64f(c.sb + OFF_PLAN);
#pragma unroll 1
      for (int g = 4; g < 2 * KB_LAYER; g++) {
        const uint32_t x = __float_as_uint(nx.x), y = __float_as_uint(nx.y);
        nx = lds64f(c.sb + OFF_PLAN + g * 16 - 48);
        if (y & A_NEW) ready = 1u << 31;
        for (unsigned it = 0; !((ready >> (x >> 27)) & 1) && it < SPIN_LIMIT; it++) {
          unsigned v; asm volatile("ld.relaxed.gpu.global.u32 %0, [%1];" : "=r"(v) : "l"(fp + (y >> 16)) : "memory");
          ready |= __ballot_sync(0xffffffffu, v == tag);
          asm volatile("fence.proxy.async.global;" ::: "memory");
        }
        mbar_wait(c.sb + OFF_EMPTY + (x & 0x38), x & 1);
        const uint32_t full = c.sb + OFF_FULL + 8 * (g & 7), dst = c.sb + (x & 0x3e000);
        const CUtensorMap* mp = (const CUtensorMap*)((const char*)&p + (y & 0x180));
        if (!(y & A_QUIET)) mbar_expect_e(full, y & 0x4004);
        if (!(y & A_COPY)) tma_ld4_mc_e(dst, mp, full, x & 0xfc0, c.m * 4 + c.rank * 2);
        else if (!(y & A_NONE)) { tma_ld4_e(dst, mp, full, x & 0xfc0, c.m * 4); tma_ld4_e(dst + 8192, mp, full, x & 0xfc0, c.m * 4 + 2); }
        else if (y & A_PAIR) {
          const uint32_t peer = mapa(c.sb, c.rank ^ 1);
          mbar_wait(c.sb + OFF_FULL, g < KB_LAYER);
          dsmem_copy_e(peer + 3 * 32768, c.sb + OFF_STG, peer + OFF_FULL + 8);
        }
      }
    } else if (c.w == 1) {
      float2 nx = lds64f(c.sb + OFF_PLAN + 8);
#pragma unroll 1
      for (int g = 4; g < 2 * KB_LAYER; g++) {
        const uint32_t x = __float_as_uint(nx.x), y = __float_as_uint(nx.y);
        nx = lds64f(c.sb + OFF_PLAN + g * 16 - 40);
        mbar_wait(c.sb + OFF_EMPTY + (x & 0x38), x & 1);
        const uint32_t full = c.sb + OFF_FULL + 8 * (g & 7);
        mbar_expect_e(full, y & 0x6000);
        tma_ld3_e(c.sb + (x & 0x3e000), (const CUtensorMap*)((const char*)&p + (y >> 16)), full, y & 0x3c0, x & 0xfc0, x >> 26);
      }
    } else if (c.w == 2) {
      bar_arrive(BAR_FREE, 160);
#pragma unroll 1
      for (int t = 0; t < 14; t++) {
        const int layer = t >= 7, type = t - layer * 7;
        const int slab = c.m * 4;
        unsigned* flag = g_flags + c.m * 32 + c.j;
        if (type == 2 || type == 6) {
          flag += (t + 1) * 512 + c.j;
          bar_sync(BAR_RES, 160);
          tma_st4_e(&p.st_out, c.sb + OFF_X, c.j * 128, slab);
          if (t < 13) {
            bulk_wait_read_e();
            PTL(t, 8);
            publish_e(flag++, tag);
            PTL(t, 9);
            mbar_wait(c.sb + OFF_EMPTY + 56, t == 2);
#pragma unroll
            for (int h = 0; h < 2; h++) tma_ld4_mc_e(c.sb + 3 * 40960 + h * 8192, &p.ld_out, c.sb + OFF_FULL + 40, c.j * 128, slab + 2 * h, 2 - c.rank);
            mbar_wait(c.sb + OFF_FULL + 8 * S1, t != 2);
          }
          if (t == 13) bar_sync(BAR_RES2, 160);
          tma_st4_e(&p.st_out, c.sb + OFF_X + A_BYTES, c.j * 128 + 64, slab);
          bulk_wait_read_e();
          PTL(t, 11);
        } else {
          flag += (layer * 7 + (type < 2 ? 2 : 6)) * 512 + (type < 2 ? type : type - 3) * 8;
          const int col = type < 2 ? (c.j + 8 * type) * 64 : type == 3 ? c.j * 192 : (type == 4 ? 1536 : 2560) + c.j * 128;
#pragma unroll 1
          for (int ch = type == 3 ? -1 : 0; ch < (type < 2 ? 1 : 2); ch++) {
            if (type < 2) fetch_halo(c, tag, layer * 2 + type);
            bar_sync(BAR_READY, 160);
#pragma unroll 1
            for (int z = 0; z < 4; z += PC) {
              if (z && type != 1) bulk_wait_read_e();
              tma_st4_e(&p.st_h, c.sb + OFF_STG + z * 4096, col + (ch < 0 ? 128 : ch * 64), slab + z);
            }
            if (type == 1) { mbar_wait(c.sb + OFF_FULL, layer); mbar_arrive_e(c.sb + OFF_FULL); }
            bulk_wait_read_e();
            if (t < 12 || ch == 0) bar_arrive(BAR_FREE, 160);
          }
          PTL(t, 14);
        }
        if (t < 13) publish_e(flag, tag);
        PTL(t, 6);
      }
      if (c.lane == 0) epochs[blockIdx.x] = tag;
    } else {
      mbar_pace(c.sb + OFF_EMPTY + 8 * (c.m & 3), 0);
      PTL(14, 14);
      mbar_expect_e(c.sb + OFF_XBAR, 32768);
#pragma unroll
      for (int i = 0; i < 4; i++) tma_ld4_e(c.sb + OFF_X + i * 8192, &p.ld_x, c.sb + OFF_XBAR, c.j * 128 + (i >> 1) * 64, c.m * 4 + (i & 1) * 2);
#pragma unroll
      for (int i = 0; i < 4; i++) sts32f(c.sb + OFF_B2 + i * 128 + c.lane * 4, __bfloat162float(p.b2[c.j * 128 + i * 32 + c.lane]));
#pragma unroll 1
      for (int part = 0; part < 7; part++) {
        if (part < 5) {
          load_table(c, p, part, tag);
          mbar_arrive_e(c.sb + OFF_TBL + 8 * part);
          PTL(part, 7);
        }
        if (part < 2 || part > 4) fetch_halo(c, tag, part < 2 ? part : part - 3);
        if ((0x52 >> part) & 1) {
          const uint32_t peer = mapa(c.sb, c.rank ^ 1);
          mbar_expect_e(c.sb + OFF_PEER, A_BYTES);
          bar_sync(BAR_RES2, 160);
          mbar_wait(c.sb + OFF_EMPTY + 56, part == 1);
          uint32_t src = c.sb + OFF_X + A_BYTES + c.lane * 16, dst = peer + 2 * 40960 + c.lane * 16;
          float4 v[4];
#pragma unroll
          for (int z = 0; z < 4; z++) v[z] = lds128f(src + z * 512);
#pragma unroll 1
          for (int i = 0; i < 8; i++, src += 2048, dst += 2048) {
#define PUSH(n) asm volatile("st.async.weak.shared::cluster.mbarrier::complete_tx::bytes.v4.f32 [%0 + %6], {%1, %2, %3, %4}, [%5];" \
              :: "r"(dst), "f"(v[n].x), "f"(v[n].y), "f"(v[n].z), "f"(v[n].w), "r"(peer + OFF_PEER), "n"(n * 512) : "memory"); \
            v[n] = lds128f(src + 2048 + n * 512)
            PUSH(0); PUSH(1); PUSH(2); PUSH(3);
#undef PUSH
          }
          PTL(part == 1 ? 2 : part == 4 ? 6 : 9, 10);
          mbar_wait(c.sb + OFF_PEER, part == 4);
          fence_async_smem();
          mbar_arrive_e(c.sb + OFF_FULL + 32);
        }
      }
    }
  } else {
    place(c, slot);
    const int r = tid >> 3;
    const uint32_t dst = c.sb + 2 * 40960 + r * 128 + ((tid ^ r) & 7) * 16;
    const char* ga = x0 + (c.m * 128 + (r & 15) * 2 + c.wg) * 2048 + (tid & 7) * 16;
    const char* gb = w0 + r * 6144 + c.j * 128 + (tid & 7) * 16;
#pragma unroll
    for (int s = 0; s < 2; s++) {
#pragma unroll
      for (int i = 0; i < 10; i++)
        asm volatile("cp.async.cg.shared.global [%0], [%1], 16;" :: "r"(dst + s * 40960 + i * 4096),
          "l"(i < 4 ? ga + i * 65536 + s * 128 : gb + (2 * s + (i & 1)) * (32 * 6144) + (i / 2 - 2) * 2048) : "memory");
      if (!s) {
        mbar_init_e(c.sb + OFF_EMPTY + 8 * k, 8);
        mbar_init_e(c.sb + (k < 4 ? OFF_XBAR : OFF_FULL) + 8 * k, k < 4 ? 1 : 2);
        if (k < 7) mbar_init_e(c.sb + OFF_XBAR + 32 + 8 * k, k > 4 ? 256 : 1);
        else sts128(c.sb + OFF_ZERO, 0u, 0u, 0u, 0u);
        asm volatile("fence.mbarrier_init.release.cluster;\nbarrier.cluster.arrive.relaxed.aligned;" ::: "memory");
        bar_sync(BAR_EPI, 256);
      }
      asm volatile("cp.async.mbarrier.arrive.noinc.shared::cta.b64 [%0];" :: "r"(c.sb + OFF_PRE + 8 * s) : "memory");
    }
    asm volatile("barrier.cluster.wait.aligned;" ::: "memory");
    reg_alloc<232>();
    if (c.wg) { mbar_wait(c.sb + OFF_XBAR, 0); TL(-1, 4); row_stats<8>(c, 1); }
#pragma unroll 1
    for (int t = c.wg; t < 14; t += 2) {
      const int layer = t >= 7, type = t - layer * 7;
      const int g0 = layer * KB_LAYER + type * 16;
      float acc[2][96];
      if (type == 2 || type == 6) {
        init_res(c, acc, t, type == 6);
        mainloop<128, 1>(c, acc, t, type, g0, type == 6 ? 56 : 16);
        finish(c, t, 7);
        epi_res(c, acc);
        if (t == 13) asm volatile("barrier.cluster.arrive.relaxed.aligned;" ::: "memory");
        TL(t, 4);
        continue;
      }
      if (type < 4) {
        mainloop<192, 0>(c, acc, t, type, g0, type == 1 ? 13 : 16);
        if (type < 2) { epi_qkv(c, acc, t, type); goto done; }
        finish(c, t, 1);
        bar_sync(BAR_EPI + c.wg, 256);
        mbar_wait(c.sb + OFF_TBL + 16, 0);
        epi_up<2>(c, acc, type);
      } else {
        mainloop<128, 0>(c, acc, t, type, g0, 16);
        finish(c, t, 7);
        bar_sync(BAR_EPI + c.wg, 256);
        mbar_wait(c.sb + OFF_TBL + 8 * (type - 1), 0);
      }
      epi_up<0>(c, acc, type);
      TL(t, 4);
    done:
      if (type != 1 && type != 5) bar_arrive(BAR_EPI + (c.wg ^ 1), 256);
    }
    if (c.wg == 1) {
      asm volatile("barrier.cluster.wait.aligned;" ::: "memory");
    }
  }
}

typedef CUresult (*EncodeFn)(CUtensorMap*, CUtensorMapDataType, cuuint32_t, void*, const cuuint64_t*, const cuuint64_t*,
                             const cuuint32_t*, const cuuint32_t*, CUtensorMapInterleave, CUtensorMapSwizzle,
                             CUtensorMapL2promotion, CUtensorMapFloatOOBfill);

void make_map(EncodeFn fn, CUtensorMap* m, const void* ptr, int rank, const cuuint64_t* dims, const cuuint64_t* strides, const cuuint32_t* box) {
  const cuuint32_t es[4] = {1, 1, 1, 1};
  fn(m, CU_TENSOR_MAP_DATA_TYPE_BFLOAT16, rank, const_cast<void*>(ptr), dims, strides, box, es, CU_TENSOR_MAP_INTERLEAVE_NONE,
     CU_TENSOR_MAP_SWIZZLE_128B, CU_TENSOR_MAP_L2_PROMOTION_L2_128B, CU_TENSOR_MAP_FLOAT_OOB_FILL_NONE);
}
void map_rows(EncodeFn fn, CUtensorMap* m, const void* ptr, int cols, int rows, int box_slabs, bool tokens) {
  const cuuint64_t rb = (cuuint64_t)cols * 2;
  const cuuint64_t dims[4] = {(cuuint64_t)cols, 16, 2, (cuuint64_t)(rows / 32)};
  const cuuint64_t st[3] = {tokens ? 2 * rb : rb, tokens ? rb : 16 * rb, 32 * rb};
  const cuuint32_t box[4] = {64, 16, 2, (cuuint32_t)box_slabs};
  make_map(fn, m, ptr, 4, dims, st, box);
}
void map_w(EncodeFn fn, CUtensorMap* m, const void* ptr, int K, int N, int inner, int nch) {
  const cuuint64_t dims[3] = {(cuuint64_t)inner, (cuuint64_t)K, (cuuint64_t)(N / inner)}, st[2] = {(cuuint64_t)N * 2, (cuuint64_t)inner * 2};
  const cuuint32_t box[3] = {64, 64, (cuuint32_t)nch};
  make_map(fn, m, ptr, 3, dims, st, box);
}

}

extern "C" void kernel_launch(void* const* d_in, const int* in_sizes, int n_in, void* d_out, int out_size) {
  (void)in_sizes; (void)n_in; (void)out_size;
  Params p;
  p.b1 = (const __nv_bfloat16*)d_in[5]; p.b2 = (const __nv_bfloat16*)d_in[7];
  void* fnp = nullptr; cudaDriverEntryPointQueryResult qr;
  cudaGetDriverEntryPoint("cuTensorMapEncodeTiled", &fnp, cudaEnableDefault, &qr);
  EncodeFn fn = (EncodeFn)fnp;
  void *h, *epochs;
  cudaGetSymbolAddress(&h, g_h);
  cudaGetSymbolAddress(&epochs, g_plan);
  map_rows(fn, &p.ld_x, d_in[0], D_, S_, 2, true);
  map_rows(fn, &p.ld_out, d_out, D_, S_, 2, true);
  map_rows(fn, &p.ld_h, h, F_, S_, 2, false);
  map_rows(fn, &p.st_h, h, F_, S_, PC, false);
  map_rows(fn, &p.st_out, d_out, D_, S_, 4, true);
  map_w(fn, &p.w_qkv, d_in[1], D_, 3 * D_, D_, 3);
  map_w(fn, &p.w_o, d_in[2], D_, D_, 64, 2);
  map_w(fn, &p.w_1a, d_in[4], D_, F_, 64, 3);
  map_w(fn, &p.w_1b, d_in[4], D_, F_, 64, 2);
  map_w(fn, &p.w_2, d_in[6], F_, D_, 64, 2);
  cudaFuncSetAttribute(fused_kernel, cudaFuncAttributeMaxDynamicSharedMemorySize, SMEM_BYTES);
  fused_kernel<<<132, 384, SMEM_BYTES>>>((unsigned*)epochs, (const char*)d_in[0], (const char*)d_in[1], p);
}
```

```cpp
#include <cuda_runtime.h>
#include <cuda_bf16.h>
#include <cuda.h>
#include <stdint.h>

#define EXP 0
namespace {

constexpr int S_ = 2048, D_ = 1024, F_ = 3584;
constexpr int A_BYTES = 16384;
constexpr int OFF_X   = 163840;
constexpr int OFF_STG = OFF_X + 32768;
constexpr int OFF_CSQ = OFF_STG + 20480;
constexpr int OFF_UP  = OFF_CSQ + 1536;
constexpr int OFF_B2  = OFF_UP + 3584;
constexpr int OFF_RST = OFF_B2 + 512 + 256;
constexpr int OFF_FULL = OFF_RST + 1024;
constexpr int OFF_EMPTY = OFF_FULL + 64;
constexpr int OFF_XBAR = OFF_EMPTY + 64;
constexpr int OFF_TBL = OFF_XBAR + 8;
constexpr int OFF_HALO = OFF_XBAR + 48;
constexpr int OFF_SLOT = OFF_XBAR + 88;
constexpr int OFF_PRE = OFF_XBAR + 72;
constexpr int OFF_ZERO = OFF_XBAR + 96;
constexpr int OFF_TAG = OFF_ZERO + 16;
constexpr int OFF_PLAN = OFF_TAG + 16, PLAN_BYTES = 5120;
constexpr int SMEM_BYTES = OFF_PLAN + PLAN_BYTES + 48 + 1024;
constexpr int KB_LAYER = 6 * 16 + 56;
constexpr int NCS = 384 + 448;
constexpr unsigned SPIN_LIMIT = 1u << 20;
constexpr int NS = 12, NP = 8, SA = 7, SB = 11, PAUSE1 = 7, PAUSE2 = 8, HGK = 8, HGO = 11, HG1 = 3;
constexpr int SK = 3;
constexpr uint32_t DESC_A = 1u << 16, DESC_B = (512u << 16) + A_BYTES / 16;
enum { BAR_START = 1, BAR_EPI = 3, BAR_WG = 5, BAR_P0 = 7, BAR_P1 = 8, BAR_RES = 9, BAR_READY = 10, BAR_FREE = 11, BAR_COPY = 12, BAR_RES2 = 13, BAR_HGO = 14 };

struct Params {
  CUtensorMap ld_x, ld_out, ld_h, st_h, st_out, w_qkv, w_o, w_1a, w_1b, w_2;
  const __nv_bfloat16 *b1, *b2;
};

__device__ __align__(1024) __nv_bfloat16 g_h[S_ * F_];
__device__ __align__(128) uint4 g_stats[4 * S_ * 8];
__device__ __align__(128) uint2 g_cs[8 * NCS];
__device__ __align__(128) uint4 g_halo[4 * 128 * 11 * 32];
__device__ __align__(128) unsigned g_flags[14 * 16 * 32];
#define TL(t, e)
#define PTL(t, e)
#if !defined(TIMELINE) || !(EXP & 8)
#undef TK
#define TK(t, k)
#endif

template<int N, int KEEP> __device__ __forceinline__ void wgmma_ss(float (&d)[96], uint32_t da, uint32_t db);
template<> __device__ __forceinline__ void wgmma_ss<128, 0>(float (&d)[96], uint32_t da, uint32_t db) {
  asm volatile("{\n.reg .pred p;\n.reg .b64 a, b;\nsetp.ne.b32 p, 0, 0;\nmov.b64 a, {%64, 0x40000080};\nmov.b64 b, {%65, 0x40000040};\nwgmma.mma_async.sync.aligned.m64n128k16.f32.bf16.bf16 {%0, %1, %2, %3, %4, %5, %6, %7, %8, %9, %10, %11, %12, %13, %14, %15, %16, %17, %18, %19, %20, %21, %22, %23, %24, %25, %26, %27, %28, %29, %30, %31, %32, %33, %34, %35, %36, %37, %38, %39, %40, %41, %42, %43, %44, %45, %46, %47, %48, %49, %50, %51, %52, %53, %54, %55, %56, %57, %58, %59, %60, %61, %62, %63}, a, b, p, 1, 1, 0, 1;\n}"
    : "=f"(d[0]), "=f"(d[1]), "=f"(d[2]), "=f"(d[3]), "=f"(d[4]), "=f"(d[5]), "=f"(d[6]), "=f"(d[7]), "=f"(d[8]), "=f"(d[9]), "=f"(d[10]), "=f"(d[11]), "=f"(d[12]), "=f"(d[13]), "=f"(d[14]), "=f"(d[15]), "=f"(d[16]), "=f"(d[17]), "=f"(d[18]), "=f"(d[19]), "=f"(d[20]), "=f"(d[21]), "=f"(d[22]), "=f"(d[23]), "=f"(d[24]), "=f"(d[25]), "=f"(d[26]), "=f"(d[27]), "=f"(d[28]), "=f"(d[29]), "=f"(d[30]), "=f"(d[31]), "=f"(d[32]), "=f"(d[33]), "=f"(d[34]), "=f"(d[35]), "=f"(d[36]), "=f"(d[37]), "=f"(d[38]), "=f"(d[39]), "=f"(d[40]), "=f"(d[41]), "=f"(d[42]), "=f"(d[43]), "=f"(d[44]), "=f"(d[45]), "=f"(d[46]), "=f"(d[47]), "=f"(d[48]), "=f"(d[49]), "=f"(d[50]), "=f"(d[51]), "=f"(d[52]), "=f"(d[53]), "=f"(d[54]), "=f"(d[55]), "=f"(d[56]), "=f"(d[57]), "=f"(d[58]), "=f"(d[59]), "=f"(d[60]), "=f"(d[61]), "=f"(d[62]), "=f"(d[63])
    : "r"(da), "r"(db));
}
template<> __device__ __forceinline__ void wgmma_ss<128, 1>(float (&d)[96], uint32_t da, uint32_t db) {
  asm volatile("{\n.reg .pred p;\n.reg .b64 a, b;\nsetp.ne.b32 p, 1, 0;\nmov.b64 a, {%64, 0x40000080};\nmov.b64 b, {%65, 0x40000040};\nwgmma.mma_async.sync.aligned.m64n128k16.f32.bf16.bf16 {%0, %1, %2, %3, %4, %5, %6, %7, %8, %9, %10, %11, %12, %13, %14, %15, %16, %17, %18, %19, %20, %21, %22, %23, %24, %25, %26, %27, %28, %29, %30, %31, %32, %33, %34, %35, %36, %37, %38, %39, %40, %41, %42, %43, %44, %45, %46, %47, %48, %49, %50, %51, %52, %53, %54, %55, %56, %57, %58, %59, %60, %61, %62, %63}, a, b, p, 1, 1, 0, 1;\n}"
    : "+f"(d[0]), "+f"(d[1]), "+f"(d[2]), "+f"(d[3]), "+f"(d[4]), "+f"(d[5]), "+f"(d[6]), "+f"(d[7]), "+f"(d[8]), "+f"(d[9]), "+f"(d[10]), "+f"(d[11]), "+f"(d[12]), "+f"(d[13]), "+f"(d[14]), "+f"(d[15]), "+f"(d[16]), "+f"(d[17]), "+f"(d[18]), "+f"(d[19]), "+f"(d[20]), "+f"(d[21]), "+f"(d[22]), "+f"(d[23]), "+f"(d[24]), "+f"(d[25]), "+f"(d[26]), "+f"(d[27]), "+f"(d[28]), "+f"(d[29]), "+f"(d[30]), "+f"(d[31]), "+f"(d[32]), "+f"(d[33]), "+f"(d[34]), "+f"(d[35]), "+f"(d[36]), "+f"(d[37]), "+f"(d[38]), "+f"(d[39]), "+f"(d[40]), "+f"(d[41]), "+f"(d[42]), "+f"(d[43]), "+f"(d[44]), "+f"(d[45]), "+f"(d[46]), "+f"(d[47]), "+f"(d[48]), "+f"(d[49]), "+f"(d[50]), "+f"(d[51]), "+f"(d[52]), "+f"(d[53]), "+f"(d[54]), "+f"(d[55]), "+f"(d[56]), "+f"(d[57]), "+f"(d[58]), "+f"(d[59]), "+f"(d[60]), "+f"(d[61]), "+f"(d[62]), "+f"(d[63])
    : "r"(da), "r"(db));
}
template<> __device__ __forceinline__ void wgmma_ss<192, 0>(float (&d)[96], uint32_t da, uint32_t db) {
  asm volatile("{\n.reg .pred p;\n.reg .b64 a, b;\nsetp.ne.b32 p, 0, 0;\nmov.b64 a, {%96, 0x40000080};\nmov.b64 b, {%97, 0x40000040};\nwgmma.mma_async.sync.aligned.m64n192k16.f32.bf16.bf16 {%0, %1, %2, %3, %4, %5, %6, %7, %8, %9, %10, %11, %12, %13, %14, %15, %16, %17, %18, %19, %20, %21, %22, %23, %24, %25, %26, %27, %28, %29, %30, %31, %32, %33, %34, %35, %36, %37, %38, %39, %40, %41, %42, %43, %44, %45, %46, %47, %48, %49, %50, %51, %52, %53, %54, %55, %56, %57, %58, %59, %60, %61, %62, %63, %64, %65, %66, %67, %68, %69, %70, %71, %72, %73, %74, %75, %76, %77, %78, %79, %80, %81, %82, %83, %84, %85, %86, %87, %88, %89, %90, %91, %92, %93, %94, %95}, a, b, p, 1, 1, 0, 1;\n}"
    : "=f"(d[0]), "=f"(d[1]), "=f"(d[2]), "=f"(d[3]), "=f"(d[4]), "=f"(d[5]), "=f"(d[6]), "=f"(d[7]), "=f"(d[8]), "=f"(d[9]), "=f"(d[10]), "=f"(d[11]), "=f"(d[12]), "=f"(d[13]), "=f"(d[14]), "=f"(d[15]), "=f"(d[16]), "=f"(d[17]), "=f"(d[18]), "=f"(d[19]), "=f"(d[20]), "=f"(d[21]), "=f"(d[22]), "=f"(d[23]), "=f"(d[24]), "=f"(d[25]), "=f"(d[26]), "=f"(d[27]), "=f"(d[28]), "=f"(d[29]), "=f"(d[30]), "=f"(d[31]), "=f"(d[32]), "=f"(d[33]), "=f"(d[34]), "=f"(d[35]), "=f"(d[36]), "=f"(d[37]), "=f"(d[38]), "=f"(d[39]), "=f"(d[40]), "=f"(d[41]), "=f"(d[42]), "=f"(d[43]), "=f"(d[44]), "=f"(d[45]), "=f"(d[46]), "=f"(d[47]), "=f"(d[48]), "=f"(d[49]), "=f"(d[50]), "=f"(d[51]), "=f"(d[52]), "=f"(d[53]), "=f"(d[54]), "=f"(d[55]), "=f"(d[56]), "=f"(d[57]), "=f"(d[58]), "=f"(d[59]), "=f"(d[60]), "=f"(d[61]), "=f"(d[62]), "=f"(d[63]), "=f"(d[64]), "=f"(d[65]), "=f"(d[66]), "=f"(d[67]), "=f"(d[68]), "=f"(d[69]), "=f"(d[70]), "=f"(d[71]), "=f"(d[72]), "=f"(d[73]), "=f"(d[74]), "=f"(d[75]), "=f"(d[76]), "=f"(d[77]), "=f"(d[78]), "=f"(d[79]), "=f"(d[80]), "=f"(d[81]), "=f"(d[82]), "=f"(d[83]), "=f"(d[84]), "=f"(d[85]), "=f"(d[86]), "=f"(d[87]), "=f"(d[88]), "=f"(d[89]), "=f"(d[90]), "=f"(d[91]), "=f"(d[92]), "=f"(d[93]), "=f"(d[94]), "=f"(d[95])
    : "r"(da), "r"(db));
}
template<> __device__ __forceinline__ void wgmma_ss<192, 1>(float (&d)[96], uint32_t da, uint32_t db) {
  asm volatile("{\n.reg .pred p;\n.reg .b64 a, b;\nsetp.ne.b32 p, 1, 0;\nmov.b64 a, {%96, 0x40000080};\nmov.b64 b, {%97, 0x40000040};\nwgmma.mma_async.sync.aligned.m64n192k16.f32.bf16.bf16 {%0, %1, %2, %3, %4, %5, %6, %7, %8, %9, %10, %11, %12, %13, %14, %15, %16, %17, %18, %19, %20, %21, %22, %23, %24, %25, %26, %27, %28, %29, %30, %31, %32, %33, %34, %35, %36, %37, %38, %39, %40, %41, %42, %43, %44, %45, %46, %47, %48, %49, %50, %51, %52, %53, %54, %55, %56, %57, %58, %59, %60, %61, %62, %63, %64, %65, %66, %67, %68, %69, %70, %71, %72, %73, %74, %75, %76, %77, %78, %79, %80, %81, %82, %83, %84, %85, %86, %87, %88, %89, %90, %91, %92, %93, %94, %95}, a, b, p, 1, 1, 0, 1;\n}"
    : "+f"(d[0]), "+f"(d[1]), "+f"(d[2]), "+f"(d[3]), "+f"(d[4]), "+f"(d[5]), "+f"(d[6]), "+f"(d[7]), "+f"(d[8]), "+f"(d[9]), "+f"(d[10]), "+f"(d[11]), "+f"(d[12]), "+f"(d[13]), "+f"(d[14]), "+f"(d[15]), "+f"(d[16]), "+f"(d[17]), "+f"(d[18]), "+f"(d[19]), "+f"(d[20]), "+f"(d[21]), "+f"(d[22]), "+f"(d[23]), "+f"(d[24]), "+f"(d[25]), "+f"(d[26]), "+f"(d[27]), "+f"(d[28]), "+f"(d[29]), "+f"(d[30]), "+f"(d[31]), "+f"(d[32]), "+f"(d[33]), "+f"(d[34]), "+f"(d[35]), "+f"(d[36]), "+f"(d[37]), "+f"(d[38]), "+f"(d[39]), "+f"(d[40]), "+f"(d[41]), "+f"(d[42]), "+f"(d[43]), "+f"(d[44]), "+f"(d[45]), "+f"(d[46]), "+f"(d[47]), "+f"(d[48]), "+f"(d[49]), "+f"(d[50]), "+f"(d[51]), "+f"(d[52]), "+f"(d[53]), "+f"(d[54]), "+f"(d[55]), "+f"(d[56]), "+f"(d[57]), "+f"(d[58]), "+f"(d[59]), "+f"(d[60]), "+f"(d[61]), "+f"(d[62]), "+f"(d[63]), "+f"(d[64]), "+f"(d[65]), "+f"(d[66]), "+f"(d[67]), "+f"(d[68]), "+f"(d[69]), "+f"(d[70]), "+f"(d[71]), "+f"(d[72]), "+f"(d[73]), "+f"(d[74]), "+f"(d[75]), "+f"(d[76]), "+f"(d[77]), "+f"(d[78]), "+f"(d[79]), "+f"(d[80]), "+f"(d[81]), "+f"(d[82]), "+f"(d[83]), "+f"(d[84]), "+f"(d[85]), "+f"(d[86]), "+f"(d[87]), "+f"(d[88]), "+f"(d[89]), "+f"(d[90]), "+f"(d[91]), "+f"(d[92]), "+f"(d[93]), "+f"(d[94]), "+f"(d[95])
    : "r"(da), "r"(db));
}
template<> __device__ __forceinline__ void wgmma_ss<128, 2>(float (&d)[96], uint32_t da, uint32_t db) {
  asm volatile("{\n.reg .pred p;\n.reg .b64 a, b;\nsetp.ne.b32 p, 2, 0;\nmov.b64 a, {%64, 0x40000040};\nmov.b64 b, {%65, 0x40000040};\nwgmma.mma_async.sync.aligned.m64n128k16.f32.bf16.bf16 {%0, %1, %2, %3, %4, %5, %6, %7, %8, %9, %10, %11, %12, %13, %14, %15, %16, %17, %18, %19, %20, %21, %22, %23, %24, %25, %26, %27, %28, %29, %30, %31, %32, %33, %34, %35, %36, %37, %38, %39, %40, %41, %42, %43, %44, %45, %46, %47, %48, %49, %50, %51, %52, %53, %54, %55, %56, %57, %58, %59, %60, %61, %62, %63}, b, a, p, 1, 1, 1, 0;\n}"
    : "+f"(d[0]), "+f"(d[1]), "+f"(d[2]), "+f"(d[3]), "+f"(d[4]), "+f"(d[5]), "+f"(d[6]), "+f"(d[7]), "+f"(d[8]), "+f"(d[9]), "+f"(d[10]), "+f"(d[11]), "+f"(d[12]), "+f"(d[13]), "+f"(d[14]), "+f"(d[15]), "+f"(d[16]), "+f"(d[17]), "+f"(d[18]), "+f"(d[19]), "+f"(d[20]), "+f"(d[21]), "+f"(d[22]), "+f"(d[23]), "+f"(d[24]), "+f"(d[25]), "+f"(d[26]), "+f"(d[27]), "+f"(d[28]), "+f"(d[29]), "+f"(d[30]), "+f"(d[31]), "+f"(d[32]), "+f"(d[33]), "+f"(d[34]), "+f"(d[35]), "+f"(d[36]), "+f"(d[37]), "+f"(d[38]), "+f"(d[39]), "+f"(d[40]), "+f"(d[41]), "+f"(d[42]), "+f"(d[43]), "+f"(d[44]), "+f"(d[45]), "+f"(d[46]), "+f"(d[47]), "+f"(d[48]), "+f"(d[49]), "+f"(d[50]), "+f"(d[51]), "+f"(d[52]), "+f"(d[53]), "+f"(d[54]), "+f"(d[55]), "+f"(d[56]), "+f"(d[57]), "+f"(d[58]), "+f"(d[59]), "+f"(d[60]), "+f"(d[61]), "+f"(d[62]), "+f"(d[63])
    : "r"(da), "r"(db));
}

__device__ __forceinline__ uint32_t smem_u32(const void* p) { return (uint32_t)__cvta_generic_to_shared(p); }
__device__ __forceinline__ void mbar_arrive_cluster(uint32_t bar) { asm volatile("mbarrier.arrive.shared::cluster.b64 _, [%0];" :: "r"(bar) : "memory"); }
__device__ __forceinline__ void mbar_wait(uint32_t bar, uint32_t parity) {
  asm volatile(
    "{\n.reg .pred p;\n.reg .u32 n;\n"
    "mbarrier.try_wait.parity.shared::cta.b64 p, [%0], %1;\n"
    "@p bra.uni WAIT_DONE;\n"
    "mov.u32 n, 0;\n"
    "WAIT_LOOP:\n"
    "mbarrier.try_wait.parity.shared::cta.b64 p, [%0], %1;\n"
    "@p bra.uni WAIT_DONE;\n"
    "add.u32 n, n, 1;\n"
    "setp.lt.u32 p, n, 0x100000;\n"
    "@p bra.uni WAIT_LOOP;\n"
    "trap;\n"
    "WAIT_DONE:\n}" :: "r"(bar), "r"(parity) : "memory");
}
__device__ __forceinline__ void mbar_pace(uint32_t bar, uint32_t parity) {
  asm volatile(
    "{\n.reg .pred p;\n.reg .u32 n;\nmov.u32 n, 0;\n"
    "PACE_LOOP:\n"
    "mbarrier.try_wait.parity.shared::cta.b64 p, [%0], %1, 1000;\n"
    "add.u32 n, n, 1;\n"
    "setp.lt.and.u32 p, n, 16, !p;\n"
    "@p bra.uni PACE_LOOP;\n}" :: "r"(bar), "r"(parity) : "memory");
}
__device__ __forceinline__ uint32_t mbar_test(uint32_t bar, uint32_t parity) {
  uint32_t ok;
  asm volatile("{\n.reg .pred p;\nmbarrier.test_wait.parity.shared::cta.b64 p, [%1], %2;\nselp.u32 %0, 1, 0, p;\n}" : "=r"(ok) : "r"(bar), "r"(parity) : "memory");
  return ok;
}
#define ELECT "{\n.reg .pred p;\nelect.sync _|p, 0xffffffff;\n"
__device__ __forceinline__ void mbar_init_e(uint32_t bar, uint32_t cnt) { asm volatile(ELECT "@p mbarrier.init.shared::cta.b64 [%0], %1;\n}" :: "r"(bar), "r"(cnt) : "memory"); }
__device__ __forceinline__ void mbar_arrive_e(uint32_t bar) { asm volatile(ELECT "@p mbarrier.arrive.shared::cta.b64 _, [%0];\n}" :: "r"(bar) : "memory"); }
__device__ __forceinline__ void mbar_expect_e(uint32_t bar, uint32_t bytes) { asm volatile(ELECT "@p mbarrier.arrive.expect_tx.shared::cta.b64 _, [%0], %1;\n}" :: "r"(bar), "r"(bytes) : "memory"); }
__device__ __forceinline__ void tma_ld4_e(uint32_t dst, const CUtensorMap* m, uint32_t bar, int c0, int c3) {
  asm volatile(ELECT "@p cp.async.bulk.tensor.4d.shared::cluster.global.mbarrier::complete_tx::bytes [%0], [%1, {%3, %5, %5, %4}], [%2];\n}"
    :: "r"(dst), "l"(m), "r"(bar), "r"(c0), "r"(c3), "r"(0) : "memory");
}
__device__ __forceinline__ void tma_ld4_mc_e(uint32_t dst, const CUtensorMap* m, uint32_t bar, int c0, int c3, uint16_t mask = 3) {
  asm volatile(ELECT "@p cp.async.bulk.tensor.4d.shared::cluster.global.mbarrier::complete_tx::bytes.multicast::cluster [%0], [%1, {%3, %5, %5, %4}], [%2], %6;\n}"
    :: "r"(dst), "l"(m), "r"(bar), "r"(c0), "r"(c3), "r"(0), "h"(mask) : "memory");
}
__device__ __forceinline__ void tma_ld3_e(uint32_t dst, const CUtensorMap* m, uint32_t bar, int c0, int c1, int c2) {
  asm volatile(ELECT "@p cp.async.bulk.tensor.3d.shared::cluster.global.mbarrier::complete_tx::bytes [%0], [%1, {%3, %4, %5}], [%2];\n}"
    :: "r"(dst), "l"(m), "r"(bar), "r"(c0), "r"(c1), "r"(c2) : "memory");
}
__device__ __forceinline__ void tma_st4_e(const CUtensorMap* m, uint32_t src, int c0, int c3) {
  asm volatile(ELECT "@p cp.async.bulk.tensor.4d.global.shared::cta.bulk_group [%0, {%2, %4, %4, %3}], [%1];\n}"
    :: "l"(m), "r"(src), "r"(c0), "r"(c3), "r"(0) : "memory");
}
__device__ __forceinline__ void dsmem_copy_e(uint32_t dst, uint32_t src, uint32_t bar) {
  asm volatile(ELECT "@p cp.async.bulk.shared::cluster.shared::cta.mbarrier::complete_tx::bytes [%0], [%1], 16384, [%2];\n}"
    :: "r"(dst), "r"(src), "r"(bar) : "memory");
}
__device__ __forceinline__ void bulk_wait_read_e() { asm volatile(ELECT "@p cp.async.bulk.commit_group;\n@p cp.async.bulk.wait_group.read 0;\n}" ::: "memory"); __syncwarp(); }
__device__ __forceinline__ void publish_e(unsigned* flag, unsigned tag) {
  asm volatile(ELECT "@p fence.proxy.async;\n@p st.relaxed.gpu.global.u32 [%0], %1;\n}" :: "l"(flag), "r"(tag) : "memory");
  __syncwarp();
}
__device__ __forceinline__ void fence_async_smem() { asm volatile("fence.proxy.async.shared::cta;" ::: "memory"); }
__device__ __forceinline__ void wgmma_fence() { asm volatile("wgmma.fence.sync.aligned;" ::: "memory"); }
__device__ __forceinline__ void wgmma_commit() { asm volatile("wgmma.commit_group.sync.aligned;" ::: "memory"); }
template<int N> __device__ __forceinline__ void wgmma_wait() { asm volatile("wgmma.wait_group.sync.aligned %0;" :: "n"(N) : "memory"); }
__device__ __forceinline__ void bar_sync(int id, int n) { asm volatile("bar.sync %0, %1;" :: "r"(id), "r"(n) : "memory"); }
__device__ __forceinline__ void bar_arrive(int id, int n) { asm volatile("bar.arrive %0, %1;" :: "r"(id), "r"(n) : "memory"); }
__device__ __forceinline__ void bar_arrive_here(int id, float dep, float zero) {
  asm volatile("{\n.reg .pred p;\n.reg .u32 n;\nsetp.ne.u32 p, %2, 0;\nor.b32 n, %1, 256;\nmin.u32 n, n, 256;\nAGAIN:\nbar.arrive %0, n;\n@p bra.uni AGAIN;\n}"
    :: "r"(id), "r"(__float_as_uint(dep)), "r"(__float_as_uint(zero)) : "memory");
}
__device__ __forceinline__ void bar_sync_after(int id, uint32_t dep) {
  asm volatile("{\n.reg .u32 n;\nor.b32 n, %1, 256;\nmin.u32 n, n, 256;\nbar.sync %0, n;\n}" :: "r"(id), "r"(dep) : "memory");
}
__device__ __forceinline__ uint32_t mapa(uint32_t a, uint32_t r) { uint32_t d; asm("mapa.shared::cluster.u32 %0, %1, %2;" : "=r"(d) : "r"(a), "r"(r)); return d; }
__device__ __forceinline__ void st_tag128(uint4* p, uint32_t a, uint32_t b, uint32_t c, uint32_t tag) {
  asm volatile("{\n.reg .b64 lo, hi;\n.reg .b128 v;\nmov.b64 lo, {%1, %2};\nmov.b64 hi, {%3, %4};\nmov.b128 v, {lo, hi};\nst.relaxed.gpu.global.b128 [%0], v;\n}"
    :: "l"(p), "r"(a), "r"(b), "r"(c), "r"(tag) : "memory");
}
__device__ __forceinline__ void st_tag128_if(bool on, uint4* p, uint32_t a, uint32_t b, uint32_t c, uint32_t tag) {
  asm volatile("{\n.reg .pred q;\n.reg .b64 lo, hi;\n.reg .b128 v;\nsetp.ne.u32 q, %5, 0;\nmov.b64 lo, {%1, %2};\nmov.b64 hi, {%3, %4};\nmov.b128 v, {lo, hi};\n@q st.relaxed.gpu.global.b128 [%0], v;\n}"
    :: "l"(p), "r"(a), "r"(b), "r"(c), "r"(tag), "r"((uint32_t)on) : "memory");
}
__device__ __forceinline__ uint4 ld_tag128(const uint4* p) {
  uint4 v;
  asm volatile("{\n.reg .b64 lo, hi;\n.reg .b128 v;\nld.relaxed.gpu.global.b128 v, [%4];\nmov.b128 {lo, hi}, v;\nmov.b64 {%0, %1}, lo;\nmov.b64 {%2, %3}, hi;\n}"
    : "=r"(v.x), "=r"(v.y), "=r"(v.z), "=r"(v.w) : "l"(p) : "memory");
  return v;
}
__device__ __forceinline__ void st_tag64(uint2* p, float a, uint32_t tag) {
  asm volatile("{\n.reg .b64 v;\nmov.b64 v, {%1, %2};\nst.relaxed.gpu.global.b64 [%0], v;\n}" :: "l"(p), "r"(__float_as_uint(a)), "r"(tag) : "memory");
}
__device__ __forceinline__ uint2 ld_tag64(const uint2* p) {
  uint2 v;
  asm volatile("{\n.reg .b64 v;\nld.relaxed.gpu.global.b64 v, [%2];\nmov.b64 {%0, %1}, v;\n}" : "=r"(v.x), "=r"(v.y) : "l"(p) : "memory");
  return v;
}
__device__ __forceinline__ uint32_t pack_bf16(float lo, float hi) { uint32_t r; asm("cvt.rn.bf16x2.f32 %0, %1, %2;" : "=r"(r) : "f"(hi), "f"(lo)); return r; }
__device__ __forceinline__ uint32_t relu_sq_bf16(float lo, float hi) {
  uint32_t r; asm("{\n.reg .b32 t;\ncvt.rn.relu.bf16x2.f32 t, %1, %2;\nmul.rn.bf16x2 %0, t, t;\n}" : "=r"(r) : "f"(hi), "f"(lo)); return r;
}
__device__ __forceinline__ float bf_lo(uint32_t u) { return __uint_as_float(u << 16); }
__device__ __forceinline__ float bf_hi(uint32_t u) { return __uint_as_float(u & 0xffff0000u); }
__device__ __forceinline__ void stmatrix4(uint32_t addr, uint32_t r0, uint32_t r1, uint32_t r2, uint32_t r3) {
  asm volatile("stmatrix.sync.aligned.m8n8.x4.shared.b16 [%0], {%1, %2, %3, %4};" :: "r"(addr), "r"(r0), "r"(r1), "r"(r2), "r"(r3) : "memory");
}
__device__ __forceinline__ void ldmatrix4(uint32_t addr, uint32_t (&r)[4]) {
  asm volatile("ldmatrix.sync.aligned.m8n8.x4.shared.b16 {%0, %1, %2, %3}, [%4];" : "=r"(r[0]), "=r"(r[1]), "=r"(r[2]), "=r"(r[3]) : "r"(addr) : "memory");
}
__device__ __forceinline__ void stmatrix4_t(uint32_t addr, uint32_t r0, uint32_t r1, uint32_t r2, uint32_t r3) {
  asm volatile("stmatrix.sync.aligned.m8n8.x4.trans.shared.b16 [%0], {%1, %2, %3, %4};" :: "r"(addr), "r"(r0), "r"(r1), "r"(r2), "r"(r3) : "memory");
}
__device__ __forceinline__ void ldmatrix4_t(uint32_t addr, uint32_t (&r)[4]) {
  asm volatile("ldmatrix.sync.aligned.m8n8.x4.trans.shared.b16 {%0, %1, %2, %3}, [%4];" : "=r"(r[0]), "=r"(r[1]), "=r"(r[2]), "=r"(r[3]) : "r"(addr) : "memory");
}
__device__ __forceinline__ uint32_t movmatrix(uint32_t a) { uint32_t d; asm volatile("movmatrix.sync.aligned.m8n8.trans.b16 %0, %1;" : "=r"(d) : "r"(a)); return d; }
__device__ __forceinline__ void mma16816_z(float (&c)[4], uint32_t a0, uint32_t a1, uint32_t a2, uint32_t a3, uint32_t b0, uint32_t b1, const float4& z) {
  asm volatile("mma.sync.aligned.m16n8k16.row.col.f32.bf16.bf16.f32 {%0,%1,%2,%3}, {%4,%5,%6,%7}, {%8,%9}, {%10,%11,%12,%13};"
    : "=f"(c[0]), "=f"(c[1]), "=f"(c[2]), "=f"(c[3]) : "r"(a0), "r"(a1), "r"(a2), "r"(a3), "r"(b0), "r"(b1), "f"(z.x), "f"(z.y), "f"(z.z), "f"(z.w));
}
__device__ __forceinline__ float ex2(float x) { float y; asm("ex2.approx.ftz.f32 %0, %1;" : "=f"(y) : "f"(x)); return y; }
__device__ __forceinline__ float rcp(float x) { float y; asm("rcp.approx.ftz.f32 %0, %1;" : "=f"(y) : "f"(x)); return y; }
__device__ __forceinline__ void mma16816(float (&c)[4], uint32_t a0, uint32_t a1, uint32_t a2, uint32_t a3, uint32_t b0, uint32_t b1) {
  asm volatile("mma.sync.aligned.m16n8k16.row.col.f32.bf16.bf16.f32 {%0,%1,%2,%3}, {%4,%5,%6,%7}, {%8,%9}, {%0,%1,%2,%3};"
    : "+f"(c[0]), "+f"(c[1]), "+f"(c[2]), "+f"(c[3]) : "r"(a0), "r"(a1), "r"(a2), "r"(a3), "r"(b0), "r"(b1));
}
__device__ __forceinline__ void sts128(uint32_t a, uint32_t x, uint32_t y, uint32_t z, uint32_t w) { asm volatile("st.shared.v4.b32 [%0], {%1,%2,%3,%4};" :: "r"(a), "r"(x), "r"(y), "r"(z), "r"(w) : "memory"); }
__device__ __forceinline__ float2 lds64f(uint32_t a) { float2 v; asm volatile("ld.shared.v2.f32 {%0,%1}, [%2];" : "=f"(v.x), "=f"(v.y) : "r"(a) : "memory"); return v; }
__device__ __forceinline__ float4 lds128f(uint32_t a) { float4 v; asm volatile("ld.shared.v4.f32 {%0,%1,%2,%3}, [%4];" : "=f"(v.x), "=f"(v.y), "=f"(v.z), "=f"(v.w) : "r"(a) : "memory"); return v; }
__device__ __forceinline__ void sts32f(uint32_t a, float v) { asm volatile("st.shared.f32 [%0], %1;" :: "r"(a), "f"(v) : "memory"); }
__device__ __forceinline__ void sts64f(uint32_t a, float x, float y) { asm volatile("st.shared.v2.f32 [%0], {%1,%2};" :: "r"(a), "f"(x), "f"(y) : "memory"); }
__device__ __forceinline__ uint32_t lds32(uint32_t a) { uint32_t v; asm volatile("ld.shared.u32 %0, [%1];" : "=r"(v) : "r"(a) : "memory"); return v; }
__device__ __forceinline__ float after(float x, uint32_t d, uint32_t zero) { return __uint_as_float(__float_as_uint(x) | (d & zero)); }
template<int R> __device__ __forceinline__ void reg_alloc() { asm volatile("setmaxnreg.inc.sync.aligned.u32 %0;" :: "n"(R)); }
template<int R> __device__ __forceinline__ void reg_dealloc() { asm volatile("setmaxnreg.dec.sync.aligned.u32 %0;" :: "n"(R)); }

struct Ctx {
  uint32_t sb;
  int m, j, b, rank, wg, w, lane;
};

__device__ __forceinline__ unsigned smem_tag(const Ctx& c) { return lds32(c.sb + OFF_TAG); }
__device__ __forceinline__ int smem_block(const Ctx& c) { return lds32(c.sb + OFF_TAG + 8); }

struct WTile { int map, c0, c2; };
__host__ __device__ constexpr WTile wtile(int type, int j) {
  return WTile{128 * (type < 2 ? 5 : type < 5 ? type + 4 : type + 3), type < 2 ? (j + 8 * type) * 64 : 0,
               type < 2 ? 0 : type == 3 ? 3 * j : type == 4 ? 24 + 2 * j : type == 5 ? 40 + 2 * j : 2 * j};
}
__host__ __device__ constexpr int first_stage(int type, int part) { return ((part == 0 ? 0x2000422 : part == 1 ? 0x2 : 0x2002) >> (4 * type)) & 7; }

enum { A_NEW = 1 << 9, A_QUIET = 1 << 10, A_NONE = 1 << 11, A_PAIR = 2 << 11, A_COPY = 3 << 11 };
struct Plan {
  unsigned epoch[256];
  uint32_t v[8][PLAN_BYTES / 4];
};
constexpr Plan make_plan() {
  Plan plan{};
  for (int j = 0; j < 8; j++)
    for (int g = 4; g < 2 * KB_LAYER; g++) {
      const int layer = g >= KB_LAYER, r = g - layer * KB_LAYER;
      const bool split = (r >= 48 && r < 80) || (layer && r < 32);
      const int q = r - (r >= 48 ? 48 : 0);
      const bool head = split && q < 4, second = split && (head ? q >= 2 : q >= 18), lead = split && !second;
      const int type = split ? (r >= 48 ? 3 : 0) + second : r < 96 ? r >> 4 : 6, t = layer * 7 + type;
      const int step = !split ? r - 16 * type : head ? q & 1 : q - (second ? 16 : 2), n = step - (split && !head ? 2 : 0);
      const bool wide = type < 2 || type == 3;
      const int ns = wide || head ? 4 : 5, lag = type == 2 ? 3 : 4;
      const int e = g - (type == 3 && !head && n < 2 ? 5 + n : n + 1 > ns ? ns : n + 1 > lag ? n + 1 : lag);
      const int v = (int)(0xfb7d95ea6c842310ull >> (4 * (step & 15))) & 15;
      const int kb = split ? (v < 4 ? (j * 2) ^ v : ((j >> 1) * 4 + v) & 15) : type != 2 || step < 8 ? step : step < 10 ? j ^ step : 8 + (((j & 6) + step) & 7);
      const uint32_t x = kb * 64 + (first_stage(type, head ? 1 : 2 * split) + n) % ns * (163840 / ns);
      const bool local = type == 2 && (step >> 1) == 4;
      const int act = split && step < 4 ? (head || lead ? A_NONE : A_PAIR) : local ? (step == 8 ? A_NONE : A_COPY) : 0;
      const uint32_t piece = type == 6 ? (step < 24 ? step / 3 : (step >> 1) - 4) : (type == 2 ? !local : lead ? step >= 4 : second && step == 2) ? kb : 31;
      const int ea = split && act == A_NONE ? g - 8 - (step == 3) : e;
      const WTile w = wtile(type, j);
      uint32_t* d = plan.v[j] + (g - 4) * 4;
      d[0] = x + ((ea >> 3) & 1) + (ea & 7) * 8 + (act ? 0 : (j & 1) * 8192) + (piece << 27);
      d[1] = (!head ? A_BYTES : lead ? 4 : 0) + (type == 2 || type == 6 ? 256 : t < 2 ? 0 : 128) + act + (n == 0 && !second ? A_NEW : 0) +
             (local && step == 8 ? A_QUIET : 0) + ((uint32_t)(t - second) << 27);
      d[2] = x + ((e >> 3) & 1) + (e & 7) * 8 + (head && !wide ? 0 : A_BYTES) + ((uint32_t)w.c2 << 26);
      d[3] = w.c0 + (wide ? 24576 : 16384) + (w.map << 16);
    }
  return plan;
}
__device__ __align__(128) Plan g_plan = make_plan();

template<int NL>
__device__ __forceinline__ void row_stats(const Ctx& c, int t) {
  const int ln = t / 3;
  const unsigned tag = smem_tag(c);
  const int row = c.w * 32 + c.lane + lds32(c.sb + OFF_ZERO);
  float s = 0.f, q = 0.f;
  const uint32_t xr = c.sb + OFF_X + row * 128 + (row & 7) * 16;
#pragma unroll 1
  for (int i = 0; i < 128; i += 16) {
    const float4 v = lds128f(xr ^ i), w = lds128f((xr ^ i) + A_BYTES);
    const float u[8] = {v.x, v.y, v.z, v.w, w.x, w.y, w.z, w.w};
#pragma unroll
    for (int z = 0; z < 16; z++) { const float x = z & 1 ? bf_hi(__float_as_uint(u[z >> 1])) : bf_lo(__float_as_uint(u[z >> 1])); s += x; q = fmaf(x, x, q); }
  }
  if (NL == 8) TL(-1, 6);
  if (NL == 4) mbar_pace(c.sb + OFF_FULL + 8 * SA, ln >> 1);
  const int b = smem_block(c);
  st_tag128(g_stats + (ln * 128 + b) * 128 + row, __float_as_uint(s), __float_as_uint(q), 0u, tag);
  mbar_pace(c.sb + (NL == 4 ? OFF_FULL + 8 * (SB & 7) : OFF_EMPTY + 16), (ln >> 1) ^ 1);
  const uint4* p = g_stats + (ln * 128 + (b & ~7)) * 128 + row;
  for (unsigned it = 0;; it++) {
    bool ok = true;
    s = 0.f; q = 0.f;
#pragma unroll 1
    for (int h = 0; h < 8; h += NL) {
      uint4 v[NL];
#pragma unroll
      for (int i = 0; i < NL; i++) v[i] = ld_tag128(p + (h + i) * 128);
#pragma unroll
      for (int i = 0; i < NL; i++) { ok = ok && v[i].w == tag; s += __uint_as_float(v[i].x); q += __uint_as_float(v[i].y); }
    }
    if (__all_sync(0xffffffffu, ok) || it > SPIN_LIMIT) break;
    __nanosleep(NL == 4 ? 400 : 100);
  }
  const float mean = s * (1.0f / D_);
  const float var = fmaxf(q * (1.0f / D_) - mean * mean, 0.0f);
  sts64f(c.sb + OFF_RST + row * 8, rsqrtf(var + 1e-5f), -mean);
  if ((EXP & 256) && NL == 8) sts32f(c.sb + OFF_TAG + 12, __int_as_float(row + 77));
  if ((EXP & 512) && NL == 4) sts32f(c.sb + OFF_TAG + 12, __int_as_float(row + 77));
  bar_arrive(BAR_EPI + (c.wg ^ 1), 256);
  TL(t - 2, 5);
}

__device__ __forceinline__ uint32_t res_addr(const Ctx& c) {
  return c.sb + OFF_X + ((c.lane >> 4) * 8 + (c.lane & 7)) * 128 + (((2 * c.w + ((c.lane >> 3) & 1)) ^ (c.lane & 7)) << 4);
}

template<int BN, int RES>
__device__ __forceinline__ void mainloop(const Ctx& c, float (&acc)[2][96], int t, int type, int g, int nkb) {
  constexpr int NS = BN == 192 ? 4 : 5, STR = BN == 192 ? 40960 : 32768;
  const bool split = !RES && (BN == 192 ? t > 1 : type == 4), second = BN == 128 || type == 1;
  int st = first_stage(type, split);
  if (split && second) g -= 14;
  const uint32_t rel = mapa(c.sb + OFF_EMPTY, c.lane & 1);
  const uint32_t sb = (c.sb & 0x3ffffu) >> 4;
  uint32_t da = DESC_A + sb + (split ? OFF_X / 16 : st * (STR / 16)), db = DESC_B + sb + (BN == 128 && split ? -1024 : st * (STR / 16));
  TL(t, 0);
  bar_sync(BAR_START + c.wg, 256);
  if (RES && type == 2) bar_sync(BAR_P1, 256);
  TL(t, 1);
  mbar_wait(c.sb + OFF_FULL + 8 * (g & 7), (g >> 3) & 1);
  TL(t, 2);
  wgmma_fence();
#define MMA(i, k, keep) wgmma_ss<BN, RES ? 2 : keep>(acc[i], da + (k) * 2 + (RES ? 0 : 64 * (i)), db + (k) * 128 + (RES ? 512 * (i) : 0))
  MMA(0, 0, 0); MMA(1, 0, 0); MMA(0, 1, 1); MMA(1, 1, 1);
  wgmma_commit();
  wgmma_fence();
  MMA(0, 2, 1); MMA(1, 2, 1); MMA(0, 3, 1); MMA(1, 3, 1);
  wgmma_commit();
  const int pause = BN == 192 && type == 1 ? (split ? PAUSE2 : PAUSE1) : nkb;
  int kb = 1, lim = split ? 2 : pause, pass = split ? 2 : !RES && type != 1 ? nkb : 0;
  uint32_t other = BAR_START + (c.wg ^ 1), prev = c.lane < 2 ? rel + 8 * (g & 7) : 0;
  asm volatile("" : "+r"(other));
  if (++st == NS) st = 0;
  g++;
  da = DESC_A + sb + (split ? (OFF_X + A_BYTES) / 16 : st * (STR / 16));
  db = DESC_B + sb + (BN == 128 && split ? 1536 : st * (STR / 16));
#pragma unroll 1
  for (;;) {
    mbar_wait(c.sb + OFF_FULL + 8 * (g & 7), (g >> 3) & 1);
    bool more;
#pragma unroll 1
    do {
      wgmma_fence();
      MMA(0, 0, 1); MMA(1, 0, 1); MMA(0, 1, 1); MMA(1, 1, 1);
      wgmma_commit();
      wgmma_wait<1>();
      if (prev) mbar_arrive_cluster(prev);
      TK(t, kb);
      prev = c.lane < 2 ? rel + 8 * (g & 7) : 0;
      kb++; g++;
      if (++st == NS) st = 0;
      wgmma_fence();
      if (BN == 128 && kb == pass) bar_arrive(other, 256);
      MMA(0, 2, 1); MMA(1, 2, 1);
      if (BN == 192 && kb == pass) bar_arrive(other, 256);
      const uint32_t ok = mbar_test(c.sb + OFF_FULL + 8 * (g & 7), (g >> 3) & 1);
      MMA(0, 3, 1); MMA(1, 3, 1);
      wgmma_commit();
      more = __all_sync(0xffffffffu, ok) && kb != lim;
      da = DESC_A + sb + (RES && type == 2 && kb == 8 ? OFF_STG / 16 : st * (STR / 16));
      db = DESC_B + sb + st * (STR / 16);
    } while (more);
    if (kb != lim) continue;
    if (RES || kb == nkb) break;
    if (BN == 128 || kb == 2) {
      wgmma_wait<0>();
      if (prev) mbar_arrive_cluster(prev);
      TK(t, 16);
      if (second) row_stats<4>(c, t);
      g += second ? 14 : 2;
      st = first_stage(type, 2);
      da = DESC_A + sb + st * (STR / 16); db = DESC_B + sb + st * (STR / 16);
      lim = pause; pass = type != 1 ? nkb : 0; prev = 0;
      bar_sync(BAR_START + c.wg, 256);
    } else {
      bar_sync(BAR_P0, 256); bar_sync(BAR_P1, 256);
      lim = kb == pause ? pause + 2 : nkb;
    }
  }
  if (!RES) return;
#define PAIR(i, n) wgmma_ss<128, 2>(acc[i], da + ((n) >> 2) * 2048 + ((n) & 3) * 2, db + ((n) >> 2) * 2048 + ((n) & 3) * 128 + 512 * (i))
#define PUT(z) do { const float* a = acc[(z) >> 3] + ((z) & 7) * 8; \
    stmatrix4_t(xw + (z) * 2048, pack_bf16(a[0], a[1]), pack_bf16(a[2], a[3]), pack_bf16(a[4], a[5]), pack_bf16(a[6], a[7])); } while (0)
  const uint32_t xw = res_addr(c);
#pragma unroll
  for (int n = 0; n < 4 * SK; n++) {
    if (!(n & 3)) { mbar_wait(c.sb + OFF_FULL + 8 * (8 - SK + n / 4), (g >> 3) & 1); wgmma_fence(); }
    PAIR(0, n);
    if (n == 3) { wgmma_commit(); wgmma_wait<1>(); if (prev) mbar_arrive_cluster(prev); wgmma_fence(); }
  }
  wgmma_commit();
#pragma unroll
  for (int n = 0; n < 4 * SK; n++) {
    if (n == 4 * SK - 2 && t < 13) bar_arrive(other, 256);
    PAIR(1, n);
    wgmma_commit();
#pragma unroll
    for (int z = 0; z < 8; z++) if (z / 4 + 2 == n) PUT(z);
    if (n == 3) bar_arrive(BAR_RES, 160);
    if (n && n < 4 * SK - 1) wgmma_wait<2>();
    if (n > 4 && (n & 3) == 1 && c.lane < 2) mbar_arrive_cluster(rel + 8 * (7 - SK + n / 4));
  }
  wgmma_wait<0>();
  if (c.lane < 2) mbar_arrive_cluster(rel + 56);
  TL(t, 3);
#pragma unroll
  for (int nt = 8; nt < 16; nt++) PUT(nt);
  fence_async_smem();
  __syncwarp();
  asm volatile(ELECT "@p mbarrier.complete_tx.relaxed.cta.shared::cta.b64 [%0], 1;\n}" :: "r"(c.sb + OFF_FULL + 8) : "memory");
  bar_arrive(BAR_RES2, 160);
#undef MMA
#undef PAIR
#undef PUT
}
__device__ __forceinline__ void release(const Ctx& c, int slot, int lanes = 2) {
  if (c.lane < lanes) mbar_arrive_cluster(mapa(c.sb + OFF_EMPTY, c.lane & 1) + 8 * slot);
}
__device__ __forceinline__ void finish(const Ctx& c, int t, int slot) {
  wgmma_wait<0>();
  release(c, slot);
  TL(t, 3);
}

__device__ __forceinline__ void put_halo(uint32_t addr, bool last, uint32_t a, uint32_t b, uint32_t c, uint32_t d) {
  if (!last) stmatrix4(addr, a, b, c, d);
  else asm volatile("stmatrix.sync.aligned.m8n8.x2.shared.b16 [%0], {%1, %2};\nstmatrix.sync.aligned.m8n8.x1.shared.b16 [%0 + 256], {%3};" :: "r"(addr), "r"(a), "r"(b), "r"(c) : "memory");
}

__device__ __forceinline__ void fetch_halo(const Ctx& c, unsigned tag, int tile) {
  const int v = c.w & 1;
  const uint4* src = g_halo + (tile * 128 + c.b - 8) * 352 + v * 160 + c.lane;
  uint4 G[6];
#pragma unroll
  for (int z = 0; z < 6; z++) G[z] = make_uint4(0u, 0u, 0u, 0u);
  bar_sync(BAR_HGO + v, 64);
  for (unsigned it = 0; c.m > 0; it++) {
    bool ok = true;
#pragma unroll
    for (int z = 0; z < 6; z++) { G[z] = ld_tag128(src + z * 32); ok = ok && G[z].w == tag; }
    if (__all_sync(0xffffffffu, ok) || it > SPIN_LIMIT) break;
  }
#pragma unroll
  for (int z = 0; z < 6; z++) put_halo(c.sb + OFF_STG + c.lane * 16 + (z ? (v * 5 + z) * 384 - 128 : v * 1792), z == 5, G[z].x, G[z].y, G[z].z, G[z].w);
  if (!v) sts32f(c.sb + OFF_RST - 256 + c.lane * 8, __uint_as_float(G[0].z));
  __syncwarp();
  mbar_arrive_e(c.sb + OFF_HALO + 8 * v);
}

template<int SKEW>
__device__ __forceinline__ void conv_qkv(const Ctx& c, float (&acc)[2][96], uint32_t (&P)[3][2][4][4], int t) {
  const int lane = c.lane, w = c.w, g = lane >> 2, cc = lane & 3;
  const int layer = t >= 7;
  const uint32_t sb = (c.sb & 0x3ffffu) >> 4, par = layer ^ 1;
  uint32_t da = DESC_A + sb + 7680 + 64, db = DESC_B + sb + 7680;
#define MMA(i, n) if (SKEW) do { wgmma_ss<192, 1>(acc[i], da, db); \
    asm volatile("add.s32 %0, %0, %2;\nadd.s32 %1, %1, %3;" : "+r"(da), "+r"(db) : "r"((n) == 11 ? 5050 : (n) == 7 ? 2554 : (n) == 3 ? -7686 : 2), "r"((n) == 11 ? 4736 : (n) == 7 ? 2176 : (n) == 3 ? -8064 : 128)); } while (0)
  if (SKEW) {
    mbar_wait(c.sb + OFF_FULL + 40, par);
    wgmma_fence();
    MMA(1, 0); MMA(1, 1); MMA(1, 2); MMA(1, 3);
    wgmma_commit();
    wgmma_wait<1>();
    release(c, 4);
    mbar_wait(c.sb + OFF_FULL + 48, par);
  } else finish(c, t, layer ? 1 : 7);
  MMA(1, 4); MMA(1, 5);
  bar_sync(BAR_EPI + c.wg, 256);
  MMA(1, 6);
  mbar_wait(c.sb + OFF_TBL + 8 * SKEW, 0);
  MMA(1, 7);
  if (SKEW) mbar_wait(c.sb + OFF_FULL + 56, par);
  MMA(1, 8);
  bar_sync(BAR_FREE, 160);
  MMA(1, 9);
  const uint32_t rst = c.sb + OFF_RST + w * 256;
  float mu[4];
#pragma unroll
  for (int r = 0; r < 4; r++) mu[r] = __uint_as_float(lds32(rst + (8 * r + g) * 8 + 4));
  const uint32_t tag = smem_tag(c), rs_l = lds32(rst + lane * 8);
  const uint32_t csb = c.sb + OFF_CSQ + SKEW * 768 + cc * 16;
  const uint32_t stg = c.sb + OFF_STG + w * 4096;
  const int b = smem_block(c);
  uint4* const halo = g_halo + ((layer * 2 + SKEW) * 128 + b) * 352 + lane;
  const bool send = w == 3 && b < 120;
  float4 cs = lds128f(csb + 4 * 64);
  if (SKEW) {
    MMA(1, 10); MMA(1, 11);
    wgmma_commit();
    MMA(0, 0);
    wgmma_commit();
    MMA(0, 1);
    wgmma_commit();
    wgmma_wait<2>();
  }
#define CONV(i, np) do { _Pragma("unroll") for (int z = 0; z < 4; z++) { const int nt = 2 * (np) + (z >> 1), h = z & 1; \
    const float m = mu[2 * h + (i)]; \
    P[nt >> 3][(nt >> 2) & 1][2 * h + (i)][nt & 3] = pack_bf16(fmaf(z >> 1 ? cs.z : cs.x, m, acc[i][4 * nt + 2 * h]), \
                                                                     fmaf(z >> 1 ? cs.w : cs.y, m, acc[i][4 * nt + 2 * h + 1])); } } while (0)
#define HM(u) P[1 + (((u) >> 4) & 1)][((u) >> 3) & 1][((u) & 2) + 1][(((u) >> 1) & 2) + ((u) & 1)]
#define HW(u) ((u) == 2 ? rs_l : HM((u) - ((u) > 2)))
#pragma unroll
  for (int n = 0; n < 12; n++) {
    const int np = (n + 4) % 12;
    if (SKEW && n == HGK && w == 0) bar_arrive(BAR_HGO, 64);
    if (SKEW && n == HGO && w == 0) bar_arrive(BAR_HGO + 1, 64);
    if (SKEW && n == 8) bar_arrive(BAR_START + (c.wg ^ 1), 256);
    if (SKEW && n < 10) { MMA(0, n + 2); wgmma_commit(); }
    CONV(1, np);
    cs = lds128f(csb + (n < 11 ? (n + 5) % 12 : 0) * 64);
#pragma unroll
    for (int z = 0; z < 11; z++)
      if ((3 * z + 1) / 4 == n) {
        st_tag128_if(send, halo + z * 32, HW(3 * z), HW(3 * z + 1), HW(3 * z + 2), tag);
        put_halo(stg + 4096 + lane * 16 + (z ? z * 384 - 128 : 0), z == 10, HW(3 * z), HW(3 * z + 1), HW(3 * z + 2), tag);
      }
    if (SKEW && n < 10) wgmma_wait<2>();
    if (SKEW && (n == 3 || n == 7)) release(c, 5 + (n >> 2));
  }
#undef MMA
#undef HW
#undef HM
  if (SKEW) {
    wgmma_wait<0>();
    release(c, 7, w ? 2 : 0);
    TL(t, 3);
  }
#pragma unroll
  for (int np = 0; np < 12; np++) {
    CONV(0, np);
    if (!SKEW && np == HG1 && w == 0) { bar_arrive(BAR_HGO, 64); bar_arrive(BAR_HGO + 1, 64); }
    if (np < 11) cs = lds128f(csb + (np + 1) * 64);
  }
#undef CONV
}

__device__ __forceinline__ void epi_qkv(const Ctx& c, float (&acc)[2][96], int t, int q) {
  const int lane = c.lane, w = c.w, g = lane >> 2, cc = lane & 3;
  uint32_t P[3][2][4][4];
  if (q) conv_qkv<1>(c, acc, P, t); else conv_qkv<0>(c, acc, P, t);
  const uint32_t rst = c.sb + OFF_RST + w * 256, stg = c.sb + OFF_STG + w * 4096;
  const bool nohalo = w == 0 && smem_block(c) < 8;
#pragma unroll
  for (int z = 0; z < 16; z++) P[2][z >> 3][(z >> 1) & 2][z & 3] = movmatrix(P[2][z >> 3][(z >> 1) & 2][z & 3]);
  uint32_t K1[4][4], V1[4][4];
  const uint32_t hl = stg + (lane & 15) * 16 + (lane >> 4) * 512;
#define HZ(z) (((z) >> 1) * 1024 + ((z) & 1) * 256)
  __syncwarp();
#pragma unroll
  for (int z = 0; z < 4; z++) { ldmatrix4(hl + 4096 + HZ(z), K1[z]); ldmatrix4_t(hl + 4096 + 2048 + HZ(z), V1[z]); }
  TL(t, 9);
  bar_sync(BAR_WG + c.wg, 128);
  if (w == 0) { TL(t, 8); mbar_wait(c.sb + OFF_HALO, q); release(c, 7, 2 * q); }
  uint32_t HK[4][4], HV[4][4];
#pragma unroll
  for (int z = 0; z < 4; z++) ldmatrix4(hl + HZ(z), HK[z]);
  const bool far0 = 2 * cc > g, far1 = 2 * cc + 1 > g;
  float rk[4][2], sc[4][2];
#pragma unroll
  for (int r = 0; r < 4; r++) {
    const float rq = __uint_as_float(lds32(rst + (8 * r + g) * 8)) * (0.17677669529663687f * 1.4426950408889634f);
    const int back = r & 1 ? 64 : 192;
    rk[r][0] = __uint_as_float(lds32(rst + r * 64 + cc * 16 - (far0 ? back : 0)));
    rk[r][1] = __uint_as_float(lds32(rst + r * 64 + cc * 16 + 8 - (far1 ? back : 0)));
    sc[r][0] = rq * rk[r][0]; sc[r][1] = rq * rk[r][1];
  }
  TL(t, 4);
  float S[4][3][4];
  if (q == 0) bar_sync(BAR_P0, 256);
  float4 zero = lds128f(c.sb + OFF_ZERO);
#pragma unroll
  for (int k = 0; k < 2; k++)
#pragma unroll
    for (int z = 0; z < 4; z++) {
      const uint32_t* qa = P[0][z >> 1][2 * (z & 1)]; const uint32_t* qb = P[0][z >> 1][2 * (z & 1) + 1];
      const uint32_t* kk[3] = {HK[z], P[1][z >> 1][2 * (z & 1)], K1[z]};
#pragma unroll
      for (int n = 0; n < 3; n++) {
        if (k == 0) mma16816_z(S[z][n], qa[0], qb[0], qa[1], qb[1], kk[n][0], kk[n][1], zero);
        else mma16816(S[z][n], qa[2], qb[2], qa[3], qb[3], kk[n][2], kk[n][3]);
        if (q == 0 && k * 12 + z * 3 + n + 1 == NS) bar_arrive_here(BAR_P1, S[0][0][0], zero.x);
      }
    }
  TL(t, 10);
  const uint32_t fmask = (far0 ? 0xffffu : 0u) | (far1 ? 0xffff0000u : 0u);
  uint32_t pf[4][2], pn[4][2];
#pragma unroll
  for (int z = 0; z < 4; z++)
#pragma unroll
    for (int i = 0; i < 2; i++) {
      const int r = 2 * (z & 1) + i;
      float l0 = (far0 ? S[z][i][2 * i] : S[z][i + 1][2 * i]) * sc[r][0];
      float l1 = (far1 ? S[z][i][2 * i + 1] : S[z][i + 1][2 * i + 1]) * sc[r][1];
      if (i == 0 && nohalo) { const float neg = -1e9f * 1.4426950408889634f; if (far0) l0 = neg; if (far1) l1 = neg; }
      float mx = fmaxf(l0, l1);
      mx = fmaxf(mx, __shfl_xor_sync(0xffffffffu, mx, 1));
      mx = fmaxf(mx, __shfl_xor_sync(0xffffffffu, mx, 2));
      l0 = ex2(l0 - mx); l1 = ex2(l1 - mx);
      float sum = l0 + l1;
      l0 *= rk[r][0]; l1 *= rk[r][1];
      sum += __shfl_xor_sync(0xffffffffu, sum, 1);
      sum += __shfl_xor_sync(0xffffffffu, sum, 2);
      sum = rcp(sum);
      const uint32_t u = pack_bf16(l0 * sum, l1 * sum);
      pf[z][i] = u & fmask; pn[z][i] = u & ~fmask;
    }
  float O[4][2][2][4];
  TL(t, 11);
  if (w == 0) { mbar_wait(c.sb + OFF_HALO + 8, q); TL(t, 12); }
#pragma unroll
  for (int z = 0; z < 4; z++) ldmatrix4_t(hl + 2048 + HZ(z), HV[z]);
#undef HZ
  if (q == 0) bar_sync_after(BAR_P0, (pn[0][0] | pn[0][1] | pn[1][0]) | (pn[1][1] | pn[2][0] | pn[2][1]) | (pn[3][0] | pn[3][1]));
  zero = lds128f(c.sb + OFF_ZERO);
#pragma unroll
  for (int z = 0; z < 4; z++)
#pragma unroll
    for (int d = 0; d < 2; d++) {
      const uint32_t* v0 = P[2][z >> 1][2 * (z & 1)] + 2 * d;
      mma16816_z(O[z][0][d], HV[z][2 * d], HV[z][2 * d + 1], v0[0], v0[1], pf[z][0], pn[z][0], zero);
      mma16816_z(O[z][1][d], v0[0], v0[1], V1[z][2 * d], V1[z][2 * d + 1], pf[z][1], pn[z][1], zero);
      if (z * 4 + d * 2 + 2 == NP) bar_arrive_here(BAR_P1, O[0][0][0][0], zero.x);
    }
  TL(t, 5);
#pragma unroll
  for (int nt = 0; nt < 8; nt++) {
    uint32_t u[4];
#pragma unroll
    for (int r = 0; r < 4; r++) { const float* o = O[2 * (nt >> 2) + (r >> 1)][r & 1][(nt >> 1) & 1] + 2 * (nt & 1); u[r] = pack_bf16(o[0], o[1]); }
    stmatrix4_t(stg + lane * 128 + ((nt ^ (lane & 7)) << 4), u[0], u[1], u[2], u[3]);
  }
  fence_async_smem();
  bar_arrive(BAR_READY, 160);
  TL(t, 13);
}

template<int CH>
__device__ __forceinline__ void epi_up(const Ctx& c, float (&acc)[2][96], int type) {
  const int lane = c.lane, w = c.w, g = lane >> 2, cc = lane & 3;
  float rs[4], nm[4];
#pragma unroll
  for (int r = 0; r < 4; r++) { const float2 v = lds64f(c.sb + OFF_RST + (w * 32 + 8 * r + g) * 8); rs[r] = v.x; nm[r] = v.x * v.y; }
  const int loc0 = type == 3 ? 0 : (type == 4 ? 192 : 320);
  const uint32_t cb = c.sb + OFF_UP + loc0 * 8 + cc * 16;
  const uint32_t zero = lds32(c.sb + OFF_ZERO);
  uint32_t d[2] = {0u, 0u};
  const uint32_t stg = c.sb + OFF_STG + w * 4096;
#pragma unroll
  for (int ch = CH; ch < (CH ? 3 : 2); ch++) {
    uint32_t P[8][4];
#pragma unroll
    for (int n8 = 0; n8 < 8; n8++) {
      const int nt = ch * 8 + n8;
      const float4 cv = lds128f(cb + nt * 64);
#pragma unroll
      for (int r = 0; r < 4; r++) {
        const float m = after(nm[r], d[r & 1], zero);
        d[r & 1] = P[n8][r] = relu_sq_bf16(fmaf(acc[r & 1][4 * nt + 2 * (r >> 1)], rs[r], fmaf(cv.x, m, cv.z)),
                                           fmaf(acc[r & 1][4 * nt + 2 * (r >> 1) + 1], rs[r], fmaf(cv.y, m, cv.w)));
      }
    }
    bar_sync(BAR_FREE, 160);
#pragma unroll
    for (int n8 = 0; n8 < 8; n8++)
      stmatrix4(stg + lane * 128 + ((n8 ^ (lane & 7)) << 4), P[n8][0], P[n8][1], P[n8][2], P[n8][3]);
    fence_async_smem();
    bar_arrive(BAR_READY, 160);
  }
}

__device__ __forceinline__ void init_res(const Ctx& c, float (&acc)[2][96], int t, bool bias) {
  if (t == 2) mbar_wait(c.sb + OFF_XBAR, 0);
  const uint32_t xb = res_addr(c);
  float b[4];
#pragma unroll
  for (int r = 0; r < 4; r++) b[r] = bias ? __uint_as_float(lds32(c.sb + OFF_B2 + (r >> 1) * 256 + c.w * 64 + (r & 1) * 32 + (c.lane >> 2) * 4)) : 0.f;
#pragma unroll
  for (int z = 0; z < 16; z++) {
    uint32_t u[4];
    ldmatrix4_t(xb + z * 2048, u);
#pragma unroll
    for (int r = 0; r < 4; r++) {
      float* a = acc[z >> 3] + (z & 7) * 8 + 2 * r;
      a[0] = bf_lo(u[r]) + b[(z >> 3) * 2 + (r & 1)];
      a[1] = bf_hi(u[r]) + b[(z >> 3) * 2 + (r & 1)];
      asm volatile("" : "+f"(a[0]), "+f"(a[1]));
    }
  }
}

__device__ __forceinline__ void load_table(const Ctx& c, const Params& p, int part, unsigned tag) {
  const int i0 = (part < 4 ? part * 192 : 704) + c.lane, n = part < 3 ? 6 : 4;
  const uint2* src = g_cs + c.j * NCS + i0;
  const uint32_t dst = c.sb + OFF_CSQ + (i0 & 1) * 4 + (part < 2 ? (i0 >> 4) * 64 + (i0 & 6) * 8 + (i0 & 8) : 1536 + ((i0 - 384) >> 1) * 16);
  const __nv_bfloat16* bias = p.b1 + (part == 2 ? c.j * 192 : (part == 3 ? 1536 : 2560) + c.j * 128) + c.lane;
  float v[6];
  if (part >= 2) {
#pragma unroll
    for (int k = 0; k < 6; k++) if (k < n) sts32f(dst + k * 256 + 8, __bfloat162float(bias[k * 32]));
  }
  for (unsigned it = 0;; it++) {
    bool ok = true;
#pragma unroll
    for (int k = 0; k < 6; k++) { const uint2 a = ld_tag64(src + (k < n ? k * 32 : 0)); ok = ok && a.y == tag; v[k] = __uint_as_float(a.x); }
    if (__all_sync(0xffffffffu, ok) || it > SPIN_LIMIT) break;
    __nanosleep(200);
  }
#pragma unroll
  for (int k = 0; k < 6; k++) if (k < n) sts32f(dst + k * (part < 2 ? 128 : 256), v[k]);
  __syncwarp();
}

__device__ __forceinline__ void colsum_cta(const Ctx& c, const Params& p, unsigned* epoch) {
  if (c.wg < 2) mbar_init_e(c.sb + OFF_FULL + 32 * c.wg + 8 * c.w, 1);
  sts32f(c.sb + OFF_STG + threadIdx.x * 4, __uint_as_float(0x3f803f80u));
  fence_async_smem();
  __syncthreads();
  if (c.wg == 2) return;
  const unsigned tag = *(volatile unsigned*)epoch + 1;
  const int j = (blockIdx.x - 128) * 2 + c.wg;
  const uint32_t ring = c.sb + c.wg * 98304, full = c.sb + OFF_FULL + 32 * c.wg;
  const uint64_t ones = (uint64_t)(((c.sb + OFF_STG) & 0x3ffffu) >> 4) | (8u << 16) | ((uint64_t)16u << 32);
  float d[3][4];
#pragma unroll 1
  for (int n = -4; n < 80; n++) {
    if (n >= 0) {
      mbar_wait(full + 8 * (n & 3), (n >> 2) & 1);
      const uint64_t da = (uint64_t)(((ring + (n & 3) * 24576) & 0x3ffffu) >> 4) | (64u << 16) | ((uint64_t)(64u | (1u << 30)) << 32);
      wgmma_fence();
#pragma unroll
      for (int k = 0; k < 4; k++)
#pragma unroll
        for (int z = 0; z < 3; z++)
          asm volatile("{\n.reg .pred p;\nsetp.ne.b32 p, %6, 0;\nwgmma.mma_async.sync.aligned.m64n8k16.f32.bf16.bf16 {%0,%1,%2,%3}, %4, %5, p, 1, 1, 1, 0;\n}"
            : "+f"(d[z][0]), "+f"(d[z][1]), "+f"(d[z][2]), "+f"(d[z][3]) : "l"(da + z * 512 + k * 128), "l"(ones), "r"((n & 15) | k));
      wgmma_commit();
      wgmma_wait<0>();
      bar_sync(BAR_WG + c.wg, 128);
      if ((n & 15) == 15 && (c.lane & 3) < 2) {
        const int u = n >> 4;
        uint2* out = g_cs + j * NCS + (u < 4 ? u * 192 : 704) + c.w * 16 + (c.lane >> 2) + (c.lane & 1) * 8;
#pragma unroll
        for (int z = 0; z < 3; z++) if (z < 2 || u < 3) st_tag64(out + z * 64, (c.lane & 1) ? d[z][2] : d[z][0], tag);
      }
      __syncwarp();
    }
    if (c.w == 0 && n < 76) {
      const int u = (n + 4) >> 4;
      const WTile w = wtile(u + (u >= 2), j);
      mbar_expect_e(full + 8 * (n & 3), u < 3 ? 24576 : 16384);
      tma_ld3_e(ring + (n & 3) * 24576, (const CUtensorMap*)((const char*)&p + w.map), full + 8 * (n & 3), w.c0, ((n + 4) & 15) * 64, w.c2);
    }
  }
  bar_sync(BAR_START, 256);
  if (threadIdx.x == 0) *epoch = tag;
}

__device__ __forceinline__ void place(Ctx& c, uint32_t slot) {
  const int row = slot < 32 ? slot >> 3 : slot < 60 ? ((slot - 4) * 37) >> 8 : slot - 56;
  const int gpc = slot < 60 ? slot - row * (slot < 32 ? 8 : 7) - (slot < 32 ? 0 : 3) : 0;
  c.m = (gpc & 1) * 8 + row;
  c.j = (gpc & 6) + c.rank; c.b = c.m * 8 + c.j;
}

__global__ void __cluster_dims__(2, 1, 1) __launch_bounds__(384, 1) fused_kernel(unsigned* const epochs, const char* const x0, const char* const w0, const __grid_constant__ Params p) {
  extern __shared__ uint8_t smem_raw[];
  const int tid = threadIdx.x;
  Ctx c;
  c.sb = (smem_u32(smem_raw) + 1023) & ~1023u;
  const int k = __shfl_sync(0xffffffffu, tid >> 5, 0);
  c.wg = k >> 2; c.w = k & 3; c.lane = tid & 31;
  c.rank = blockIdx.x & 1;
  if (blockIdx.x >= 128) { colsum_cta(c, p, epochs + blockIdx.x); return; }
  uint32_t slot; asm volatile("mov.u32 %0, %%smid;" : "=r"(slot));
  slot = __shfl_sync(0xffffffffu, slot < 120 ? slot >> 1 : 60 + ((slot >> 1) & 3), 0);
  if (c.wg == 2) {
    const bool claim = tid == 320 && c.rank == 0;
    unsigned epoch, old;
    asm volatile("{\n.reg .pred p;\nsetp.ne.u32 p, %4, 0;\nmov.u32 %0, 0;\nmov.u32 %1, 0;\n@p atom.relaxed.gpu.global.add.u32 %0, [%2], 1;\n@p ld.relaxed.gpu.global.u32 %1, [%3];\n}"
      : "=r"(old), "=r"(epoch) : "l"(epochs + 132 + slot + c.lane), "l"(epochs + blockIdx.x), "r"((uint32_t)claim) : "memory");
    reg_dealloc<40>();
#pragma unroll 1
    for (int pass = 0;; pass++) {
      place(c, slot);
      if (c.w == 1) {
        asm volatile(ELECT "@p mbarrier.init.shared::cta.b64 [%0], 2;\n@p mbarrier.init.shared::cta.b64 [%0 + 8], 2;\n"
          "@p mbarrier.init.shared::cta.b64 [%0 + 16], 2;\n@p mbarrier.init.shared::cta.b64 [%0 + 24], 2;\n}" :: "r"(c.sb + OFF_FULL) : "memory");
        fence_async_smem();
        if (!pass) asm volatile("fence.mbarrier_init.release.cluster;\nbarrier.cluster.arrive.relaxed.aligned;" ::: "memory");
#pragma unroll 1
        for (int s = pass ? 0 : 2; s < 4; s++) {
          const uint32_t full = c.sb + OFF_FULL + 8 * s, dst = c.sb + (s ^ 2) * 40960;
          mbar_expect_e(full, 40960);
          tma_ld4_e(dst, &p.ld_x, full, s * 64, c.m * 4);
          tma_ld4_e(dst + 8192, &p.ld_x, full, s * 64, c.m * 4 + 2);
          tma_ld3_e(dst + A_BYTES, &p.w_qkv, full, c.j * 64, s * 64, 0);
          mbar_arrive_e(full);
        }
      } else if (!pass) {
        if (c.w == 2) { mbar_init_e(c.sb + OFF_SLOT, 1); mbar_expect_e(c.sb + OFF_SLOT, 8); }
        asm volatile("fence.mbarrier_init.release.cluster;\nbarrier.cluster.arrive.relaxed.aligned;" ::: "memory");
      }
      if (c.w == 0) {
        asm volatile("cp.async.wait_all;" ::: "memory");
#pragma unroll
        for (int i = 0; i < PLAN_BYTES; i += 512)
          asm volatile("cp.async.cg.shared.global [%0], [%1], 16;" :: "r"(c.sb + OFF_PLAN + c.lane * 16 + i), "l"(epochs + 256 + c.j * (PLAN_BYTES / 4) + c.lane * 4 + i / 4) : "memory");
      }
      if (c.w == 3) sts32f(c.sb + OFF_TAG + 8, __int_as_float(c.b));
      if (pass) { bar_sync(BAR_START, 256); break; }
      asm volatile("barrier.cluster.wait.aligned;" ::: "memory");
      if (claim) {
        uint32_t s = slot;
        for (int it = 0; old != epoch && it < 64; it++) { atomicSub(epochs + 132 + s, 1u); s = (s + 1) & 63; old = atomicAdd(epochs + 132 + s, 1u); }
#pragma unroll
        for (int r = 0; r < 2; r++)
          asm volatile("{\n.reg .u32 t;\nadd.u32 t, %1, 1;\nst.async.weak.shared::cluster.mbarrier::complete_tx::bytes.v2.b32 [%0], {t, %2}, [%3];\n}"
            :: "r"(mapa(c.sb + OFF_TAG, r)), "r"(old), "r"(s), "r"(mapa(c.sb + OFF_SLOT, r)) : "memory");
      }
      __syncwarp();
      mbar_wait(c.sb + OFF_SLOT, 0);
      const uint32_t got = __shfl_sync(0xffffffffu, lds32(c.sb + OFF_TAG + 4), 0);
      if (got == slot) {
        bar_arrive(BAR_START, 256);
#pragma unroll 1
        for (int s = 0; s < 16 && c.w == 3; s += 8) {
          mbar_wait(c.sb + OFF_PRE + s, 0);
          PTL(12, 12 + s / 8);
          fence_async_smem();
          if (c.lane < 2) asm volatile("mbarrier.arrive.shared::cta.b64 _, [%0];" :: "r"(c.sb + OFF_FULL + s) : "memory");
        }
        break;
      }
      slot = got;
      if (c.w == 1)
#pragma unroll 1
        for (int s = 0; s < 4; s++) { mbar_wait(c.sb + (s < 2 ? OFF_PRE : OFF_FULL) + 8 * s, 0); asm volatile(ELECT "@p mbarrier.inval.shared::cta.b64 [%0];\n}" :: "r"(c.sb + OFF_FULL + 8 * s) : "memory"); }
    }
    const unsigned tag = smem_tag(c);
    if (c.w < 2) { asm volatile("cp.async.wait_all;" ::: "memory"); bar_sync(BAR_COPY, 64); PTL(14, 13); }
    if (c.w == 0) {
      const char* fp = (const char*)(g_flags + c.m * 32 + c.lane);
      unsigned ready = 1u << 31;
      float2 nx = lds64f(c.sb + OFF_PLAN);
#pragma unroll 1
      for (int g = 4; g < 2 * KB_LAYER; g++) {
        const uint32_t x = __float_as_uint(nx.x), y = __float_as_uint(nx.y);
        nx = lds64f(c.sb + OFF_PLAN + g * 16 - 48);
        if (y & A_NEW) ready = 1u << 31;
        for (unsigned it = 0; !((ready >> (x >> 27)) & 1) && it < SPIN_LIMIT; it++) {
          unsigned v; asm volatile("ld.relaxed.gpu.global.u32 %0, [%1];" : "=r"(v) : "l"(fp + (y >> 16)) : "memory");
          ready |= __ballot_sync(0xffffffffu, v == tag);
          asm volatile("fence.proxy.async.global;" ::: "memory");
        }
        mbar_wait(c.sb + OFF_EMPTY + (x & 0x38), x & 1);
        const uint32_t full = c.sb + OFF_FULL + 8 * (g & 7), dst = c.sb + (x & 0x3e000);
        const CUtensorMap* mp = (const CUtensorMap*)((const char*)&p + (y & 0x180));
        if (!(y & A_QUIET)) mbar_expect_e(full, y & 0x4004);
        if (!(y & A_COPY)) tma_ld4_mc_e(dst, mp, full, x & 0xfc0, c.m * 4 + c.rank * 2);
        else if (!(y & A_NONE)) { tma_ld4_e(dst, mp, full, x & 0xfc0, c.m * 4); tma_ld4_e(dst + 8192, mp, full, x & 0xfc0, c.m * 4 + 2); }
        else if (y & A_PAIR) {
          const uint32_t peer = mapa(c.sb, c.rank ^ 1);
          mbar_wait(c.sb + OFF_FULL, g < KB_LAYER);
          dsmem_copy_e(peer + 3 * 32768, c.sb + OFF_STG, peer + OFF_FULL + 8);
        }
      }
    } else if (c.w == 1) {
      float2 nx = lds64f(c.sb + OFF_PLAN + 8);
#pragma unroll 1
      for (int g = 4; g < 2 * KB_LAYER; g++) {
        const uint32_t x = __float_as_uint(nx.x), y = __float_as_uint(nx.y);
        nx = lds64f(c.sb + OFF_PLAN + g * 16 - 40);
        mbar_wait(c.sb + OFF_EMPTY + (x & 0x38), x & 1);
        const uint32_t full = c.sb + OFF_FULL + 8 * (g & 7);
        mbar_expect_e(full, y & 0x6000);
        tma_ld3_e(c.sb + (x & 0x3e000), (const CUtensorMap*)((const char*)&p + (y >> 16)), full, y & 0x3c0, x & 0xfc0, x >> 26);
      }
    } else if (c.w == 2) {
      mbar_pace(c.sb + OFF_EMPTY + 56, 0);
#pragma unroll 1
      for (int z = 0; z < 44; z++) st_tag128(g_halo + ((z & 3) * 128 + c.b) * 352 + (z >> 2) * 32 + c.lane, 0u, 0u, 0u, 0u);
      bar_arrive(BAR_FREE, 160);
#pragma unroll 1
      for (int t = 0; t < 14; t++) {
        const int layer = t >= 7, type = t - layer * 7;
        const int slab = c.m * 4;
        unsigned* flag = g_flags + c.m * 32 + c.j;
        if (type == 2 || type == 6) {
          flag += (t + 1) * 512 + c.j;
          bar_sync(BAR_RES, 160);
          fence_async_smem();
          asm volatile(ELECT "@p mbarrier.complete_tx.relaxed.cta.shared::cta.b64 [%0], 4;\n}" :: "r"(c.sb + OFF_FULL) : "memory");
          tma_st4_e(&p.st_out, c.sb + OFF_X, c.j * 128, slab);
          if (t < 13) {
            bulk_wait_read_e();
            PTL(t, 8);
            publish_e(flag++, tag);
            PTL(t, 9);
            mbar_wait(c.sb + OFF_FULL + 8, t != 2);
            mbar_wait(c.sb + OFF_EMPTY + 56, t == 2);
#pragma unroll
            for (int h = 0; h < 2; h++) tma_ld4_mc_e(c.sb + 3 * 40960 + h * 8192, &p.ld_out, c.sb + OFF_FULL + 40, c.j * 128, slab + 2 * h, 2 - c.rank);
          }
          if (t == 13) bar_sync(BAR_RES2, 160);
          tma_st4_e(&p.ld_out, c.sb + OFF_X + A_BYTES, c.j * 128 + 64, slab);
          if (t < 13) mbar_pace(c.sb + OFF_FULL + 48, t != 2);
          tma_st4_e(&p.ld_out, c.sb + OFF_X + A_BYTES + 8192, c.j * 128 + 64, slab + 2);
          bulk_wait_read_e();
          PTL(t, 11);
        } else {
          flag += (layer * 7 + (type < 2 ? 2 : 6)) * 512 + (type < 2 ? type : type - 3) * 8;
          const int col = type < 2 ? (c.j + 8 * type) * 64 : type == 3 ? c.j * 192 : (type == 4 ? 1536 : 2560) + c.j * 128;
#pragma unroll 1
          for (int ch = type == 3 ? -1 : 0; ch < (type < 2 ? 1 : 2); ch++) {
            if (type < 2) fetch_halo(c, tag, layer * 2 + type);
            bar_sync(BAR_READY, 160);
#pragma unroll 1
            for (int z = 0; z < 4; z++) {
              if (z && type != 1) bulk_wait_read_e();
              tma_st4_e(&p.st_h, c.sb + OFF_STG + z * 4096, col + (ch < 0 ? 128 : ch * 64), slab + z);
            }
            if (type == 1) { mbar_wait(c.sb + OFF_FULL, layer); mbar_arrive_e(c.sb + OFF_FULL); }
            bulk_wait_read_e();
            if (t < 12 || ch == 0) bar_arrive(BAR_FREE, 160);
          }
          PTL(t, 14);
        }
        if (t < 13) publish_e(flag, tag);
        PTL(t, 6);
      }
      if (c.lane == 0) epochs[blockIdx.x] = tag;
    } else {
      mbar_pace(c.sb + OFF_EMPTY + 8 * (c.m & 3), 0);
      PTL(14, 14);
      mbar_expect_e(c.sb + OFF_XBAR, 32768);
#pragma unroll
      for (int i = 0; i < 4; i++) tma_ld4_e(c.sb + OFF_X + i * 8192, &p.ld_x, c.sb + OFF_XBAR, c.j * 128 + (i >> 1) * 64, c.m * 4 + (i & 1) * 2);
#pragma unroll
      for (int i = 0; i < 4; i++) sts32f(c.sb + OFF_B2 + i * 128 + c.lane * 4, __bfloat162float(p.b2[c.j * 128 + i * 32 + c.lane]));
#pragma unroll 1
      for (int part = 0; part < 7; part++) {
        if (part < 5) {
          load_table(c, p, part, tag);
          mbar_arrive_e(c.sb + OFF_TBL + 8 * part);
          PTL(part, 7);
        }
        if (part < 2 || part > 4) fetch_halo(c, tag, part < 2 ? part : part - 3);
        if ((0x52 >> part) & 1) {
          const uint32_t peer = mapa(c.sb, c.rank ^ 1);
          bar_sync(BAR_RES2, 160);
          mbar_wait(c.sb + OFF_EMPTY + 56, part == 1);
          dsmem_copy_e(peer + 2 * 40960, c.sb + OFF_X + A_BYTES, peer + OFF_FULL + 32);
        }
      }
    }
  } else {
    place(c, slot);
    const int r = tid >> 3;
    const uint32_t dst = c.sb + 2 * 40960 + r * 128 + ((tid ^ r) & 7) * 16;
    const char* ga = x0 + (c.m * 128 + (r & 15) * 2 + c.wg) * 2048 + (tid & 7) * 16;
    const char* gb = w0 + r * 6144 + c.j * 128 + (tid & 7) * 16;
#pragma unroll
    for (int s = 0; s < 2; s++) {
#pragma unroll
      for (int i = 0; i < 10; i++)
        asm volatile("cp.async.cg.shared.global [%0], [%1], 16;" :: "r"(dst + s * 40960 + i * 4096),
          "l"(i < 4 ? ga + i * 65536 + s * 128 : gb + (2 * s + (i & 1)) * (32 * 6144) + (i / 2 - 2) * 2048) : "memory");
      if (!s) {
        mbar_init_e(c.sb + OFF_EMPTY + 8 * k, 8);
        mbar_init_e(c.sb + (k < 4 ? OFF_XBAR : OFF_FULL) + 8 * k, k < 4 ? 1 : 2);
        if (k < 7) mbar_init_e(c.sb + OFF_XBAR + 32 + 8 * k, k > 4 ? 256 : 1);
        else sts128(c.sb + OFF_ZERO, 0u, 0u, 0u, 0u);
        asm volatile("fence.mbarrier_init.release.cluster;\nbarrier.cluster.arrive.relaxed.aligned;" ::: "memory");
        bar_sync(BAR_EPI, 256);
      }
      asm volatile("cp.async.mbarrier.arrive.noinc.shared::cta.b64 [%0];" :: "r"(c.sb + OFF_PRE + 8 * s) : "memory");
    }
    asm volatile("barrier.cluster.wait.aligned;" ::: "memory");
    reg_alloc<232>();
    if (c.wg) { mbar_wait(c.sb + OFF_XBAR, 0); TL(-1, 4); row_stats<8>(c, 1); }
#pragma unroll 1
    for (int t = c.wg; t < 14; t += 2) {
      const int layer = t >= 7, type = t - layer * 7;
      const int g0 = layer * KB_LAYER + type * 16;
      float acc[2][96];
      if (type == 2 || type == 6) {
        init_res(c, acc, t, type == 6);
        mainloop<128, 1>(c, acc, t, type, g0, (type == 6 ? 56 : 16) - SK);
        if (t == 13) asm volatile("barrier.cluster.arrive.relaxed.aligned;" ::: "memory");
        TL(t, 4);
        continue;
      }
      if (type < 4) {
        mainloop<192, 0>(c, acc, t, type, g0, type == 1 ? 13 : 16);
        if (type < 2) { epi_qkv(c, acc, t, type); goto done; }
        finish(c, t, 1);
        bar_sync(BAR_EPI + c.wg, 256);
        mbar_wait(c.sb + OFF_TBL + 16, 0);
        epi_up<2>(c, acc, type);
      } else {
        mainloop<128, 0>(c, acc, t, type, g0, 16);
        finish(c, t, 7);
        bar_sync(BAR_EPI + c.wg, 256);
        mbar_wait(c.sb + OFF_TBL + 8 * (type - 1), 0);
      }
      epi_up<0>(c, acc, type);
      TL(t, 4);
    done:
      if (type != 1 && type != 5) bar_arrive(BAR_EPI + (c.wg ^ 1), 256);
    }
    if (c.wg == 1) {
      asm volatile("barrier.cluster.wait.aligned;" ::: "memory");
    }
  }
}

typedef CUresult (*EncodeFn)(CUtensorMap*, CUtensorMapDataType, cuuint32_t, void*, const cuuint64_t*, const cuuint64_t*,
                             const cuuint32_t*, const cuuint32_t*, CUtensorMapInterleave, CUtensorMapSwizzle,
                             CUtensorMapL2promotion, CUtensorMapFloatOOBfill);

void make_map(EncodeFn fn, CUtensorMap* m, const void* ptr, int rank, const cuuint64_t* dims, const cuuint64_t* strides, const cuuint32_t* box) {
  const cuuint32_t es[4] = {1, 1, 1, 1};
  fn(m, CU_TENSOR_MAP_DATA_TYPE_BFLOAT16, rank, const_cast<void*>(ptr), dims, strides, box, es, CU_TENSOR_MAP_INTERLEAVE_NONE,
     CU_TENSOR_MAP_SWIZZLE_128B, CU_TENSOR_MAP_L2_PROMOTION_L2_128B, CU_TENSOR_MAP_FLOAT_OOB_FILL_NONE);
}
void map_rows(EncodeFn fn, CUtensorMap* m, const void* ptr, int cols, int rows, int box_slabs, bool tokens) {
  const cuuint64_t rb = (cuuint64_t)cols * 2;
  const cuuint64_t dims[4] = {(cuuint64_t)cols, 16, 2, (cuuint64_t)(rows / 32)};
  const cuuint64_t st[3] = {tokens ? 2 * rb : rb, tokens ? rb : 16 * rb, 32 * rb};
  const cuuint32_t box[4] = {64, 16, 2, (cuuint32_t)box_slabs};
  make_map(fn, m, ptr, 4, dims, st, box);
}
void map_w(EncodeFn fn, CUtensorMap* m, const void* ptr, int K, int N, int inner, int nch) {
  const cuuint64_t dims[3] = {(cuuint64_t)inner, (cuuint64_t)K, (cuuint64_t)(N / inner)}, st[2] = {(cuuint64_t)N * 2, (cuuint64_t)inner * 2};
  const cuuint32_t box[3] = {64, 64, (cuuint32_t)nch};
  make_map(fn, m, ptr, 3, dims, st, box);
}

}

extern "C" void kernel_launch(void* const* d_in, const int* in_sizes, int n_in, void* d_out, int out_size) {
  (void)in_sizes; (void)n_in; (void)out_size;
  Params p;
  p.b1 = (const __nv_bfloat16*)d_in[5]; p.b2 = (const __nv_bfloat16*)d_in[7];
  void* fnp = nullptr; cudaDriverEntryPointQueryResult qr;
  cudaGetDriverEntryPoint("cuTensorMapEncodeTiled", &fnp, cudaEnableDefault, &qr);
  EncodeFn fn = (EncodeFn)fnp;
  void *h, *epochs;
  cudaGetSymbolAddress(&h, g_h);
  cudaGetSymbolAddress(&epochs, g_plan);
  map_rows(fn, &p.ld_x, d_in[0], D_, S_, 2, true);
  map_rows(fn, &p.ld_out, d_out, D_, S_, 2, true);
  map_rows(fn, &p.ld_h, h, F_, S_, 2, false);
  map_rows(fn, &p.st_h, h, F_, S_, 1, false);
  map_rows(fn, &p.st_out, d_out, D_, S_, 4, true);
  map_w(fn, &p.w_qkv, d_in[1], D_, 3 * D_, D_, 3);
  map_w(fn, &p.w_o, d_in[2], D_, D_, 64, 2);
  map_w(fn, &p.w_1a, d_in[4], D_, F_, 64, 3);
  map_w(fn, &p.w_1b, d_in[4], D_, F_, 64, 2);
  map_w(fn, &p.w_2, d_in[6], F_, D_, 64, 2);
  cudaFuncSetAttribute(fused_kernel, cudaFuncAttributeMaxDynamicSharedMemorySize, SMEM_BYTES);
  fused_kernel<<<132, 384, SMEM_BYTES>>>((unsigned*)epochs, (const char*)d_in[0], (const char*)d_in[1], p);
}
```

```cpp
#include <cuda_runtime.h>
#include <cuda_bf16.h>
#include <cuda.h>
#include <stdint.h>

#define EXP 0
namespace {

constexpr int S_ = 2048, D_ = 1024, F_ = 3584;
constexpr int A_BYTES = 16384;
constexpr int OFF_X   = 163840;
constexpr int OFF_STG = OFF_X + 32768;
constexpr int OFF_CSQ = OFF_STG + 20480;
constexpr int OFF_UP  = OFF_CSQ + 1536;
constexpr int OFF_B2  = OFF_UP + 3584;
constexpr int OFF_RST = OFF_B2 + 512 + 256;
constexpr int OFF_FULL = OFF_RST + 1024;
constexpr int OFF_EMPTY = OFF_FULL + 64;
constexpr int OFF_XBAR = OFF_EMPTY + 64;
constexpr int OFF_TBL = OFF_XBAR + 8;
constexpr int OFF_HALO = OFF_XBAR + 48;
constexpr int OFF_SLOT = OFF_XBAR + 88;
constexpr int OFF_PRE = OFF_XBAR + 72;
constexpr int OFF_ZERO = OFF_XBAR + 96;
constexpr int OFF_TAG = OFF_ZERO + 16;
constexpr int OFF_PLAN = OFF_TAG + 16, PLAN_BYTES = 5120;
constexpr int SMEM_BYTES = OFF_PLAN + PLAN_BYTES + 48 + 1024;
constexpr int KB_LAYER = 6 * 16 + 56;
constexpr int NCS = 384 + 448;
constexpr unsigned SPIN_LIMIT = 1u << 20;
constexpr int NS = 12, NP = 8, SA = 7, SB = 11, PAUSE1 = 7, PAUSE2 = 8, HGK = 8, HGO = 11, HG1 = 3;
constexpr int SK = 3;
constexpr uint32_t DESC_A = 1u << 16, DESC_B = (512u << 16) + A_BYTES / 16;
enum { BAR_START = 1, BAR_EPI = 3, BAR_WG = 5, BAR_P0 = 7, BAR_P1 = 8, BAR_RES = 9, BAR_READY = 10, BAR_FREE = 11, BAR_COPY = 12, BAR_RES2 = 13, BAR_HGO = 14 };

struct Params {
  CUtensorMap ld_x, ld_out, ld_h, st_h, st_out, w_qkv, w_o, w_1a, w_1b, w_2;
  const __nv_bfloat16 *b1, *b2;
};

__device__ __align__(1024) __nv_bfloat16 g_h[S_ * F_];
__device__ __align__(128) uint4 g_stats[4 * S_ * 8];
__device__ __align__(128) uint2 g_cs[8 * NCS];
__device__ __align__(128) uint4 g_halo[4 * 128 * 11 * 32];
__device__ __align__(128) unsigned g_flags[14 * 16 * 32];
#define TL(t, e)
#define PTL(t, e)
#if !defined(TIMELINE) || !(EXP & 8)
#undef TK
#define TK(t, k)
#endif

template<int N, int KEEP> __device__ __forceinline__ void wgmma_ss(float (&d)[96], uint32_t da, uint32_t db);
template<> __device__ __forceinline__ void wgmma_ss<128, 0>(float (&d)[96], uint32_t da, uint32_t db) {
  asm volatile("{\n.reg .pred p;\n.reg .b64 a, b;\nsetp.ne.b32 p, 0, 0;\nmov.b64 a, {%64, 0x40000080};\nmov.b64 b, {%65, 0x40000040};\nwgmma.mma_async.sync.aligned.m64n128k16.f32.bf16.bf16 {%0, %1, %2, %3, %4, %5, %6, %7, %8, %9, %10, %11, %12, %13, %14, %15, %16, %17, %18, %19, %20, %21, %22, %23, %24, %25, %26, %27, %28, %29, %30, %31, %32, %33, %34, %35, %36, %37, %38, %39, %40, %41, %42, %43, %44, %45, %46, %47, %48, %49, %50, %51, %52, %53, %54, %55, %56, %57, %58, %59, %60, %61, %62, %63}, a, b, p, 1, 1, 0, 1;\n}"
    : "=f"(d[0]), "=f"(d[1]), "=f"(d[2]), "=f"(d[3]), "=f"(d[4]), "=f"(d[5]), "=f"(d[6]), "=f"(d[7]), "=f"(d[8]), "=f"(d[9]), "=f"(d[10]), "=f"(d[11]), "=f"(d[12]), "=f"(d[13]), "=f"(d[14]), "=f"(d[15]), "=f"(d[16]), "=f"(d[17]), "=f"(d[18]), "=f"(d[19]), "=f"(d[20]), "=f"(d[21]), "=f"(d[22]), "=f"(d[23]), "=f"(d[24]), "=f"(d[25]), "=f"(d[26]), "=f"(d[27]), "=f"(d[28]), "=f"(d[29]), "=f"(d[30]), "=f"(d[31]), "=f"(d[32]), "=f"(d[33]), "=f"(d[34]), "=f"(d[35]), "=f"(d[36]), "=f"(d[37]), "=f"(d[38]), "=f"(d[39]), "=f"(d[40]), "=f"(d[41]), "=f"(d[42]), "=f"(d[43]), "=f"(d[44]), "=f"(d[45]), "=f"(d[46]), "=f"(d[47]), "=f"(d[48]), "=f"(d[49]), "=f"(d[50]), "=f"(d[51]), "=f"(d[52]), "=f"(d[53]), "=f"(d[54]), "=f"(d[55]), "=f"(d[56]), "=f"(d[57]), "=f"(d[58]), "=f"(d[59]), "=f"(d[60]), "=f"(d[61]), "=f"(d[62]), "=f"(d[63])
    : "r"(da), "r"(db));
}
template<> __device__ __forceinline__ void wgmma_ss<128, 1>(float (&d)[96], uint32_t da, uint32_t db) {
  asm volatile("{\n.reg .pred p;\n.reg .b64 a, b;\nsetp.ne.b32 p, 1, 0;\nmov.b64 a, {%64, 0x40000080};\nmov.b64 b, {%65, 0x40000040};\nwgmma.mma_async.sync.aligned.m64n128k16.f32.bf16.bf16 {%0, %1, %2, %3, %4, %5, %6, %7, %8, %9, %10, %11, %12, %13, %14, %15, %16, %17, %18, %19, %20, %21, %22, %23, %24, %25, %26, %27, %28, %29, %30, %31, %32, %33, %34, %35, %36, %37, %38, %39, %40, %41, %42, %43, %44, %45, %46, %47, %48, %49, %50, %51, %52, %53, %54, %55, %56, %57, %58, %59, %60, %61, %62, %63}, a, b, p, 1, 1, 0, 1;\n}"
    : "+f"(d[0]), "+f"(d[1]), "+f"(d[2]), "+f"(d[3]), "+f"(d[4]), "+f"(d[5]), "+f"(d[6]), "+f"(d[7]), "+f"(d[8]), "+f"(d[9]), "+f"(d[10]), "+f"(d[11]), "+f"(d[12]), "+f"(d[13]), "+f"(d[14]), "+f"(d[15]), "+f"(d[16]), "+f"(d[17]), "+f"(d[18]), "+f"(d[19]), "+f"(d[20]), "+f"(d[21]), "+f"(d[22]), "+f"(d[23]), "+f"(d[24]), "+f"(d[25]), "+f"(d[26]), "+f"(d[27]), "+f"(d[28]), "+f"(d[29]), "+f"(d[30]), "+f"(d[31]), "+f"(d[32]), "+f"(d[33]), "+f"(d[34]), "+f"(d[35]), "+f"(d[36]), "+f"(d[37]), "+f"(d[38]), "+f"(d[39]), "+f"(d[40]), "+f"(d[41]), "+f"(d[42]), "+f"(d[43]), "+f"(d[44]), "+f"(d[45]), "+f"(d[46]), "+f"(d[47]), "+f"(d[48]), "+f"(d[49]), "+f"(d[50]), "+f"(d[51]), "+f"(d[52]), "+f"(d[53]), "+f"(d[54]), "+f"(d[55]), "+f"(d[56]), "+f"(d[57]), "+f"(d[58]), "+f"(d[59]), "+f"(d[60]), "+f"(d[61]), "+f"(d[62]), "+f"(d[63])
    : "r"(da), "r"(db));
}
template<> __device__ __forceinline__ void wgmma_ss<192, 0>(float (&d)[96], uint32_t da, uint32_t db) {
  asm volatile("{\n.reg .pred p;\n.reg .b64 a, b;\nsetp.ne.b32 p, 0, 0;\nmov.b64 a, {%96, 0x40000080};\nmov.b64 b, {%97, 0x40000040};\nwgmma.mma_async.sync.aligned.m64n192k16.f32.bf16.bf16 {%0, %1, %2, %3, %4, %5, %6, %7, %8, %9, %10, %11, %12, %13, %14, %15, %16, %17, %18, %19, %20, %21, %22, %23, %24, %25, %26, %27, %28, %29, %30, %31, %32, %33, %34, %35, %36, %37, %38, %39, %40, %41, %42, %43, %44, %45, %46, %47, %48, %49, %50, %51, %52, %53, %54, %55, %56, %57, %58, %59, %60, %61, %62, %63, %64, %65, %66, %67, %68, %69, %70, %71, %72, %73, %74, %75, %76, %77, %78, %79, %80, %81, %82, %83, %84, %85, %86, %87, %88, %89, %90, %91, %92, %93, %94, %95}, a, b, p, 1, 1, 0, 1;\n}"
    : "=f"(d[0]), "=f"(d[1]), "=f"(d[2]), "=f"(d[3]), "=f"(d[4]), "=f"(d[5]), "=f"(d[6]), "=f"(d[7]), "=f"(d[8]), "=f"(d[9]), "=f"(d[10]), "=f"(d[11]), "=f"(d[12]), "=f"(d[13]), "=f"(d[14]), "=f"(d[15]), "=f"(d[16]), "=f"(d[17]), "=f"(d[18]), "=f"(d[19]), "=f"(d[20]), "=f"(d[21]), "=f"(d[22]), "=f"(d[23]), "=f"(d[24]), "=f"(d[25]), "=f"(d[26]), "=f"(d[27]), "=f"(d[28]), "=f"(d[29]), "=f"(d[30]), "=f"(d[31]), "=f"(d[32]), "=f"(d[33]), "=f"(d[34]), "=f"(d[35]), "=f"(d[36]), "=f"(d[37]), "=f"(d[38]), "=f"(d[39]), "=f"(d[40]), "=f"(d[41]), "=f"(d[42]), "=f"(d[43]), "=f"(d[44]), "=f"(d[45]), "=f"(d[46]), "=f"(d[47]), "=f"(d[48]), "=f"(d[49]), "=f"(d[50]), "=f"(d[51]), "=f"(d[52]), "=f"(d[53]), "=f"(d[54]), "=f"(d[55]), "=f"(d[56]), "=f"(d[57]), "=f"(d[58]), "=f"(d[59]), "=f"(d[60]), "=f"(d[61]), "=f"(d[62]), "=f"(d[63]), "=f"(d[64]), "=f"(d[65]), "=f"(d[66]), "=f"(d[67]), "=f"(d[68]), "=f"(d[69]), "=f"(d[70]), "=f"(d[71]), "=f"(d[72]), "=f"(d[73]), "=f"(d[74]), "=f"(d[75]), "=f"(d[76]), "=f"(d[77]), "=f"(d[78]), "=f"(d[79]), "=f"(d[80]), "=f"(d[81]), "=f"(d[82]), "=f"(d[83]), "=f"(d[84]), "=f"(d[85]), "=f"(d[86]), "=f"(d[87]), "=f"(d[88]), "=f"(d[89]), "=f"(d[90]), "=f"(d[91]), "=f"(d[92]), "=f"(d[93]), "=f"(d[94]), "=f"(d[95])
    : "r"(da), "r"(db));
}
template<> __device__ __forceinline__ void wgmma_ss<192, 1>(float (&d)[96], uint32_t da, uint32_t db) {
  asm volatile("{\n.reg .pred p;\n.reg .b64 a, b;\nsetp.ne.b32 p, 1, 0;\nmov.b64 a, {%96, 0x40000080};\nmov.b64 b, {%97, 0x40000040};\nwgmma.mma_async.sync.aligned.m64n192k16.f32.bf16.bf16 {%0, %1, %2, %3, %4, %5, %6, %7, %8, %9, %10, %11, %12, %13, %14, %15, %16, %17, %18, %19, %20, %21, %22, %23, %24, %25, %26, %27, %28, %29, %30, %31, %32, %33, %34, %35, %36, %37, %38, %39, %40, %41, %42, %43, %44, %45, %46, %47, %48, %49, %50, %51, %52, %53, %54, %55, %56, %57, %58, %59, %60, %61, %62, %63, %64, %65, %66, %67, %68, %69, %70, %71, %72, %73, %74, %75, %76, %77, %78, %79, %80, %81, %82, %83, %84, %85, %86, %87, %88, %89, %90, %91, %92, %93, %94, %95}, a, b, p, 1, 1, 0, 1;\n}"
    : "+f"(d[0]), "+f"(d[1]), "+f"(d[2]), "+f"(d[3]), "+f"(d[4]), "+f"(d[5]), "+f"(d[6]), "+f"(d[7]), "+f"(d[8]), "+f"(d[9]), "+f"(d[10]), "+f"(d[11]), "+f"(d[12]), "+f"(d[13]), "+f"(d[14]), "+f"(d[15]), "+f"(d[16]), "+f"(d[17]), "+f"(d[18]), "+f"(d[19]), "+f"(d[20]), "+f"(d[21]), "+f"(d[22]), "+f"(d[23]), "+f"(d[24]), "+f"(d[25]), "+f"(d[26]), "+f"(d[27]), "+f"(d[28]), "+f"(d[29]), "+f"(d[30]), "+f"(d[31]), "+f"(d[32]), "+f"(d[33]), "+f"(d[34]), "+f"(d[35]), "+f"(d[36]), "+f"(d[37]), "+f"(d[38]), "+f"(d[39]), "+f"(d[40]), "+f"(d[41]), "+f"(d[42]), "+f"(d[43]), "+f"(d[44]), "+f"(d[45]), "+f"(d[46]), "+f"(d[47]), "+f"(d[48]), "+f"(d[49]), "+f"(d[50]), "+f"(d[51]), "+f"(d[52]), "+f"(d[53]), "+f"(d[54]), "+f"(d[55]), "+f"(d[56]), "+f"(d[57]), "+f"(d[58]), "+f"(d[59]), "+f"(d[60]), "+f"(d[61]), "+f"(d[62]), "+f"(d[63]), "+f"(d[64]), "+f"(d[65]), "+f"(d[66]), "+f"(d[67]), "+f"(d[68]), "+f"(d[69]), "+f"(d[70]), "+f"(d[71]), "+f"(d[72]), "+f"(d[73]), "+f"(d[74]), "+f"(d[75]), "+f"(d[76]), "+f"(d[77]), "+f"(d[78]), "+f"(d[79]), "+f"(d[80]), "+f"(d[81]), "+f"(d[82]), "+f"(d[83]), "+f"(d[84]), "+f"(d[85]), "+f"(d[86]), "+f"(d[87]), "+f"(d[88]), "+f"(d[89]), "+f"(d[90]), "+f"(d[91]), "+f"(d[92]), "+f"(d[93]), "+f"(d[94]), "+f"(d[95])
    : "r"(da), "r"(db));
}
template<> __device__ __forceinline__ void wgmma_ss<128, 2>(float (&d)[96], uint32_t da, uint32_t db) {
  asm volatile("{\n.reg .pred p;\n.reg .b64 a, b;\nsetp.ne.b32 p, 2, 0;\nmov.b64 a, {%64, 0x40000040};\nmov.b64 b, {%65, 0x40000040};\nwgmma.mma_async.sync.aligned.m64n128k16.f32.bf16.bf16 {%0, %1, %2, %3, %4, %5, %6, %7, %8, %9, %10, %11, %12, %13, %14, %15, %16, %17, %18, %19, %20, %21, %22, %23, %24, %25, %26, %27, %28, %29, %30, %31, %32, %33, %34, %35, %36, %37, %38, %39, %40, %41, %42, %43, %44, %45, %46, %47, %48, %49, %50, %51, %52, %53, %54, %55, %56, %57, %58, %59, %60, %61, %62, %63}, b, a, p, 1, 1, 1, 0;\n}"
    : "+f"(d[0]), "+f"(d[1]), "+f"(d[2]), "+f"(d[3]), "+f"(d[4]), "+f"(d[5]), "+f"(d[6]), "+f"(d[7]), "+f"(d[8]), "+f"(d[9]), "+f"(d[10]), "+f"(d[11]), "+f"(d[12]), "+f"(d[13]), "+f"(d[14]), "+f"(d[15]), "+f"(d[16]), "+f"(d[17]), "+f"(d[18]), "+f"(d[19]), "+f"(d[20]), "+f"(d[21]), "+f"(d[22]), "+f"(d[23]), "+f"(d[24]), "+f"(d[25]), "+f"(d[26]), "+f"(d[27]), "+f"(d[28]), "+f"(d[29]), "+f"(d[30]), "+f"(d[31]), "+f"(d[32]), "+f"(d[33]), "+f"(d[34]), "+f"(d[35]), "+f"(d[36]), "+f"(d[37]), "+f"(d[38]), "+f"(d[39]), "+f"(d[40]), "+f"(d[41]), "+f"(d[42]), "+f"(d[43]), "+f"(d[44]), "+f"(d[45]), "+f"(d[46]), "+f"(d[47]), "+f"(d[48]), "+f"(d[49]), "+f"(d[50]), "+f"(d[51]), "+f"(d[52]), "+f"(d[53]), "+f"(d[54]), "+f"(d[55]), "+f"(d[56]), "+f"(d[57]), "+f"(d[58]), "+f"(d[59]), "+f"(d[60]), "+f"(d[61]), "+f"(d[62]), "+f"(d[63])
    : "r"(da), "r"(db));
}

__device__ __forceinline__ uint32_t smem_u32(const void* p) { return (uint32_t)__cvta_generic_to_shared(p); }
__device__ __forceinline__ void mbar_arrive_cluster(uint32_t bar) { asm volatile("mbarrier.arrive.shared::cluster.b64 _, [%0];" :: "r"(bar) : "memory"); }
__device__ __forceinline__ void mbar_wait(uint32_t bar, uint32_t parity) {
  asm volatile(
    "{\n.reg .pred p;\n.reg .u32 n;\n"
    "mbarrier.try_wait.parity.shared::cta.b64 p, [%0], %1;\n"
    "@p bra.uni WAIT_DONE;\n"
    "mov.u32 n, 0;\n"
    "WAIT_LOOP:\n"
    "mbarrier.try_wait.parity.shared::cta.b64 p, [%0], %1;\n"
    "@p bra.uni WAIT_DONE;\n"
    "add.u32 n, n, 1;\n"
    "setp.lt.u32 p, n, 0x100000;\n"
    "@p bra.uni WAIT_LOOP;\n"
    "trap;\n"
    "WAIT_DONE:\n}" :: "r"(bar), "r"(parity) : "memory");
}
__device__ __forceinline__ void mbar_pace(uint32_t bar, uint32_t parity) {
  asm volatile(
    "{\n.reg .pred p;\n.reg .u32 n;\nmov.u32 n, 0;\n"
    "PACE_LOOP:\n"
    "mbarrier.try_wait.parity.shared::cta.b64 p, [%0], %1, 1000;\n"
    "add.u32 n, n, 1;\n"
    "setp.lt.and.u32 p, n, 16, !p;\n"
    "@p bra.uni PACE_LOOP;\n}" :: "r"(bar), "r"(parity) : "memory");
}
__device__ __forceinline__ uint32_t mbar_test(uint32_t bar, uint32_t parity) {
  uint32_t ok;
  asm volatile("{\n.reg .pred p;\nmbarrier.test_wait.parity.shared::cta.b64 p, [%1], %2;\nselp.u32 %0, 1, 0, p;\n}" : "=r"(ok) : "r"(bar), "r"(parity) : "memory");
  return ok;
}
#define ELECT "{\n.reg .pred p;\nelect.sync _|p, 0xffffffff;\n"
__device__ __forceinline__ void mbar_init_e(uint32_t bar, uint32_t cnt) { asm volatile(ELECT "@p mbarrier.init.shared::cta.b64 [%0], %1;\n}" :: "r"(bar), "r"(cnt) : "memory"); }
__device__ __forceinline__ void mbar_arrive_e(uint32_t bar) { asm volatile(ELECT "@p mbarrier.arrive.shared::cta.b64 _, [%0];\n}" :: "r"(bar) : "memory"); }
__device__ __forceinline__ void mbar_expect_e(uint32_t bar, uint32_t bytes) { asm volatile(ELECT "@p mbarrier.arrive.expect_tx.shared::cta.b64 _, [%0], %1;\n}" :: "r"(bar), "r"(bytes) : "memory"); }
__device__ __forceinline__ void tma_ld4_e(uint32_t dst, const CUtensorMap* m, uint32_t bar, int c0, int c3) {
  asm volatile(ELECT "@p cp.async.bulk.tensor.4d.shared::cluster.global.mbarrier::complete_tx::bytes [%0], [%1, {%3, %5, %5, %4}], [%2];\n}"
    :: "r"(dst), "l"(m), "r"(bar), "r"(c0), "r"(c3), "r"(0) : "memory");
}
__device__ __forceinline__ void tma_ld4_mc_e(uint32_t dst, const CUtensorMap* m, uint32_t bar, int c0, int c3, uint16_t mask = 3) {
  asm volatile(ELECT "@p cp.async.bulk.tensor.4d.shared::cluster.global.mbarrier::complete_tx::bytes.multicast::cluster [%0], [%1, {%3, %5, %5, %4}], [%2], %6;\n}"
    :: "r"(dst), "l"(m), "r"(bar), "r"(c0), "r"(c3), "r"(0), "h"(mask) : "memory");
}
__device__ __forceinline__ void tma_ld3_e(uint32_t dst, const CUtensorMap* m, uint32_t bar, int c0, int c1, int c2) {
  asm volatile(ELECT "@p cp.async.bulk.tensor.3d.shared::cluster.global.mbarrier::complete_tx::bytes [%0], [%1, {%3, %4, %5}], [%2];\n}"
    :: "r"(dst), "l"(m), "r"(bar), "r"(c0), "r"(c1), "r"(c2) : "memory");
}
__device__ __forceinline__ void tma_st4_e(const CUtensorMap* m, uint32_t src, int c0, int c3) {
  asm volatile(ELECT "@p cp.async.bulk.tensor.4d.global.shared::cta.bulk_group [%0, {%2, %4, %4, %3}], [%1];\n}"
    :: "l"(m), "r"(src), "r"(c0), "r"(c3), "r"(0) : "memory");
}
__device__ __forceinline__ void dsmem_copy_e(uint32_t dst, uint32_t src, uint32_t bar) {
  asm volatile(ELECT "@p cp.async.bulk.shared::cluster.shared::cta.mbarrier::complete_tx::bytes [%0], [%1], 16384, [%2];\n}"
    :: "r"(dst), "r"(src), "r"(bar) : "memory");
}
__device__ __forceinline__ void bulk_wait_read_e() { asm volatile(ELECT "@p cp.async.bulk.commit_group;\n@p cp.async.bulk.wait_group.read 0;\n}" ::: "memory"); __syncwarp(); }
__device__ __forceinline__ void publish_e(unsigned* flag, unsigned tag) {
  asm volatile(ELECT "@p fence.proxy.async;\n@p st.relaxed.gpu.global.u32 [%0], %1;\n}" :: "l"(flag), "r"(tag) : "memory");
  __syncwarp();
}
__device__ __forceinline__ void fence_async_smem() { asm volatile("fence.proxy.async.shared::cta;" ::: "memory"); }
__device__ __forceinline__ void wgmma_fence() { asm volatile("wgmma.fence.sync.aligned;" ::: "memory"); }
__device__ __forceinline__ void wgmma_commit() { asm volatile("wgmma.commit_group.sync.aligned;" ::: "memory"); }
template<int N> __device__ __forceinline__ void wgmma_wait() { asm volatile("wgmma.wait_group.sync.aligned %0;" :: "n"(N) : "memory"); }
__device__ __forceinline__ void bar_sync(int id, int n) { asm volatile("bar.sync %0, %1;" :: "r"(id), "r"(n) : "memory"); }
__device__ __forceinline__ void bar_arrive(int id, int n) { asm volatile("bar.arrive %0, %1;" :: "r"(id), "r"(n) : "memory"); }
__device__ __forceinline__ void bar_arrive_here(int id, float dep, float zero) {
  asm volatile("{\n.reg .pred p;\n.reg .u32 n;\nsetp.ne.u32 p, %2, 0;\nor.b32 n, %1, 256;\nmin.u32 n, n, 256;\nAGAIN:\nbar.arrive %0, n;\n@p bra.uni AGAIN;\n}"
    :: "r"(id), "r"(__float_as_uint(dep)), "r"(__float_as_uint(zero)) : "memory");
}
__device__ __forceinline__ void bar_sync_after(int id, uint32_t dep) {
  asm volatile("{\n.reg .u32 n;\nor.b32 n, %1, 256;\nmin.u32 n, n, 256;\nbar.sync %0, n;\n}" :: "r"(id), "r"(dep) : "memory");
}
__device__ __forceinline__ uint32_t mapa(uint32_t a, uint32_t r) { uint32_t d; asm("mapa.shared::cluster.u32 %0, %1, %2;" : "=r"(d) : "r"(a), "r"(r)); return d; }
__device__ __forceinline__ void st_tag128(uint4* p, uint32_t a, uint32_t b, uint32_t c, uint32_t tag) {
  asm volatile("{\n.reg .b64 lo, hi;\n.reg .b128 v;\nmov.b64 lo, {%1, %2};\nmov.b64 hi, {%3, %4};\nmov.b128 v, {lo, hi};\nst.relaxed.gpu.global.b128 [%0], v;\n}"
    :: "l"(p), "r"(a), "r"(b), "r"(c), "r"(tag) : "memory");
}
__device__ __forceinline__ void st_tag128_if(bool on, uint4* p, uint32_t a, uint32_t b, uint32_t c, uint32_t tag) {
  asm volatile("{\n.reg .pred q;\n.reg .b64 lo, hi;\n.reg .b128 v;\nsetp.ne.u32 q, %5, 0;\nmov.b64 lo, {%1, %2};\nmov.b64 hi, {%3, %4};\nmov.b128 v, {lo, hi};\n@q st.relaxed.gpu.global.b128 [%0], v;\n}"
    :: "l"(p), "r"(a), "r"(b), "r"(c), "r"(tag), "r"((uint32_t)on) : "memory");
}
__device__ __forceinline__ uint4 ld_tag128(const uint4* p) {
  uint4 v;
  asm volatile("{\n.reg .b64 lo, hi;\n.reg .b128 v;\nld.relaxed.gpu.global.b128 v, [%4];\nmov.b128 {lo, hi}, v;\nmov.b64 {%0, %1}, lo;\nmov.b64 {%2, %3}, hi;\n}"
    : "=r"(v.x), "=r"(v.y), "=r"(v.z), "=r"(v.w) : "l"(p) : "memory");
  return v;
}
__device__ __forceinline__ void st_tag64(uint2* p, float a, uint32_t tag) {
  asm volatile("{\n.reg .b64 v;\nmov.b64 v, {%1, %2};\nst.relaxed.gpu.global.b64 [%0], v;\n}" :: "l"(p), "r"(__float_as_uint(a)), "r"(tag) : "memory");
}
__device__ __forceinline__ uint2 ld_tag64(const uint2* p) {
  uint2 v;
  asm volatile("{\n.reg .b64 v;\nld.relaxed.gpu.global.b64 v, [%2];\nmov.b64 {%0, %1}, v;\n}" : "=r"(v.x), "=r"(v.y) : "l"(p) : "memory");
  return v;
}
__device__ __forceinline__ uint32_t pack_bf16(float lo, float hi) { uint32_t r; asm("cvt.rn.bf16x2.f32 %0, %1, %2;" : "=r"(r) : "f"(hi), "f"(lo)); return r; }
__device__ __forceinline__ uint32_t relu_sq_bf16(float lo, float hi) {
  uint32_t r; asm("{\n.reg .b32 t;\ncvt.rn.relu.bf16x2.f32 t, %1, %2;\nmul.rn.bf16x2 %0, t, t;\n}" : "=r"(r) : "f"(hi), "f"(lo)); return r;
}
__device__ __forceinline__ float bf_lo(uint32_t u) { return __uint_as_float(u << 16); }
__device__ __forceinline__ float bf_hi(uint32_t u) { return __uint_as_float(u & 0xffff0000u); }
__device__ __forceinline__ void stmatrix4(uint32_t addr, uint32_t r0, uint32_t r1, uint32_t r2, uint32_t r3) {
  asm volatile("stmatrix.sync.aligned.m8n8.x4.shared.b16 [%0], {%1, %2, %3, %4};" :: "r"(addr), "r"(r0), "r"(r1), "r"(r2), "r"(r3) : "memory");
}
__device__ __forceinline__ void ldmatrix4(uint32_t addr, uint32_t (&r)[4]) {
  asm volatile("ldmatrix.sync.aligned.m8n8.x4.shared.b16 {%0, %1, %2, %3}, [%4];" : "=r"(r[0]), "=r"(r[1]), "=r"(r[2]), "=r"(r[3]) : "r"(addr) : "memory");
}
__device__ __forceinline__ void stmatrix4_t(uint32_t addr, uint32_t r0, uint32_t r1, uint32_t r2, uint32_t r3) {
  asm volatile("stmatrix.sync.aligned.m8n8.x4.trans.shared.b16 [%0], {%1, %2, %3, %4};" :: "r"(addr), "r"(r0), "r"(r1), "r"(r2), "r"(r3) : "memory");
}
__device__ __forceinline__ void ldmatrix4_t(uint32_t addr, uint32_t (&r)[4]) {
  asm volatile("ldmatrix.sync.aligned.m8n8.x4.trans.shared.b16 {%0, %1, %2, %3}, [%4];" : "=r"(r[0]), "=r"(r[1]), "=r"(r[2]), "=r"(r[3]) : "r"(addr) : "memory");
}
__device__ __forceinline__ uint32_t movmatrix(uint32_t a) { uint32_t d; asm volatile("movmatrix.sync.aligned.m8n8.trans.b16 %0, %1;" : "=r"(d) : "r"(a)); return d; }
__device__ __forceinline__ void mma16816_z(float (&c)[4], uint32_t a0, uint32_t a1, uint32_t a2, uint32_t a3, uint32_t b0, uint32_t b1, const float4& z) {
  asm volatile("mma.sync.aligned.m16n8k16.row.col.f32.bf16.bf16.f32 {%0,%1,%2,%3}, {%4,%5,%6,%7}, {%8,%9}, {%10,%11,%12,%13};"
    : "=f"(c[0]), "=f"(c[1]), "=f"(c[2]), "=f"(c[3]) : "r"(a0), "r"(a1), "r"(a2), "r"(a3), "r"(b0), "r"(b1), "f"(z.x), "f"(z.y), "f"(z.z), "f"(z.w));
}
__device__ __forceinline__ float ex2(float x) { float y; asm("ex2.approx.ftz.f32 %0, %1;" : "=f"(y) : "f"(x)); return y; }
__device__ __forceinline__ float rcp(float x) { float y; asm("rcp.approx.ftz.f32 %0, %1;" : "=f"(y) : "f"(x)); return y; }
__device__ __forceinline__ void mma16816(float (&c)[4], uint32_t a0, uint32_t a1, uint32_t a2, uint32_t a3, uint32_t b0, uint32_t b1) {
  asm volatile("mma.sync.aligned.m16n8k16.row.col.f32.bf16.bf16.f32 {%0,%1,%2,%3}, {%4,%5,%6,%7}, {%8,%9}, {%0,%1,%2,%3};"
    : "+f"(c[0]), "+f"(c[1]), "+f"(c[2]), "+f"(c[3]) : "r"(a0), "r"(a1), "r"(a2), "r"(a3), "r"(b0), "r"(b1));
}
__device__ __forceinline__ void sts128(uint32_t a, uint32_t x, uint32_t y, uint32_t z, uint32_t w) { asm volatile("st.shared.v4.b32 [%0], {%1,%2,%3,%4};" :: "r"(a), "r"(x), "r"(y), "r"(z), "r"(w) : "memory"); }
__device__ __forceinline__ float2 lds64f(uint32_t a) { float2 v; asm volatile("ld.shared.v2.f32 {%0,%1}, [%2];" : "=f"(v.x), "=f"(v.y) : "r"(a) : "memory"); return v; }
__device__ __forceinline__ float4 lds128f(uint32_t a) { float4 v; asm volatile("ld.shared.v4.f32 {%0,%1,%2,%3}, [%4];" : "=f"(v.x), "=f"(v.y), "=f"(v.z), "=f"(v.w) : "r"(a) : "memory"); return v; }
__device__ __forceinline__ void sts32f(uint32_t a, float v) { asm volatile("st.shared.f32 [%0], %1;" :: "r"(a), "f"(v) : "memory"); }
__device__ __forceinline__ void sts64f(uint32_t a, float x, float y) { asm volatile("st.shared.v2.f32 [%0], {%1,%2};" :: "r"(a), "f"(x), "f"(y) : "memory"); }
__device__ __forceinline__ uint32_t lds32(uint32_t a) { uint32_t v; asm volatile("ld.shared.u32 %0, [%1];" : "=r"(v) : "r"(a) : "memory"); return v; }
__device__ __forceinline__ float after(float x, uint32_t d, uint32_t zero) { return __uint_as_float(__float_as_uint(x) | (d & zero)); }
template<int R> __device__ __forceinline__ void reg_alloc() { asm volatile("setmaxnreg.inc.sync.aligned.u32 %0;" :: "n"(R)); }
template<int R> __device__ __forceinline__ void reg_dealloc() { asm volatile("setmaxnreg.dec.sync.aligned.u32 %0;" :: "n"(R)); }

struct Ctx {
  uint32_t sb;
  int m, j, b, rank, wg, w, lane;
};

__device__ __forceinline__ unsigned smem_tag(const Ctx& c) { return lds32(c.sb + OFF_TAG); }
__device__ __forceinline__ int smem_block(const Ctx& c) { return lds32(c.sb + OFF_TAG + 8); }

struct WTile { int map, c0, c2; };
__host__ __device__ constexpr WTile wtile(int type, int j) {
  return WTile{128 * (type < 2 ? 5 : type < 5 ? type + 4 : type + 3), type < 2 ? (j + 8 * type) * 64 : 0,
               type < 2 ? 0 : type == 3 ? 3 * j : type == 4 ? 24 + 2 * j : type == 5 ? 40 + 2 * j : 2 * j};
}
__host__ __device__ constexpr int first_stage(int type, int part) { return ((part == 0 ? 0x2000422 : part == 1 ? 0x2 : 0x2002) >> (4 * type)) & 7; }

enum { A_NEW = 1 << 9, A_QUIET = 1 << 10, A_NONE = 1 << 11, A_PAIR = 2 << 11, A_COPY = 3 << 11 };
struct Plan {
  unsigned epoch[256];
  uint32_t v[8][PLAN_BYTES / 4];
};
constexpr Plan make_plan() {
  Plan plan{};
  for (int j = 0; j < 8; j++)
    for (int g = 4; g < 2 * KB_LAYER; g++) {
      const int layer = g >= KB_LAYER, r = g - layer * KB_LAYER;
      const bool split = (r >= 48 && r < 80) || (layer && r < 32);
      const int q = r - (r >= 48 ? 48 : 0);
      const bool head = split && q < 4, second = split && (head ? q >= 2 : q >= 18), lead = split && !second;
      const int type = split ? (r >= 48 ? 3 : 0) + second : r < 96 ? r >> 4 : 6, t = layer * 7 + type;
      const int step = !split ? r - 16 * type : head ? q & 1 : q - (second ? 16 : 2), n = step - (split && !head ? 2 : 0);
      const bool wide = type < 2 || type == 3;
      const int ns = wide || head ? 4 : 5, lag = type == 2 ? 3 : 4;
      const int e = g - (split && q && q < (r < 48 ? 4 : 6) ? 5 + (r >= 48 && q > 1) : n + 1 > ns ? ns : n + 1 > lag ? n + 1 : lag);
      const int v = (int)(0xfb7d95ea6c842310ull >> (4 * (step & 15))) & 15;
      const int kb = split ? (v < 4 ? (j * 2) ^ v : ((j >> 1) * 4 + v) & 15) : type != 2 || step < 8 ? step : step < 10 ? j ^ step : 8 + (((j & 6) + step) & 7);
      const uint32_t x = kb * 64 + (first_stage(type, head ? 1 : 2 * split) + n) % ns * (163840 / ns);
      const bool local = type == 2 && (step >> 1) == 4;
      const int act = split && step < 4 ? (head || lead ? A_NONE : A_PAIR) : local ? (step == 8 ? A_NONE : A_COPY) : 0;
      const uint32_t piece = type == 6 ? (step < 24 ? step / 3 : (step >> 1) - 4) : (type == 2 ? !local : lead ? step >= 4 : second && step == 2) ? kb : 31;
      const int ea = split && act == A_NONE ? g - 8 - (step == 3) : e;
      const WTile w = wtile(type, j);
      uint32_t* d = plan.v[j] + (g - 4) * 4;
      d[0] = x + ((ea >> 3) & 1) + (ea & 7) * 8 + (act ? 0 : (j & 1) * 8192) + (piece << 27);
      d[1] = (!head ? A_BYTES : lead ? 4 : 0) + (type == 2 || type == 6 ? 256 : t < 2 ? 0 : 128) + act + (n == 0 && !second ? A_NEW : 0) +
             (local && step == 8 ? A_QUIET : 0) + ((uint32_t)(t - second) << 27);
      d[2] = x + ((e >> 3) & 1) + (e & 7) * 8 + (!head || !type ? A_BYTES : wide ? 0 : 24576) + ((uint32_t)w.c2 << 26);
      d[3] = w.c0 + (wide ? 24576 : 16384) + (w.map << 16);
    }
  return plan;
}
__device__ __align__(128) Plan g_plan = make_plan();

template<int NL>
__device__ __forceinline__ void row_stats(const Ctx& c, int t) {
  const int ln = t / 3;
  const unsigned tag = smem_tag(c);
  const int row = c.w * 32 + c.lane + lds32(c.sb + OFF_ZERO);
  float s = 0.f, q = 0.f;
  const uint32_t xr = c.sb + OFF_X + row * 128 + (row & 7) * 16;
#pragma unroll 1
  for (int i = 0; i < 128; i += 16) {
    const float4 v = lds128f(xr ^ i), w = lds128f((xr ^ i) + A_BYTES);
    const float u[8] = {v.x, v.y, v.z, v.w, w.x, w.y, w.z, w.w};
#pragma unroll
    for (int z = 0; z < 16; z++) { const float x = z & 1 ? bf_hi(__float_as_uint(u[z >> 1])) : bf_lo(__float_as_uint(u[z >> 1])); s += x; q = fmaf(x, x, q); }
  }
  if (NL == 8) TL(-1, 6);
  if (NL == 4) mbar_pace(c.sb + OFF_FULL + 8 * SA, ln >> 1);
  const int b = smem_block(c);
  st_tag128(g_stats + (ln * 128 + b) * 128 + row, __float_as_uint(s), __float_as_uint(q), 0u, tag);
  mbar_pace(c.sb + (NL == 4 ? OFF_FULL + 8 * (SB & 7) : OFF_EMPTY + 16), (ln >> 1) ^ 1);
  const uint4* p = g_stats + (ln * 128 + (b & ~7)) * 128 + row;
  for (unsigned it = 0;; it++) {
    bool ok = true;
    s = 0.f; q = 0.f;
#pragma unroll 1
    for (int h = 0; h < 8; h += NL) {
      uint4 v[NL];
#pragma unroll
      for (int i = 0; i < NL; i++) v[i] = ld_tag128(p + (h + i) * 128);
#pragma unroll
      for (int i = 0; i < NL; i++) { ok = ok && v[i].w == tag; s += __uint_as_float(v[i].x); q += __uint_as_float(v[i].y); }
    }
    if (__all_sync(0xffffffffu, ok) || it > SPIN_LIMIT) break;
    __nanosleep(NL == 4 ? 400 : 100);
  }
  const float mean = s * (1.0f / D_);
  const float var = fmaxf(q * (1.0f / D_) - mean * mean, 0.0f);
  sts64f(c.sb + OFF_RST + row * 8, rsqrtf(var + 1e-5f), -mean);
  if ((EXP & 256) && NL == 8) sts32f(c.sb + OFF_TAG + 12, __int_as_float(row + 77));
  if ((EXP & 512) && NL == 4) sts32f(c.sb + OFF_TAG + 12, __int_as_float(row + 77));
  bar_arrive(BAR_EPI + (c.wg ^ 1), 256);
  TL(t - 2, 5);
}

__device__ __forceinline__ uint32_t res_addr(const Ctx& c) {
  return c.sb + OFF_X + ((c.lane >> 4) * 8 + (c.lane & 7)) * 128 + (((2 * c.w + ((c.lane >> 3) & 1)) ^ (c.lane & 7)) << 4);
}

template<int BN, int RES>
__device__ __forceinline__ void mainloop(const Ctx& c, float (&acc)[2][96], int t, int type, int g, int nkb) {
  constexpr int NS = BN == 192 ? 4 : 5, STR = BN == 192 ? 40960 : 32768;
  const bool split = !RES && (BN == 192 ? t > 1 : type == 4), second = BN == 128 || type == 1;
  int st = first_stage(type, split);
  if (split && second) g -= 14;
  const uint32_t rel = mapa(c.sb + OFF_EMPTY, c.lane & 1);
  const uint32_t sb = (c.sb & 0x3ffffu) >> 4;
  const uint32_t hb = BN == 192 && split && type ? 1024 : 0;
  uint32_t da = DESC_A + sb + (split ? OFF_X / 16 : st * (STR / 16)), db = DESC_B + sb + (BN == 128 && split ? 512 : st * (STR / 16) - hb);
  TL(t, 0);
  bar_sync(BAR_START + c.wg, 256);
  if (RES && type == 2) bar_sync(BAR_P1, 256);
  TL(t, 1);
  mbar_wait(c.sb + OFF_FULL + 8 * (g & 7), (g >> 3) & 1);
  TL(t, 2);
  wgmma_fence();
#define MMA(i, k, keep) wgmma_ss<BN, RES ? 2 : keep>(acc[i], da + (k) * 2 + (RES ? 0 : 64 * (i)), db + (k) * 128 + (RES ? 512 * (i) : 0))
  MMA(0, 0, 0); MMA(1, 0, 0); MMA(0, 1, 1); MMA(1, 1, 1);
  wgmma_commit();
  wgmma_fence();
  MMA(0, 2, 1); MMA(1, 2, 1); MMA(0, 3, 1); MMA(1, 3, 1);
  wgmma_commit();
  const int pause = BN == 192 && type == 1 ? (split ? PAUSE2 : PAUSE1) : nkb;
  int kb = 1, lim = split ? 2 : pause, pass = split ? 2 : !RES && type != 1 ? nkb : 0;
  uint32_t other = BAR_START + (c.wg ^ 1), prev = c.lane < 2 ? rel + 8 * (g & 7) : 0;
  asm volatile("" : "+r"(other));
  if (++st == NS) st = 0;
  g++;
  da = DESC_A + sb + (split ? (OFF_X + A_BYTES) / 16 : st * (STR / 16));
  db = DESC_B + sb + (BN == 128 && split ? 3072 : st * (STR / 16) - hb);
#pragma unroll 1
  for (;;) {
    mbar_wait(c.sb + OFF_FULL + 8 * (g & 7), (g >> 3) & 1);
    bool more;
#pragma unroll 1
    do {
      wgmma_fence();
      MMA(0, 0, 1); MMA(1, 0, 1); MMA(0, 1, 1); MMA(1, 1, 1);
      wgmma_commit();
      wgmma_wait<1>();
      if (prev) mbar_arrive_cluster(prev);
      TK(t, kb);
      prev = c.lane < 2 ? rel + 8 * (g & 7) : 0;
      kb++; g++;
      if (++st == NS) st = 0;
      wgmma_fence();
      if (BN == 128 && kb == pass) bar_arrive(other, 256);
      MMA(0, 2, 1); MMA(1, 2, 1);
      if (BN == 192 && kb == pass) bar_arrive(other, 256);
      const uint32_t ok = mbar_test(c.sb + OFF_FULL + 8 * (g & 7), (g >> 3) & 1);
      MMA(0, 3, 1); MMA(1, 3, 1);
      wgmma_commit();
      more = __all_sync(0xffffffffu, ok) && kb != lim;
      da = DESC_A + sb + (RES && type == 2 && kb == 8 ? OFF_STG / 16 : st * (STR / 16));
      db = DESC_B + sb + st * (STR / 16);
    } while (more);
    if (kb != lim) continue;
    if (RES || kb == nkb) break;
    if (BN == 128 || kb == 2) {
      wgmma_wait<0>();
      if (prev) mbar_arrive_cluster(prev);
      TK(t, 16);
      if (second) row_stats<4>(c, t);
      g += second ? 14 : 2;
      st = first_stage(type, 2);
      da = DESC_A + sb + st * (STR / 16); db = DESC_B + sb + st * (STR / 16);
      lim = pause; pass = type != 1 ? nkb : 0; prev = 0;
      bar_sync(BAR_START + c.wg, 256);
    } else {
      bar_sync(BAR_P0, 256); bar_sync(BAR_P1, 256);
      lim = kb == pause ? pause + 2 : nkb;
    }
  }
  if (!RES) return;
#define PAIR(i, n) wgmma_ss<128, 2>(acc[i], da + ((n) >> 2) * 2048 + ((n) & 3) * 2, db + ((n) >> 2) * 2048 + ((n) & 3) * 128 + 512 * (i))
#define PUT(z) do { const float* a = acc[(z) >> 3] + ((z) & 7) * 8; \
    stmatrix4_t(xw + (z) * 2048, pack_bf16(a[0], a[1]), pack_bf16(a[2], a[3]), pack_bf16(a[4], a[5]), pack_bf16(a[6], a[7])); } while (0)
  const uint32_t xw = res_addr(c);
#pragma unroll
  for (int n = 0; n < 4 * SK; n++) {
    if (!(n & 3)) { mbar_wait(c.sb + OFF_FULL + 8 * (8 - SK + n / 4), (g >> 3) & 1); wgmma_fence(); }
    PAIR(0, n);
    if (n == 3) { wgmma_commit(); wgmma_wait<1>(); if (prev) mbar_arrive_cluster(prev); wgmma_fence(); }
  }
  wgmma_commit();
#pragma unroll
  for (int n = 0; n < 4 * SK; n++) {
    if (n == 4 * SK - 2 && t < 13) bar_arrive(other, 256);
    PAIR(1, n);
    wgmma_commit();
#pragma unroll
    for (int z = 0; z < 8; z++) if (z / 4 + 2 == n) PUT(z);
    if (n == 3) bar_arrive(BAR_RES, 160);
    if (n && n < 4 * SK - 1) wgmma_wait<2>();
    if (n > 4 && (n & 3) == 1 && c.lane < 2) mbar_arrive_cluster(rel + 8 * (7 - SK + n / 4));
  }
  wgmma_wait<0>();
  if (c.lane < 2) mbar_arrive_cluster(rel + 56);
  TL(t, 3);
#pragma unroll
  for (int nt = 8; nt < 16; nt++) PUT(nt);
  fence_async_smem();
  __syncwarp();
  asm volatile(ELECT "@p mbarrier.complete_tx.relaxed.cta.shared::cta.b64 [%0], 1;\n}" :: "r"(c.sb + OFF_FULL + 8) : "memory");
  bar_arrive(BAR_RES2, 160);
#undef MMA
#undef PAIR
#undef PUT
}
__device__ __forceinline__ void release(const Ctx& c, int slot, int lanes = 2) {
  if (c.lane < lanes) mbar_arrive_cluster(mapa(c.sb + OFF_EMPTY, c.lane & 1) + 8 * slot);
}
__device__ __forceinline__ void finish(const Ctx& c, int t, int slot) {
  wgmma_wait<0>();
  release(c, slot);
  TL(t, 3);
}

__device__ __forceinline__ void put_halo(uint32_t addr, bool last, uint32_t a, uint32_t b, uint32_t c, uint32_t d) {
  if (!last) stmatrix4(addr, a, b, c, d);
  else asm volatile("stmatrix.sync.aligned.m8n8.x2.shared.b16 [%0], {%1, %2};\nstmatrix.sync.aligned.m8n8.x1.shared.b16 [%0 + 256], {%3};" :: "r"(addr), "r"(a), "r"(b), "r"(c) : "memory");
}

__device__ __forceinline__ void fetch_halo(const Ctx& c, unsigned tag, int tile) {
  const int v = c.w & 1;
  const uint4* src = g_halo + (tile * 128 + c.b - 8) * 352 + v * 160 + c.lane;
  uint4 G[6];
#pragma unroll
  for (int z = 0; z < 6; z++) G[z] = make_uint4(0u, 0u, 0u, 0u);
  bar_sync(BAR_HGO + v, 64);
  for (unsigned it = 0; c.m > 0; it++) {
    bool ok = true;
    if (it && !(tile & 1)) __nanosleep(200);
#pragma unroll
    for (int z = 0; z < 6; z++) { G[z] = ld_tag128(src + z * 32); ok = ok && G[z].w == tag; }
    if (__all_sync(0xffffffffu, ok) || it > SPIN_LIMIT) break;
  }
#pragma unroll
  for (int z = 0; z < 6; z++) put_halo(c.sb + OFF_STG + c.lane * 16 + (z ? (v * 5 + z) * 384 - 128 : v * 1792), z == 5, G[z].x, G[z].y, G[z].z, G[z].w);
  if (!v) sts32f(c.sb + OFF_RST - 256 + c.lane * 8, __uint_as_float(G[0].z));
  __syncwarp();
  mbar_arrive_e(c.sb + OFF_HALO + 8 * v);
}

template<int SKEW>
__device__ __forceinline__ void conv_qkv(const Ctx& c, float (&acc)[2][96], uint32_t (&P)[3][2][4][4], int t) {
  const int lane = c.lane, w = c.w, g = lane >> 2, cc = lane & 3;
  const int layer = t >= 7;
  const uint32_t sb = (c.sb & 0x3ffffu) >> 4, par = layer ^ 1;
  uint32_t da = DESC_A + sb + 7680 + 64, db = DESC_B + sb + 7680;
#define MMA(i, n) if (SKEW) do { wgmma_ss<192, 1>(acc[i], da, db); \
    asm volatile("add.s32 %0, %0, %2;\nadd.s32 %1, %1, %3;" : "+r"(da), "+r"(db) : "r"((n) == 11 ? 5050 : (n) == 7 ? 2554 : (n) == 3 ? -7686 : 2), "r"((n) == 11 ? 4736 : (n) == 7 ? 2176 : (n) == 3 ? -8064 : 128)); } while (0)
  if (SKEW) {
    mbar_wait(c.sb + OFF_FULL + 40, par);
    wgmma_fence();
    MMA(1, 0); MMA(1, 1); MMA(1, 2); MMA(1, 3);
    wgmma_commit();
    wgmma_wait<1>();
    release(c, 4);
    mbar_wait(c.sb + OFF_FULL + 48, par);
  } else finish(c, t, layer ? 1 : 7);
  MMA(1, 4); MMA(1, 5);
  bar_sync(BAR_EPI + c.wg, 256);
  MMA(1, 6);
  mbar_wait(c.sb + OFF_TBL + 8 * SKEW, 0);
  MMA(1, 7);
  if (SKEW) mbar_wait(c.sb + OFF_FULL + 56, par);
  MMA(1, 8);
  bar_sync(BAR_FREE, 160);
  MMA(1, 9);
  const uint32_t rst = c.sb + OFF_RST + w * 256;
  float mu[4];
#pragma unroll
  for (int r = 0; r < 4; r++) mu[r] = __uint_as_float(lds32(rst + (8 * r + g) * 8 + 4));
  const uint32_t tag = smem_tag(c), rs_l = lds32(rst + lane * 8);
  const uint32_t csb = c.sb + OFF_CSQ + SKEW * 768 + cc * 16;
  const uint32_t stg = c.sb + OFF_STG + w * 4096;
  const int b = smem_block(c);
  uint4* const halo = g_halo + ((layer * 2 + SKEW) * 128 + b) * 352 + lane;
  const bool send = w == 3 && b < 120;
  float4 cs = lds128f(csb + 4 * 64);
  if (SKEW) {
    MMA(1, 10); MMA(1, 11);
    wgmma_commit();
    MMA(0, 0);
    wgmma_commit();
    MMA(0, 1);
    wgmma_commit();
    wgmma_wait<2>();
  }
#define CONV(i, np) do { _Pragma("unroll") for (int z = 0; z < 4; z++) { const int nt = 2 * (np) + (z >> 1), h = z & 1; \
    const float m = mu[2 * h + (i)]; \
    P[nt >> 3][(nt >> 2) & 1][2 * h + (i)][nt & 3] = pack_bf16(fmaf(z >> 1 ? cs.z : cs.x, m, acc[i][4 * nt + 2 * h]), \
                                                                     fmaf(z >> 1 ? cs.w : cs.y, m, acc[i][4 * nt + 2 * h + 1])); } } while (0)
#define HM(u) P[1 + (((u) >> 4) & 1)][((u) >> 3) & 1][((u) & 2) + 1][(((u) >> 1) & 2) + ((u) & 1)]
#define HW(u) ((u) == 2 ? rs_l : HM((u) - ((u) > 2)))
#pragma unroll
  for (int n = 0; n < 12; n++) {
    const int np = (n + 4) % 12;
    if (SKEW && n == HGK && w == 0) bar_arrive(BAR_HGO, 64);
    if (SKEW && n == HGO && w == 0) bar_arrive(BAR_HGO + 1, 64);
    if (SKEW && n == 8) bar_arrive(BAR_START + (c.wg ^ 1), 256);
    if (SKEW && n < 10) { MMA(0, n + 2); wgmma_commit(); }
    CONV(1, np);
    cs = lds128f(csb + (n < 11 ? (n + 5) % 12 : 0) * 64);
#pragma unroll
    for (int z = 0; z < 11; z++)
      if ((3 * z + 1) / 4 == n) {
        st_tag128_if(send, halo + z * 32, HW(3 * z), HW(3 * z + 1), HW(3 * z + 2), tag);
        put_halo(stg + 4096 + lane * 16 + (z ? z * 384 - 128 : 0), z == 10, HW(3 * z), HW(3 * z + 1), HW(3 * z + 2), tag);
      }
    if (SKEW && n < 10) wgmma_wait<2>();
    if (SKEW && (n == 3 || n == 7)) release(c, 5 + (n >> 2));
  }
#undef MMA
#undef HW
#undef HM
  if (SKEW) {
    wgmma_wait<0>();
    release(c, 7, w ? 2 : 0);
    TL(t, 3);
  }
#pragma unroll
  for (int np = 0; np < 12; np++) {
    CONV(0, np);
    if (!SKEW && np == HG1 && w == 0) { bar_arrive(BAR_HGO, 64); bar_arrive(BAR_HGO + 1, 64); }
    if (np < 11) cs = lds128f(csb + (np + 1) * 64);
  }
#undef CONV
}

__device__ __forceinline__ void epi_qkv(const Ctx& c, float (&acc)[2][96], int t, int q) {
  const int lane = c.lane, w = c.w, g = lane >> 2, cc = lane & 3;
  uint32_t P[3][2][4][4];
  if (q) conv_qkv<1>(c, acc, P, t); else conv_qkv<0>(c, acc, P, t);
  const uint32_t rst = c.sb + OFF_RST + w * 256, stg = c.sb + OFF_STG + w * 4096;
  const bool nohalo = w == 0 && smem_block(c) < 8;
#pragma unroll
  for (int z = 0; z < 16; z++) P[2][z >> 3][(z >> 1) & 2][z & 3] = movmatrix(P[2][z >> 3][(z >> 1) & 2][z & 3]);
  uint32_t K1[4][4], V1[4][4];
  const uint32_t hl = stg + (lane & 15) * 16 + (lane >> 4) * 512;
#define HZ(z) (((z) >> 1) * 1024 + ((z) & 1) * 256)
  __syncwarp();
#pragma unroll
  for (int z = 0; z < 4; z++) { ldmatrix4(hl + 4096 + HZ(z), K1[z]); ldmatrix4_t(hl + 4096 + 2048 + HZ(z), V1[z]); }
  TL(t, 9);
  bar_sync(BAR_WG + c.wg, 128);
  if (w == 0) { TL(t, 8); mbar_wait(c.sb + OFF_HALO, q); release(c, 7, 2 * q); }
  uint32_t HK[4][4], HV[4][4];
#pragma unroll
  for (int z = 0; z < 4; z++) ldmatrix4(hl + HZ(z), HK[z]);
  const bool far0 = 2 * cc > g, far1 = 2 * cc + 1 > g;
  float rk[4][2], sc[4][2];
#pragma unroll
  for (int r = 0; r < 4; r++) {
    const float rq = __uint_as_float(lds32(rst + (8 * r + g) * 8)) * (0.17677669529663687f * 1.4426950408889634f);
    const int back = r & 1 ? 64 : 192;
    rk[r][0] = __uint_as_float(lds32(rst + r * 64 + cc * 16 - (far0 ? back : 0)));
    rk[r][1] = __uint_as_float(lds32(rst + r * 64 + cc * 16 + 8 - (far1 ? back : 0)));
    sc[r][0] = rq * rk[r][0]; sc[r][1] = rq * rk[r][1];
  }
  TL(t, 4);
  float S[4][3][4];
  if (q == 0) bar_sync(BAR_P0, 256);
  float4 zero = lds128f(c.sb + OFF_ZERO);
#pragma unroll
  for (int k = 0; k < 2; k++)
#pragma unroll
    for (int z = 0; z < 4; z++) {
      const uint32_t* qa = P[0][z >> 1][2 * (z & 1)]; const uint32_t* qb = P[0][z >> 1][2 * (z & 1) + 1];
      const uint32_t* kk[3] = {HK[z], P[1][z >> 1][2 * (z & 1)], K1[z]};
#pragma unroll
      for (int n = 0; n < 3; n++) {
        if (k == 0) mma16816_z(S[z][n], qa[0], qb[0], qa[1], qb[1], kk[n][0], kk[n][1], zero);
        else mma16816(S[z][n], qa[2], qb[2], qa[3], qb[3], kk[n][2], kk[n][3]);
        if (q == 0 && k * 12 + z * 3 + n + 1 == NS) bar_arrive_here(BAR_P1, S[0][0][0], zero.x);
      }
    }
  TL(t, 10);
  const uint32_t fmask = (far0 ? 0xffffu : 0u) | (far1 ? 0xffff0000u : 0u);
  uint32_t pf[4][2], pn[4][2];
#pragma unroll
  for (int z = 0; z < 4; z++)
#pragma unroll
    for (int i = 0; i < 2; i++) {
      const int r = 2 * (z & 1) + i;
      float l0 = (far0 ? S[z][i][2 * i] : S[z][i + 1][2 * i]) * sc[r][0];
      float l1 = (far1 ? S[z][i][2 * i + 1] : S[z][i + 1][2 * i + 1]) * sc[r][1];
      if (i == 0 && nohalo) { const float neg = -1e9f * 1.4426950408889634f; if (far0) l0 = neg; if (far1) l1 = neg; }
      float mx = fmaxf(l0, l1);
      mx = fmaxf(mx, __shfl_xor_sync(0xffffffffu, mx, 1));
      mx = fmaxf(mx, __shfl_xor_sync(0xffffffffu, mx, 2));
      l0 = ex2(l0 - mx); l1 = ex2(l1 - mx);
      float sum = l0 + l1;
      l0 *= rk[r][0]; l1 *= rk[r][1];
      sum += __shfl_xor_sync(0xffffffffu, sum, 1);
      sum += __shfl_xor_sync(0xffffffffu, sum, 2);
      sum = rcp(sum);
      const uint32_t u = pack_bf16(l0 * sum, l1 * sum);
      pf[z][i] = u & fmask; pn[z][i] = u & ~fmask;
    }
  float O[4][2][2][4];
  TL(t, 11);
  if (w == 0) { mbar_wait(c.sb + OFF_HALO + 8, q); TL(t, 12); }
#pragma unroll
  for (int z = 0; z < 4; z++) ldmatrix4_t(hl + 2048 + HZ(z), HV[z]);
#undef HZ
  if (q == 0) bar_sync_after(BAR_P0, (pn[0][0] | pn[0][1] | pn[1][0]) | (pn[1][1] | pn[2][0] | pn[2][1]) | (pn[3][0] | pn[3][1]));
  zero = lds128f(c.sb + OFF_ZERO);
#pragma unroll
  for (int z = 0; z < 4; z++)
#pragma unroll
    for (int d = 0; d < 2; d++) {
      const uint32_t* v0 = P[2][z >> 1][2 * (z & 1)] + 2 * d;
      mma16816_z(O[z][0][d], HV[z][2 * d], HV[z][2 * d + 1], v0[0], v0[1], pf[z][0], pn[z][0], zero);
      mma16816_z(O[z][1][d], v0[0], v0[1], V1[z][2 * d], V1[z][2 * d + 1], pf[z][1], pn[z][1], zero);
      if (z * 4 + d * 2 + 2 == NP) bar_arrive_here(BAR_P1, O[0][0][0][0], zero.x);
    }
  TL(t, 5);
#pragma unroll
  for (int nt = 0; nt < 8; nt++) {
    uint32_t u[4];
#pragma unroll
    for (int r = 0; r < 4; r++) { const float* o = O[2 * (nt >> 2) + (r >> 1)][r & 1][(nt >> 1) & 1] + 2 * (nt & 1); u[r] = pack_bf16(o[0], o[1]); }
    stmatrix4_t(stg + lane * 128 + ((nt ^ (lane & 7)) << 4), u[0], u[1], u[2], u[3]);
  }
  fence_async_smem();
  bar_arrive(BAR_READY, 160);
  TL(t, 13);
}

template<int CH>
__device__ __forceinline__ void epi_up(const Ctx& c, float (&acc)[2][96], int type) {
  const int lane = c.lane, w = c.w, g = lane >> 2, cc = lane & 3;
  float rs[4], nm[4];
#pragma unroll
  for (int r = 0; r < 4; r++) { const float2 v = lds64f(c.sb + OFF_RST + (w * 32 + 8 * r + g) * 8); rs[r] = v.x; nm[r] = v.x * v.y; }
  const int loc0 = type == 3 ? 0 : (type == 4 ? 192 : 320);
  const uint32_t cb = c.sb + OFF_UP + loc0 * 8 + cc * 16;
  const uint32_t zero = lds32(c.sb + OFF_ZERO);
  uint32_t d[2] = {0u, 0u};
  const uint32_t stg = c.sb + OFF_STG + w * 4096;
#pragma unroll
  for (int ch = CH; ch < (CH ? 3 : 2); ch++) {
    uint32_t P[8][4];
#pragma unroll
    for (int n8 = 0; n8 < 8; n8++) {
      const int nt = ch * 8 + n8;
      const float4 cv = lds128f(cb + nt * 64);
#pragma unroll
      for (int r = 0; r < 4; r++) {
        const float m = after(nm[r], d[r & 1], zero);
        d[r & 1] = P[n8][r] = relu_sq_bf16(fmaf(acc[r & 1][4 * nt + 2 * (r >> 1)], rs[r], fmaf(cv.x, m, cv.z)),
                                           fmaf(acc[r & 1][4 * nt + 2 * (r >> 1) + 1], rs[r], fmaf(cv.y, m, cv.w)));
      }
    }
    bar_sync(BAR_FREE, 160);
#pragma unroll
    for (int n8 = 0; n8 < 8; n8++)
      stmatrix4(stg + lane * 128 + ((n8 ^ (lane & 7)) << 4), P[n8][0], P[n8][1], P[n8][2], P[n8][3]);
    fence_async_smem();
    bar_arrive(BAR_READY, 160);
  }
}

__device__ __forceinline__ void init_res(const Ctx& c, float (&acc)[2][96], int t, bool bias) {
  if (t == 2) mbar_wait(c.sb + OFF_XBAR, 0);
  uint32_t xb = res_addr(c);
  const uint32_t zero = lds32(c.sb + OFF_ZERO);
  float b[4];
#pragma unroll
  for (int r = 0; r < 4; r++) b[r] = bias ? __uint_as_float(lds32(c.sb + OFF_B2 + (r >> 1) * 256 + c.w * 64 + (r & 1) * 32 + (c.lane >> 2) * 4)) : 0.f;
#pragma unroll
  for (int z = 0; z < 16; z++) {
    uint32_t u[4];
    asm volatile("{\n.reg .pred p;\nSTAY:\nldmatrix.sync.aligned.m8n8.x4.trans.shared.b16 {%0, %1, %2, %3}, [%4];\nsetp.lt.u32 p, %0, %5;\n@p bra.uni STAY;\n}"
      : "=r"(u[0]), "=r"(u[1]), "=r"(u[2]), "=r"(u[3]) : "r"(xb + z * 2048), "r"(zero) : "memory");
#pragma unroll
    for (int r = 0; r < 4; r++) {
      float* a = acc[z >> 3] + (z & 7) * 8 + 2 * r;
      a[0] = bf_lo(u[r]) + b[(z >> 3) * 2 + (r & 1)];
      a[1] = bf_hi(u[r]) + b[(z >> 3) * 2 + (r & 1)];
      asm volatile("" : "+f"(a[0]), "+f"(a[1]));
    }
  }
}

__device__ __forceinline__ void load_table(const Ctx& c, const Params& p, int part, unsigned tag) {
  const int i0 = (part < 4 ? part * 192 : 704) + c.lane, n = part < 3 ? 6 : 4;
  const uint2* src = g_cs + c.j * NCS + i0;
  const uint32_t dst = c.sb + OFF_CSQ + (i0 & 1) * 4 + (part < 2 ? (i0 >> 4) * 64 + (i0 & 6) * 8 + (i0 & 8) : 1536 + ((i0 - 384) >> 1) * 16);
  const __nv_bfloat16* bias = p.b1 + (part == 2 ? c.j * 192 : (part == 3 ? 1536 : 2560) + c.j * 128) + c.lane;
  float v[6];
  if (part >= 2) {
#pragma unroll
    for (int k = 0; k < 6; k++) if (k < n) sts32f(dst + k * 256 + 8, __bfloat162float(bias[k * 32]));
  }
  for (unsigned it = 0;; it++) {
    bool ok = true;
#pragma unroll
    for (int k = 0; k < 6; k++) { const uint2 a = ld_tag64(src + (k < n ? k * 32 : 0)); ok = ok && a.y == tag; v[k] = __uint_as_float(a.x); }
    if (__all_sync(0xffffffffu, ok) || it > SPIN_LIMIT) break;
    __nanosleep(200);
  }
#pragma unroll
  for (int k = 0; k < 6; k++) if (k < n) sts32f(dst + k * (part < 2 ? 128 : 256), v[k]);
  __syncwarp();
}

__device__ __forceinline__ void colsum_cta(const Ctx& c, const Params& p, unsigned* epoch) {
  if (c.wg < 2) mbar_init_e(c.sb + OFF_FULL + 32 * c.wg + 8 * c.w, 1);
  sts32f(c.sb + OFF_STG + threadIdx.x * 4, __uint_as_float(0x3f803f80u));
  fence_async_smem();
  __syncthreads();
  if (c.wg == 2) return;
  const unsigned tag = *(volatile unsigned*)epoch + 1;
  const int j = (blockIdx.x - 128) * 2 + c.wg;
  const uint32_t ring = c.sb + c.wg * 98304, full = c.sb + OFF_FULL + 32 * c.wg;
  const uint64_t ones = (uint64_t)(((c.sb + OFF_STG) & 0x3ffffu) >> 4) | (8u << 16) | ((uint64_t)16u << 32);
  float d[3][4];
#pragma unroll 1
  for (int n = -4; n < 80; n++) {
    if (n >= 0) {
      mbar_wait(full + 8 * (n & 3), (n >> 2) & 1);
      const uint64_t da = (uint64_t)(((ring + (n & 3) * 24576) & 0x3ffffu) >> 4) | (64u << 16) | ((uint64_t)(64u | (1u << 30)) << 32);
      wgmma_fence();
#pragma unroll
      for (int k = 0; k < 4; k++)
#pragma unroll
        for (int z = 0; z < 3; z++)
          asm volatile("{\n.reg .pred p;\nsetp.ne.b32 p, %6, 0;\nwgmma.mma_async.sync.aligned.m64n8k16.f32.bf16.bf16 {%0,%1,%2,%3}, %4, %5, p, 1, 1, 1, 0;\n}"
            : "+f"(d[z][0]), "+f"(d[z][1]), "+f"(d[z][2]), "+f"(d[z][3]) : "l"(da + z * 512 + k * 128), "l"(ones), "r"((n & 15) | k));
      wgmma_commit();
      wgmma_wait<0>();
      bar_sync(BAR_WG + c.wg, 128);
      if ((n & 15) == 15 && (c.lane & 3) < 2) {
        const int u = n >> 4;
        uint2* out = g_cs + j * NCS + (u < 4 ? u * 192 : 704) + c.w * 16 + (c.lane >> 2) + (c.lane & 1) * 8;
#pragma unroll
        for (int z = 0; z < 3; z++) if (z < 2 || u < 3) st_tag64(out + z * 64, (c.lane & 1) ? d[z][2] : d[z][0], tag);
      }
      __syncwarp();
    }
    if (c.w == 0 && n < 76) {
      const int u = (n + 4) >> 4;
      const WTile w = wtile(u + (u >= 2), j);
      mbar_expect_e(full + 8 * (n & 3), u < 3 ? 24576 : 16384);
      tma_ld3_e(ring + (n & 3) * 24576, (const CUtensorMap*)((const char*)&p + w.map), full + 8 * (n & 3), w.c0, ((n + 4) & 15) * 64, w.c2);
    }
  }
  bar_sync(BAR_START, 256);
  if (threadIdx.x == 0) *epoch = tag;
}

__device__ __forceinline__ void place(Ctx& c, uint32_t slot) {
  const int row = slot < 32 ? slot >> 3 : slot < 60 ? ((slot - 4) * 37) >> 8 : slot - 56;
  const int gpc = slot < 60 ? slot - row * (slot < 32 ? 8 : 7) - (slot < 32 ? 0 : 3) : 0;
  c.m = (gpc & 1) * 8 + row;
  c.j = (gpc & 6) + c.rank; c.b = c.m * 8 + c.j;
}

__global__ void __cluster_dims__(2, 1, 1) __launch_bounds__(384, 1) fused_kernel(unsigned* const epochs, const char* const x0, const char* const w0, const __grid_constant__ Params p) {
  extern __shared__ uint8_t smem_raw[];
  const int tid = threadIdx.x;
  Ctx c;
  c.sb = (smem_u32(smem_raw) + 1023) & ~1023u;
  const int k = __shfl_sync(0xffffffffu, tid >> 5, 0);
  c.wg = k >> 2; c.w = k & 3; c.lane = tid & 31;
  c.rank = blockIdx.x & 1;
  if (blockIdx.x >= 128) { colsum_cta(c, p, epochs + blockIdx.x); return; }
  uint32_t slot; asm volatile("mov.u32 %0, %%smid;" : "=r"(slot));
  slot = __shfl_sync(0xffffffffu, slot < 120 ? slot >> 1 : 60 + ((slot >> 1) & 3), 0);
  if (c.wg == 2) {
    const bool claim = tid == 320 && c.rank == 0;
    unsigned epoch, old;
    asm volatile("{\n.reg .pred p;\nsetp.ne.u32 p, %4, 0;\nmov.u32 %0, 0;\nmov.u32 %1, 0;\n@p atom.relaxed.gpu.global.add.u32 %0, [%2], 1;\n@p ld.relaxed.gpu.global.u32 %1, [%3];\n}"
      : "=r"(old), "=r"(epoch) : "l"(epochs + 132 + slot + c.lane), "l"(epochs + blockIdx.x), "r"((uint32_t)claim) : "memory");
    reg_dealloc<40>();
#pragma unroll 1
    for (int pass = 0;; pass++) {
      place(c, slot);
      if (c.w == 1) {
        asm volatile(ELECT "@p mbarrier.init.shared::cta.b64 [%0], 2;\n@p mbarrier.init.shared::cta.b64 [%0 + 8], 2;\n"
          "@p mbarrier.init.shared::cta.b64 [%0 + 16], 2;\n@p mbarrier.init.shared::cta.b64 [%0 + 24], 2;\n}" :: "r"(c.sb + OFF_FULL) : "memory");
        fence_async_smem();
        if (!pass) asm volatile("fence.mbarrier_init.release.cluster;\nbarrier.cluster.arrive.relaxed.aligned;" ::: "memory");
#pragma unroll 1
        for (int s = pass ? 0 : 2; s < 4; s++) {
          const uint32_t full = c.sb + OFF_FULL + 8 * s, dst = c.sb + (s ^ 2) * 40960;
          mbar_expect_e(full, 40960);
          tma_ld4_e(dst, &p.ld_x, full, s * 64, c.m * 4);
          tma_ld4_e(dst + 8192, &p.ld_x, full, s * 64, c.m * 4 + 2);
          tma_ld3_e(dst + A_BYTES, &p.w_qkv, full, c.j * 64, s * 64, 0);
          mbar_arrive_e(full);
        }
      } else if (!pass) {
        if (c.w == 2) { mbar_init_e(c.sb + OFF_SLOT, 1); mbar_expect_e(c.sb + OFF_SLOT, 8); }
        asm volatile("fence.mbarrier_init.release.cluster;\nbarrier.cluster.arrive.relaxed.aligned;" ::: "memory");
      }
      if (c.w == 0) {
        asm volatile("cp.async.wait_all;" ::: "memory");
#pragma unroll
        for (int i = 0; i < PLAN_BYTES; i += 512)
          asm volatile("cp.async.cg.shared.global [%0], [%1], 16;" :: "r"(c.sb + OFF_PLAN + c.lane * 16 + i), "l"(epochs + 256 + c.j * (PLAN_BYTES / 4) + c.lane * 4 + i / 4) : "memory");
      }
      if (c.w == 3) sts32f(c.sb + OFF_TAG + 8, __int_as_float(c.b));
      if (pass) { bar_sync(BAR_START, 256); break; }
      asm volatile("barrier.cluster.wait.aligned;" ::: "memory");
      if (claim) {
        uint32_t s = slot;
        for (int it = 0; old != epoch && it < 64; it++) { atomicSub(epochs + 132 + s, 1u); s = (s + 1) & 63; old = atomicAdd(epochs + 132 + s, 1u); }
#pragma unroll
        for (int r = 0; r < 2; r++)
          asm volatile("{\n.reg .u32 t;\nadd.u32 t, %1, 1;\nst.async.weak.shared::cluster.mbarrier::complete_tx::bytes.v2.b32 [%0], {t, %2}, [%3];\n}"
            :: "r"(mapa(c.sb + OFF_TAG, r)), "r"(old), "r"(s), "r"(mapa(c.sb + OFF_SLOT, r)) : "memory");
      }
      __syncwarp();
      mbar_wait(c.sb + OFF_SLOT, 0);
      const uint32_t got = __shfl_sync(0xffffffffu, lds32(c.sb + OFF_TAG + 4), 0);
      if (got == slot) {
        bar_arrive(BAR_START, 256);
#pragma unroll 1
        for (int s = 0; s < 16 && c.w == 3; s += 8) {
          mbar_wait(c.sb + OFF_PRE + s, 0);
          PTL(12, 12 + s / 8);
          fence_async_smem();
          if (c.lane < 2) asm volatile("mbarrier.arrive.shared::cta.b64 _, [%0];" :: "r"(c.sb + OFF_FULL + s) : "memory");
        }
        break;
      }
      slot = got;
      if (c.w == 1)
#pragma unroll 1
        for (int s = 0; s < 4; s++) { mbar_wait(c.sb + (s < 2 ? OFF_PRE : OFF_FULL) + 8 * s, 0); asm volatile(ELECT "@p mbarrier.inval.shared::cta.b64 [%0];\n}" :: "r"(c.sb + OFF_FULL + 8 * s) : "memory"); }
    }
    const unsigned tag = smem_tag(c);
    if (c.w < 2) { asm volatile("cp.async.wait_all;" ::: "memory"); bar_sync(BAR_COPY, 64); PTL(14, 13); }
    if (c.w == 0) {
      const char* fp = (const char*)(g_flags + c.m * 32 + c.lane);
      unsigned ready = 1u << 31;
      float2 nx = lds64f(c.sb + OFF_PLAN);
#pragma unroll 1
      for (int g = 4; g < 2 * KB_LAYER; g++) {
        const uint32_t x = __float_as_uint(nx.x), y = __float_as_uint(nx.y);
        nx = lds64f(c.sb + OFF_PLAN + g * 16 - 48);
        if (y & A_NEW) ready = 1u << 31;
        for (unsigned it = 0; !((ready >> (x >> 27)) & 1) && it < SPIN_LIMIT; it++) {
          unsigned v; asm volatile("ld.relaxed.gpu.global.u32 %0, [%1];" : "=r"(v) : "l"(fp + (y >> 16)) : "memory");
          ready |= __ballot_sync(0xffffffffu, v == tag);
          asm volatile("fence.proxy.async.global;" ::: "memory");
        }
        mbar_wait(c.sb + OFF_EMPTY + (x & 0x38), x & 1);
        const uint32_t full = c.sb + OFF_FULL + 8 * (g & 7), dst = c.sb + (x & 0x3e000);
        const CUtensorMap* mp = (const CUtensorMap*)((const char*)&p + (y & 0x180));
        if (!(y & A_QUIET)) mbar_expect_e(full, y & 0x4004);
        if (!(y & A_COPY)) tma_ld4_mc_e(dst, mp, full, x & 0xfc0, c.m * 4 + c.rank * 2);
        else if (!(y & A_NONE)) { tma_ld4_e(dst, mp, full, x & 0xfc0, c.m * 4); tma_ld4_e(dst + 8192, mp, full, x & 0xfc0, c.m * 4 + 2); }
        else if (y & A_PAIR) {
          const uint32_t peer = mapa(c.sb, c.rank ^ 1);
          mbar_wait(c.sb + OFF_FULL, g < KB_LAYER);
          dsmem_copy_e(peer + 3 * 32768, c.sb + OFF_STG, peer + OFF_FULL + 8);
        }
      }
    } else if (c.w == 1) {
      float2 nx = lds64f(c.sb + OFF_PLAN + 8);
#pragma unroll 1
      for (int g = 4; g < 2 * KB_LAYER; g++) {
        const uint32_t x = __float_as_uint(nx.x), y = __float_as_uint(nx.y);
        nx = lds64f(c.sb + OFF_PLAN + g * 16 - 40);
        mbar_wait(c.sb + OFF_EMPTY + (x & 0x38), x & 1);
        const uint32_t full = c.sb + OFF_FULL + 8 * (g & 7);
        mbar_expect_e(full, y & 0x6000);
        tma_ld3_e(c.sb + (x & 0x3e000), (const CUtensorMap*)((const char*)&p + (y >> 16)), full, y & 0x3c0, x & 0xfc0, x >> 26);
      }
    } else if (c.w == 2) {
      mbar_pace(c.sb + OFF_EMPTY + 56, 0);
#pragma unroll 1
      for (int z = 0; z < 44; z++) st_tag128(g_halo + ((z & 3) * 128 + c.b) * 352 + (z >> 2) * 32 + c.lane, 0u, 0u, 0u, 0u);
      bar_arrive(BAR_FREE, 160);
#pragma unroll 1
      for (int t = 0; t < 14; t++) {
        const int layer = t >= 7, type = t - layer * 7;
        const int slab = c.m * 4;
        unsigned* flag = g_flags + c.m * 32 + c.j;
        if (type == 2 || type == 6) {
          flag += (t + 1) * 512 + c.j;
          bar_sync(BAR_RES, 160);
          fence_async_smem();
          asm volatile(ELECT "@p mbarrier.complete_tx.relaxed.cta.shared::cta.b64 [%0], 4;\n}" :: "r"(c.sb + OFF_FULL) : "memory");
          tma_st4_e(&p.st_out, c.sb + OFF_X, c.j * 128, slab);
          if (t < 13) {
            bulk_wait_read_e();
            PTL(t, 8);
            publish_e(flag++, tag);
            PTL(t, 9);
            mbar_wait(c.sb + OFF_FULL + 8, t != 2);
            mbar_wait(c.sb + OFF_EMPTY + 56, t == 2);
#pragma unroll
            for (int h = 0; h < 2; h++) tma_ld4_mc_e(c.sb + 3 * 40960 + h * 8192, &p.ld_out, c.sb + OFF_FULL + 40, c.j * 128, slab + 2 * h, 2 - c.rank);
          }
          if (t == 13) bar_sync(BAR_RES2, 160);
          tma_st4_e(&p.ld_out, c.sb + OFF_X + A_BYTES, c.j * 128 + 64, slab);
          if (t < 13) mbar_pace(c.sb + OFF_FULL + 48, t != 2);
          tma_st4_e(&p.ld_out, c.sb + OFF_X + A_BYTES + 8192, c.j * 128 + 64, slab + 2);
          bulk_wait_read_e();
          PTL(t, 11);
        } else {
          flag += (layer * 7 + (type < 2 ? 2 : 6)) * 512 + (type < 2 ? type : type - 3) * 8;
          const int col = type < 2 ? (c.j + 8 * type) * 64 : type == 3 ? c.j * 192 : (type == 4 ? 1536 : 2560) + c.j * 128;
#pragma unroll 1
          for (int ch = type == 3 ? -1 : 0; ch < (type < 2 ? 1 : 2); ch++) {
            if (type < 2) fetch_halo(c, tag, layer * 2 + type);
            bar_sync(BAR_READY, 160);
#pragma unroll 1
            for (int z = 0; z < 4; z++) {
              if (z && type != 1) bulk_wait_read_e();
              tma_st4_e(&p.st_h, c.sb + OFF_STG + z * 4096, col + (ch < 0 ? 128 : ch * 64), slab + z);
            }
            if (type == 1) { mbar_wait(c.sb + OFF_FULL, layer); mbar_arrive_e(c.sb + OFF_FULL); }
            bulk_wait_read_e();
            if (t < 12 || ch == 0) bar_arrive(BAR_FREE, 160);
          }
          PTL(t, 14);
        }
        if (t < 13) publish_e(flag, tag);
        PTL(t, 6);
      }
      if (c.lane == 0) epochs[blockIdx.x] = tag;
    } else {
      mbar_pace(c.sb + OFF_EMPTY + 8 * (c.m & 3), 0);
      PTL(14, 14);
      mbar_expect_e(c.sb + OFF_XBAR, 32768);
#pragma unroll
      for (int i = 0; i < 4; i++) tma_ld4_e(c.sb + OFF_X + i * 8192, &p.ld_x, c.sb + OFF_XBAR, c.j * 128 + (i >> 1) * 64, c.m * 4 + (i & 1) * 2);
#pragma unroll
      for (int i = 0; i < 4; i++) sts32f(c.sb + OFF_B2 + i * 128 + c.lane * 4, __bfloat162float(p.b2[c.j * 128 + i * 32 + c.lane]));
#pragma unroll 1
      for (int part = 0; part < 7; part++) {
        if (part < 5) {
          load_table(c, p, part, tag);
          mbar_arrive_e(c.sb + OFF_TBL + 8 * part);
          PTL(part, 7);
        }
        if (part < 2 || part > 4) fetch_halo(c, tag, part < 2 ? part : part - 3);
        if ((0x52 >> part) & 1) {
          const uint32_t peer = mapa(c.sb, c.rank ^ 1);
          bar_sync(BAR_RES2, 160);
          mbar_wait(c.sb + OFF_EMPTY + 56, part == 1);
          dsmem_copy_e(peer + 2 * 40960, c.sb + OFF_X + A_BYTES, peer + OFF_FULL + 32);
        }
      }
    }
  } else {
    place(c, slot);
    const int r = tid >> 3;
    const uint32_t dst = c.sb + 2 * 40960 + r * 128 + ((tid ^ r) & 7) * 16;
    const char* ga = x0 + (c.m * 128 + (r & 15) * 2 + c.wg) * 2048 + (tid & 7) * 16;
    const char* gb = w0 + r * 6144 + c.j * 128 + (tid & 7) * 16;
#pragma unroll
    for (int s = 0; s < 2; s++) {
#pragma unroll
      for (int i = 0; i < 10; i++)
        asm volatile("cp.async.cg.shared.global [%0], [%1], 16;" :: "r"(dst + s * 40960 + i * 4096),
          "l"(i < 4 ? ga + i * 65536 + s * 128 : gb + (2 * s + (i & 1)) * (32 * 6144) + (i / 2 - 2) * 2048) : "memory");
      if (!s) {
        mbar_init_e(c.sb + OFF_EMPTY + 8 * k, 8);
        mbar_init_e(c.sb + (k < 4 ? OFF_XBAR : OFF_FULL) + 8 * k, k < 4 ? 1 : 2);
        if (k < 7) mbar_init_e(c.sb + OFF_XBAR + 32 + 8 * k, k > 4 ? 256 : 1);
        else sts128(c.sb + OFF_ZERO, 0u, 0u, 0u, 0u);
        asm volatile("fence.mbarrier_init.release.cluster;\nbarrier.cluster.arrive.relaxed.aligned;" ::: "memory");
        bar_sync(BAR_EPI, 256);
      }
      asm volatile("cp.async.mbarrier.arrive.noinc.shared::cta.b64 [%0];" :: "r"(c.sb + OFF_PRE + 8 * s) : "memory");
    }
    asm volatile("barrier.cluster.wait.aligned;" ::: "memory");
    reg_alloc<232>();
    if (c.wg) { mbar_wait(c.sb + OFF_XBAR, 0); TL(-1, 4); row_stats<8>(c, 1); }
#pragma unroll 1
    for (int t = c.wg; t < 14; t += 2) {
      const int layer = t >= 7, type = t - layer * 7;
      const int g0 = layer * KB_LAYER + type * 16;
      float acc[2][96];
      if (type == 2 || type == 6) {
        init_res(c, acc, t, type == 6);
        mainloop<128, 1>(c, acc, t, type, g0, (type == 6 ? 56 : 16) - SK);
        if (t == 13) asm volatile("barrier.cluster.arrive.relaxed.aligned;" ::: "memory");
        TL(t, 4);
        continue;
      }
      if (type < 4) {
        mainloop<192, 0>(c, acc, t, type, g0, type == 1 ? 13 : 16);
        if (type < 2) { epi_qkv(c, acc, t, type); goto done; }
        finish(c, t, 1);
        bar_sync(BAR_EPI + c.wg, 256);
        mbar_wait(c.sb + OFF_TBL + 16, 0);
        epi_up<2>(c, acc, type);
      } else {
        mainloop<128, 0>(c, acc, t, type, g0, 16);
        finish(c, t, 7);
        bar_sync(BAR_EPI + c.wg, 256);
        mbar_wait(c.sb + OFF_TBL + 8 * (type - 1), 0);
      }
      epi_up<0>(c, acc, type);
      TL(t, 4);
    done:
      if (type != 1 && type != 5) bar_arrive(BAR_EPI + (c.wg ^ 1), 256);
    }
    if (c.wg == 1) {
      asm volatile("barrier.cluster.wait.aligned;" ::: "memory");
    }
  }
}

typedef CUresult (*EncodeFn)(CUtensorMap*, CUtensorMapDataType, cuuint32_t, void*, const cuuint64_t*, const cuuint64_t*,
                             const cuuint32_t*, const cuuint32_t*, CUtensorMapInterleave, CUtensorMapSwizzle,
                             CUtensorMapL2promotion, CUtensorMapFloatOOBfill);

void make_map(EncodeFn fn, CUtensorMap* m, const void* ptr, int rank, const cuuint64_t* dims, const cuuint64_t* strides, const cuuint32_t* box) {
  const cuuint32_t es[4] = {1, 1, 1, 1};
  fn(m, CU_TENSOR_MAP_DATA_TYPE_BFLOAT16, rank, const_cast<void*>(ptr), dims, strides, box, es, CU_TENSOR_MAP_INTERLEAVE_NONE,
     CU_TENSOR_MAP_SWIZZLE_128B, CU_TENSOR_MAP_L2_PROMOTION_L2_128B, CU_TENSOR_MAP_FLOAT_OOB_FILL_NONE);
}
void map_rows(EncodeFn fn, CUtensorMap* m, const void* ptr, int cols, int rows, int box_slabs, bool tokens) {
  const cuuint64_t rb = (cuuint64_t)cols * 2;
  const cuuint64_t dims[4] = {(cuuint64_t)cols, 16, 2, (cuuint64_t)(rows / 32)};
  const cuuint64_t st[3] = {tokens ? 2 * rb : rb, tokens ? rb : 16 * rb, 32 * rb};
  const cuuint32_t box[4] = {64, 16, 2, (cuuint32_t)box_slabs};
  make_map(fn, m, ptr, 4, dims, st, box);
}
void map_w(EncodeFn fn, CUtensorMap* m, const void* ptr, int K, int N, int inner, int nch) {
  const cuuint64_t dims[3] = {(cuuint64_t)inner, (cuuint64_t)K, (cuuint64_t)(N / inner)}, st[2] = {(cuuint64_t)N * 2, (cuuint64_t)inner * 2};
  const cuuint32_t box[3] = {64, 64, (cuuint32_t)nch};
  make_map(fn, m, ptr, 3, dims, st, box);
}

}

extern "C" void kernel_launch(void* const* d_in, const int* in_sizes, int n_in, void* d_out, int out_size) {
  (void)in_sizes; (void)n_in; (void)out_size;
  Params p;
  p.b1 = (const __nv_bfloat16*)d_in[5]; p.b2 = (const __nv_bfloat16*)d_in[7];
  void* fnp = nullptr; cudaDriverEntryPointQueryResult qr;
  cudaGetDriverEntryPoint("cuTensorMapEncodeTiled", &fnp, cudaEnableDefault, &qr);
  EncodeFn fn = (EncodeFn)fnp;
  void *h, *epochs;
  cudaGetSymbolAddress(&h, g_h);
  cudaGetSymbolAddress(&epochs, g_plan);
  map_rows(fn, &p.ld_x, d_in[0], D_, S_, 2, true);
  map_rows(fn, &p.ld_out, d_out, D_, S_, 2, true);
  map_rows(fn, &p.ld_h, h, F_, S_, 2, false);
  map_rows(fn, &p.st_h, h, F_, S_, 1, false);
  map_rows(fn, &p.st_out, d_out, D_, S_, 4, true);
  map_w(fn, &p.w_qkv, d_in[1], D_, 3 * D_, D_, 3);
  map_w(fn, &p.w_o, d_in[2], D_, D_, 64, 2);
  map_w(fn, &p.w_1a, d_in[4], D_, F_, 64, 3);
  map_w(fn, &p.w_1b, d_in[4], D_, F_, 64, 2);
  map_w(fn, &p.w_2, d_in[6], F_, D_, 64, 2);
  cudaFuncSetAttribute(fused_kernel, cudaFuncAttributeMaxDynamicSharedMemorySize, SMEM_BYTES);
  fused_kernel<<<132, 384, SMEM_BYTES>>>((unsigned*)epochs, (const char*)d_in[0], (const char*)d_in[1], p);
}
```

```cpp
#include <cuda_runtime.h>
#include <cuda_bf16.h>
#include <cuda.h>
#include <stdint.h>

#define EXP 0
namespace {

constexpr int S_ = 2048, D_ = 1024, F_ = 3584;
constexpr int A_BYTES = 16384;
constexpr int OFF_X   = 163840;
constexpr int OFF_STG = OFF_X + 32768;
constexpr int OFF_CSQ = OFF_STG + 20480;
constexpr int OFF_UP  = OFF_CSQ + 1536;
constexpr int OFF_B2  = OFF_UP + 3584;
constexpr int OFF_RST = OFF_B2 + 512 + 256;
constexpr int OFF_FULL = OFF_RST + 1024;
constexpr int OFF_EMPTY = OFF_FULL + 64;
constexpr int OFF_XBAR = OFF_EMPTY + 64;
constexpr int OFF_TBL = OFF_XBAR + 8;
constexpr int OFF_HALO = OFF_XBAR + 48;
constexpr int OFF_SLOT = OFF_XBAR + 88;
constexpr int OFF_PRE = OFF_XBAR + 72;
constexpr int OFF_ZERO = OFF_XBAR + 96;
constexpr int OFF_TAG = OFF_ZERO + 16;
constexpr int OFF_PLAN = OFF_TAG + 16, PLAN_BYTES = 5120;
constexpr int SMEM_BYTES = OFF_PLAN + PLAN_BYTES + 48 + 1024;
constexpr int KB_LAYER = 6 * 16 + 56;
constexpr int NCS = 384 + 448;
constexpr unsigned SPIN_LIMIT = 1u << 20;
constexpr int NS = 12, NP = 8, SA = 7, SB = 11, PAUSE1 = 7, PAUSE2 = 8, HGK = 8, HGO = 11, HG1 = 3;
constexpr int SK = 3;
constexpr uint32_t DESC_A = 1u << 16, DESC_B = (512u << 16) + A_BYTES / 16;
enum { BAR_START = 1, BAR_EPI = 3, BAR_WG = 5, BAR_P0 = 7, BAR_P1 = 8, BAR_RES = 9, BAR_READY = 10, BAR_FREE = 11, BAR_COPY = 12, BAR_RES2 = 13, BAR_HGO = 14 };

struct Params {
  CUtensorMap ld_x, ld_out, ld_h, st_h, st_out, w_qkv, w_o, w_1a, w_1b, w_2;
  const __nv_bfloat16 *b1, *b2;
};

__device__ __align__(1024) __nv_bfloat16 g_h[S_ * F_];
__device__ __align__(128) uint4 g_stats[4 * S_ * 8];
__device__ __align__(128) uint2 g_cs[8 * NCS];
__device__ __align__(128) uint4 g_halo[4 * 128 * 11 * 32];
__device__ __align__(128) unsigned g_flags[14 * 16 * 32];
#define TL(t, e)
#define PTL(t, e)
#if !defined(TIMELINE) || !(EXP & 8)
#undef TK
#define TK(t, k)
#endif

template<int N, int KEEP> __device__ __forceinline__ void wgmma_ss(float (&d)[96], uint32_t da, uint32_t db);
template<> __device__ __forceinline__ void wgmma_ss<128, 0>(float (&d)[96], uint32_t da, uint32_t db) {
  asm volatile("{\n.reg .pred p;\n.reg .b64 a, b;\nsetp.ne.b32 p, 0, 0;\nmov.b64 a, {%64, 0x40000080};\nmov.b64 b, {%65, 0x40000040};\nwgmma.mma_async.sync.aligned.m64n128k16.f32.bf16.bf16 {%0, %1, %2, %3, %4, %5, %6, %7, %8, %9, %10, %11, %12, %13, %14, %15, %16, %17, %18, %19, %20, %21, %22, %23, %24, %25, %26, %27, %28, %29, %30, %31, %32, %33, %34, %35, %36, %37, %38, %39, %40, %41, %42, %43, %44, %45, %46, %47, %48, %49, %50, %51, %52, %53, %54, %55, %56, %57, %58, %59, %60, %61, %62, %63}, a, b, p, 1, 1, 0, 1;\n}"
    : "=f"(d[0]), "=f"(d[1]), "=f"(d[2]), "=f"(d[3]), "=f"(d[4]), "=f"(d[5]), "=f"(d[6]), "=f"(d[7]), "=f"(d[8]), "=f"(d[9]), "=f"(d[10]), "=f"(d[11]), "=f"(d[12]), "=f"(d[13]), "=f"(d[14]), "=f"(d[15]), "=f"(d[16]), "=f"(d[17]), "=f"(d[18]), "=f"(d[19]), "=f"(d[20]), "=f"(d[21]), "=f"(d[22]), "=f"(d[23]), "=f"(d[24]), "=f"(d[25]), "=f"(d[26]), "=f"(d[27]), "=f"(d[28]), "=f"(d[29]), "=f"(d[30]), "=f"(d[31]), "=f"(d[32]), "=f"(d[33]), "=f"(d[34]), "=f"(d[35]), "=f"(d[36]), "=f"(d[37]), "=f"(d[38]), "=f"(d[39]), "=f"(d[40]), "=f"(d[41]), "=f"(d[42]), "=f"(d[43]), "=f"(d[44]), "=f"(d[45]), "=f"(d[46]), "=f"(d[47]), "=f"(d[48]), "=f"(d[49]), "=f"(d[50]), "=f"(d[51]), "=f"(d[52]), "=f"(d[53]), "=f"(d[54]), "=f"(d[55]), "=f"(d[56]), "=f"(d[57]), "=f"(d[58]), "=f"(d[59]), "=f"(d[60]), "=f"(d[61]), "=f"(d[62]), "=f"(d[63])
    : "r"(da), "r"(db));
}
template<> __device__ __forceinline__ void wgmma_ss<128, 1>(float (&d)[96], uint32_t da, uint32_t db) {
  asm volatile("{\n.reg .pred p;\n.reg .b64 a, b;\nsetp.ne.b32 p, 1, 0;\nmov.b64 a, {%64, 0x40000080};\nmov.b64 b, {%65, 0x40000040};\nwgmma.mma_async.sync.aligned.m64n128k16.f32.bf16.bf16 {%0, %1, %2, %3, %4, %5, %6, %7, %8, %9, %10, %11, %12, %13, %14, %15, %16, %17, %18, %19, %20, %21, %22, %23, %24, %25, %26, %27, %28, %29, %30, %31, %32, %33, %34, %35, %36, %37, %38, %39, %40, %41, %42, %43, %44, %45, %46, %47, %48, %49, %50, %51, %52, %53, %54, %55, %56, %57, %58, %59, %60, %61, %62, %63}, a, b, p, 1, 1, 0, 1;\n}"
    : "+f"(d[0]), "+f"(d[1]), "+f"(d[2]), "+f"(d[3]), "+f"(d[4]), "+f"(d[5]), "+f"(d[6]), "+f"(d[7]), "+f"(d[8]), "+f"(d[9]), "+f"(d[10]), "+f"(d[11]), "+f"(d[12]), "+f"(d[13]), "+f"(d[14]), "+f"(d[15]), "+f"(d[16]), "+f"(d[17]), "+f"(d[18]), "+f"(d[19]), "+f"(d[20]), "+f"(d[21]), "+f"(d[22]), "+f"(d[23]), "+f"(d[24]), "+f"(d[25]), "+f"(d[26]), "+f"(d[27]), "+f"(d[28]), "+f"(d[29]), "+f"(d[30]), "+f"(d[31]), "+f"(d[32]), "+f"(d[33]), "+f"(d[34]), "+f"(d[35]), "+f"(d[36]), "+f"(d[37]), "+f"(d[38]), "+f"(d[39]), "+f"(d[40]), "+f"(d[41]), "+f"(d[42]), "+f"(d[43]), "+f"(d[44]), "+f"(d[45]), "+f"(d[46]), "+f"(d[47]), "+f"(d[48]), "+f"(d[49]), "+f"(d[50]), "+f"(d[51]), "+f"(d[52]), "+f"(d[53]), "+f"(d[54]), "+f"(d[55]), "+f"(d[56]), "+f"(d[57]), "+f"(d[58]), "+f"(d[59]), "+f"(d[60]), "+f"(d[61]), "+f"(d[62]), "+f"(d[63])
    : "r"(da), "r"(db));
}
template<> __device__ __forceinline__ void wgmma_ss<192, 0>(float (&d)[96], uint32_t da, uint32_t db) {
  asm volatile("{\n.reg .pred p;\n.reg .b64 a, b;\nsetp.ne.b32 p, 0, 0;\nmov.b64 a, {%96, 0x40000080};\nmov.b64 b, {%97, 0x40000040};\nwgmma.mma_async.sync.aligned.m64n192k16.f32.bf16.bf16 {%0, %1, %2, %3, %4, %5, %6, %7, %8, %9, %10, %11, %12, %13, %14, %15, %16, %17, %18, %19, %20, %21, %22, %23, %24, %25, %26, %27, %28, %29, %30, %31, %32, %33, %34, %35, %36, %37, %38, %39, %40, %41, %42, %43, %44, %45, %46, %47, %48, %49, %50, %51, %52, %53, %54, %55, %56, %57, %58, %59, %60, %61, %62, %63, %64, %65, %66, %67, %68, %69, %70, %71, %72, %73, %74, %75, %76, %77, %78, %79, %80, %81, %82, %83, %84, %85, %86, %87, %88, %89, %90, %91, %92, %93, %94, %95}, a, b, p, 1, 1, 0, 1;\n}"
    : "=f"(d[0]), "=f"(d[1]), "=f"(d[2]), "=f"(d[3]), "=f"(d[4]), "=f"(d[5]), "=f"(d[6]), "=f"(d[7]), "=f"(d[8]), "=f"(d[9]), "=f"(d[10]), "=f"(d[11]), "=f"(d[12]), "=f"(d[13]), "=f"(d[14]), "=f"(d[15]), "=f"(d[16]), "=f"(d[17]), "=f"(d[18]), "=f"(d[19]), "=f"(d[20]), "=f"(d[21]), "=f"(d[22]), "=f"(d[23]), "=f"(d[24]), "=f"(d[25]), "=f"(d[26]), "=f"(d[27]), "=f"(d[28]), "=f"(d[29]), "=f"(d[30]), "=f"(d[31]), "=f"(d[32]), "=f"(d[33]), "=f"(d[34]), "=f"(d[35]), "=f"(d[36]), "=f"(d[37]), "=f"(d[38]), "=f"(d[39]), "=f"(d[40]), "=f"(d[41]), "=f"(d[42]), "=f"(d[43]), "=f"(d[44]), "=f"(d[45]), "=f"(d[46]), "=f"(d[47]), "=f"(d[48]), "=f"(d[49]), "=f"(d[50]), "=f"(d[51]), "=f"(d[52]), "=f"(d[53]), "=f"(d[54]), "=f"(d[55]), "=f"(d[56]), "=f"(d[57]), "=f"(d[58]), "=f"(d[59]), "=f"(d[60]), "=f"(d[61]), "=f"(d[62]), "=f"(d[63]), "=f"(d[64]), "=f"(d[65]), "=f"(d[66]), "=f"(d[67]), "=f"(d[68]), "=f"(d[69]), "=f"(d[70]), "=f"(d[71]), "=f"(d[72]), "=f"(d[73]), "=f"(d[74]), "=f"(d[75]), "=f"(d[76]), "=f"(d[77]), "=f"(d[78]), "=f"(d[79]), "=f"(d[80]), "=f"(d[81]), "=f"(d[82]), "=f"(d[83]), "=f"(d[84]), "=f"(d[85]), "=f"(d[86]), "=f"(d[87]), "=f"(d[88]), "=f"(d[89]), "=f"(d[90]), "=f"(d[91]), "=f"(d[92]), "=f"(d[93]), "=f"(d[94]), "=f"(d[95])
    : "r"(da), "r"(db));
}
template<> __device__ __forceinline__ void wgmma_ss<192, 1>(float (&d)[96], uint32_t da, uint32_t db) {
  asm volatile("{\n.reg .pred p;\n.reg .b64 a, b;\nsetp.ne.b32 p, 1, 0;\nmov.b64 a, {%96, 0x40000080};\nmov.b64 b, {%97, 0x40000040};\nwgmma.mma_async.sync.aligned.m64n192k16.f32.bf16.bf16 {%0, %1, %2, %3, %4, %5, %6, %7, %8, %9, %10, %11, %12, %13, %14, %15, %16, %17, %18, %19, %20, %21, %22, %23, %24, %25, %26, %27, %28, %29, %30, %31, %32, %33, %34, %35, %36, %37, %38, %39, %40, %41, %42, %43, %44, %45, %46, %47, %48, %49, %50, %51, %52, %53, %54, %55, %56, %57, %58, %59, %60, %61, %62, %63, %64, %65, %66, %67, %68, %69, %70, %71, %72, %73, %74, %75, %76, %77, %78, %79, %80, %81, %82, %83, %84, %85, %86, %87, %88, %89, %90, %91, %92, %93, %94, %95}, a, b, p, 1, 1, 0, 1;\n}"
    : "+f"(d[0]), "+f"(d[1]), "+f"(d[2]), "+f"(d[3]), "+f"(d[4]), "+f"(d[5]), "+f"(d[6]), "+f"(d[7]), "+f"(d[8]), "+f"(d[9]), "+f"(d[10]), "+f"(d[11]), "+f"(d[12]), "+f"(d[13]), "+f"(d[14]), "+f"(d[15]), "+f"(d[16]), "+f"(d[17]), "+f"(d[18]), "+f"(d[19]), "+f"(d[20]), "+f"(d[21]), "+f"(d[22]), "+f"(d[23]), "+f"(d[24]), "+f"(d[25]), "+f"(d[26]), "+f"(d[27]), "+f"(d[28]), "+f"(d[29]), "+f"(d[30]), "+f"(d[31]), "+f"(d[32]), "+f"(d[33]), "+f"(d[34]), "+f"(d[35]), "+f"(d[36]), "+f"(d[37]), "+f"(d[38]), "+f"(d[39]), "+f"(d[40]), "+f"(d[41]), "+f"(d[42]), "+f"(d[43]), "+f"(d[44]), "+f"(d[45]), "+f"(d[46]), "+f"(d[47]), "+f"(d[48]), "+f"(d[49]), "+f"(d[50]), "+f"(d[51]), "+f"(d[52]), "+f"(d[53]), "+f"(d[54]), "+f"(d[55]), "+f"(d[56]), "+f"(d[57]), "+f"(d[58]), "+f"(d[59]), "+f"(d[60]), "+f"(d[61]), "+f"(d[62]), "+f"(d[63]), "+f"(d[64]), "+f"(d[65]), "+f"(d[66]), "+f"(d[67]), "+f"(d[68]), "+f"(d[69]), "+f"(d[70]), "+f"(d[71]), "+f"(d[72]), "+f"(d[73]), "+f"(d[74]), "+f"(d[75]), "+f"(d[76]), "+f"(d[77]), "+f"(d[78]), "+f"(d[79]), "+f"(d[80]), "+f"(d[81]), "+f"(d[82]), "+f"(d[83]), "+f"(d[84]), "+f"(d[85]), "+f"(d[86]), "+f"(d[87]), "+f"(d[88]), "+f"(d[89]), "+f"(d[90]), "+f"(d[91]), "+f"(d[92]), "+f"(d[93]), "+f"(d[94]), "+f"(d[95])
    : "r"(da), "r"(db));
}
template<> __device__ __forceinline__ void wgmma_ss<128, 2>(float (&d)[96], uint32_t da, uint32_t db) {
  asm volatile("{\n.reg .pred p;\n.reg .b64 a, b;\nsetp.ne.b32 p, 2, 0;\nmov.b64 a, {%64, 0x40000040};\nmov.b64 b, {%65, 0x40000040};\nwgmma.mma_async.sync.aligned.m64n128k16.f32.bf16.bf16 {%0, %1, %2, %3, %4, %5, %6, %7, %8, %9, %10, %11, %12, %13, %14, %15, %16, %17, %18, %19, %20, %21, %22, %23, %24, %25, %26, %27, %28, %29, %30, %31, %32, %33, %34, %35, %36, %37, %38, %39, %40, %41, %42, %43, %44, %45, %46, %47, %48, %49, %50, %51, %52, %53, %54, %55, %56, %57, %58, %59, %60, %61, %62, %63}, b, a, p, 1, 1, 1, 0;\n}"
    : "+f"(d[0]), "+f"(d[1]), "+f"(d[2]), "+f"(d[3]), "+f"(d[4]), "+f"(d[5]), "+f"(d[6]), "+f"(d[7]), "+f"(d[8]), "+f"(d[9]), "+f"(d[10]), "+f"(d[11]), "+f"(d[12]), "+f"(d[13]), "+f"(d[14]), "+f"(d[15]), "+f"(d[16]), "+f"(d[17]), "+f"(d[18]), "+f"(d[19]), "+f"(d[20]), "+f"(d[21]), "+f"(d[22]), "+f"(d[23]), "+f"(d[24]), "+f"(d[25]), "+f"(d[26]), "+f"(d[27]), "+f"(d[28]), "+f"(d[29]), "+f"(d[30]), "+f"(d[31]), "+f"(d[32]), "+f"(d[33]), "+f"(d[34]), "+f"(d[35]), "+f"(d[36]), "+f"(d[37]), "+f"(d[38]), "+f"(d[39]), "+f"(d[40]), "+f"(d[41]), "+f"(d[42]), "+f"(d[43]), "+f"(d[44]), "+f"(d[45]), "+f"(d[46]), "+f"(d[47]), "+f"(d[48]), "+f"(d[49]), "+f"(d[50]), "+f"(d[51]), "+f"(d[52]), "+f"(d[53]), "+f"(d[54]), "+f"(d[55]), "+f"(d[56]), "+f"(d[57]), "+f"(d[58]), "+f"(d[59]), "+f"(d[60]), "+f"(d[61]), "+f"(d[62]), "+f"(d[63])
    : "r"(da), "r"(db));
}

__device__ __forceinline__ uint32_t smem_u32(const void* p) { return (uint32_t)__cvta_generic_to_shared(p); }
__device__ __forceinline__ void mbar_arrive_cluster(uint32_t bar) { asm volatile("mbarrier.arrive.shared::cluster.b64 _, [%0];" :: "r"(bar) : "memory"); }
__device__ __forceinline__ void mbar_wait(uint32_t bar, uint32_t parity) {
  asm volatile(
    "{\n.reg .pred p;\n.reg .u32 n;\n"
    "mbarrier.try_wait.parity.shared::cta.b64 p, [%0], %1;\n"
    "@p bra.uni WAIT_DONE;\n"
    "mov.u32 n, 0;\n"
    "WAIT_LOOP:\n"
    "mbarrier.try_wait.parity.shared::cta.b64 p, [%0], %1;\n"
    "@p bra.uni WAIT_DONE;\n"
    "add.u32 n, n, 1;\n"
    "setp.lt.u32 p, n, 0x100000;\n"
    "@p bra.uni WAIT_LOOP;\n"
    "trap;\n"
    "WAIT_DONE:\n}" :: "r"(bar), "r"(parity) : "memory");
}
__device__ __forceinline__ void mbar_pace(uint32_t bar, uint32_t parity) {
  asm volatile(
    "{\n.reg .pred p;\n.reg .u32 n;\nmov.u32 n, 0;\n"
    "PACE_LOOP:\n"
    "mbarrier.try_wait.parity.shared::cta.b64 p, [%0], %1, 1000;\n"
    "add.u32 n, n, 1;\n"
    "setp.lt.and.u32 p, n, 16, !p;\n"
    "@p bra.uni PACE_LOOP;\n}" :: "r"(bar), "r"(parity) : "memory");
}
__device__ __forceinline__ uint32_t mbar_test(uint32_t bar, uint32_t parity) {
  uint32_t ok;
  asm volatile("{\n.reg .pred p;\nmbarrier.test_wait.parity.shared::cta.b64 p, [%1], %2;\nselp.u32 %0, 1, 0, p;\n}" : "=r"(ok) : "r"(bar), "r"(parity) : "memory");
  return ok;
}
#define ELECT "{\n.reg .pred p;\nelect.sync _|p, 0xffffffff;\n"
__device__ __forceinline__ void mbar_init_e(uint32_t bar, uint32_t cnt) { asm volatile(ELECT "@p mbarrier.init.shared::cta.b64 [%0], %1;\n}" :: "r"(bar), "r"(cnt) : "memory"); }
__device__ __forceinline__ void mbar_arrive_e(uint32_t bar) { asm volatile(ELECT "@p mbarrier.arrive.shared::cta.b64 _, [%0];\n}" :: "r"(bar) : "memory"); }
__device__ __forceinline__ void mbar_expect_e(uint32_t bar, uint32_t bytes) { asm volatile(ELECT "@p mbarrier.arrive.expect_tx.shared::cta.b64 _, [%0], %1;\n}" :: "r"(bar), "r"(bytes) : "memory"); }
__device__ __forceinline__ void tma_ld4_e(uint32_t dst, const CUtensorMap* m, uint32_t bar, int c0, int c3) {
  asm volatile(ELECT "@p cp.async.bulk.tensor.4d.shared::cluster.global.mbarrier::complete_tx::bytes [%0], [%1, {%3, %5, %5, %4}], [%2];\n}"
    :: "r"(dst), "l"(m), "r"(bar), "r"(c0), "r"(c3), "r"(0) : "memory");
}
__device__ __forceinline__ void tma_ld4_mc_e(uint32_t dst, const CUtensorMap* m, uint32_t bar, int c0, int c3, uint16_t mask = 3) {
  asm volatile(ELECT "@p cp.async.bulk.tensor.4d.shared::cluster.global.mbarrier::complete_tx::bytes.multicast::cluster [%0], [%1, {%3, %5, %5, %4}], [%2], %6;\n}"
    :: "r"(dst), "l"(m), "r"(bar), "r"(c0), "r"(c3), "r"(0), "h"(mask) : "memory");
}
__device__ __forceinline__ void tma_ld3_e(uint32_t dst, const CUtensorMap* m, uint32_t bar, int c0, int c1, int c2) {
  asm volatile(ELECT "@p cp.async.bulk.tensor.3d.shared::cluster.global.mbarrier::complete_tx::bytes [%0], [%1, {%3, %4, %5}], [%2];\n}"
    :: "r"(dst), "l"(m), "r"(bar), "r"(c0), "r"(c1), "r"(c2) : "memory");
}
__device__ __forceinline__ void tma_st4_e(const CUtensorMap* m, uint32_t src, int c0, int c3) {
  asm volatile(ELECT "@p cp.async.bulk.tensor.4d.global.shared::cta.bulk_group [%0, {%2, %4, %4, %3}], [%1];\n}"
    :: "l"(m), "r"(src), "r"(c0), "r"(c3), "r"(0) : "memory");
}
__device__ __forceinline__ void dsmem_copy_e(uint32_t dst, uint32_t src, uint32_t bar) {
  asm volatile(ELECT "@p cp.async.bulk.shared::cluster.shared::cta.mbarrier::complete_tx::bytes [%0], [%1], 16384, [%2];\n}"
    :: "r"(dst), "r"(src), "r"(bar) : "memory");
}
__device__ __forceinline__ void bulk_wait_read_e() { asm volatile(ELECT "@p cp.async.bulk.commit_group;\n@p cp.async.bulk.wait_group.read 0;\n}" ::: "memory"); __syncwarp(); }
__device__ __forceinline__ void publish_e(unsigned* flag, unsigned tag) {
  asm volatile(ELECT "@p fence.proxy.async;\n@p st.relaxed.gpu.global.u32 [%0], %1;\n}" :: "l"(flag), "r"(tag) : "memory");
  __syncwarp();
}
__device__ __forceinline__ void fence_async_smem() { asm volatile("fence.proxy.async.shared::cta;" ::: "memory"); }
__device__ __forceinline__ void wgmma_fence() { asm volatile("wgmma.fence.sync.aligned;" ::: "memory"); }
__device__ __forceinline__ void wgmma_commit() { asm volatile("wgmma.commit_group.sync.aligned;" ::: "memory"); }
template<int N> __device__ __forceinline__ void wgmma_wait() { asm volatile("wgmma.wait_group.sync.aligned %0;" :: "n"(N) : "memory"); }
__device__ __forceinline__ void bar_sync(int id, int n) { asm volatile("bar.sync %0, %1;" :: "r"(id), "r"(n) : "memory"); }
__device__ __forceinline__ void bar_arrive(int id, int n) { asm volatile("bar.arrive %0, %1;" :: "r"(id), "r"(n) : "memory"); }
__device__ __forceinline__ void bar_arrive_here(int id, float dep, float zero) {
  asm volatile("{\n.reg .pred p;\n.reg .u32 n;\nsetp.ne.u32 p, %2, 0;\nor.b32 n, %1, 256;\nmin.u32 n, n, 256;\nAGAIN:\nbar.arrive %0, n;\n@p bra.uni AGAIN;\n}"
    :: "r"(id), "r"(__float_as_uint(dep)), "r"(__float_as_uint(zero)) : "memory");
}
__device__ __forceinline__ void bar_sync_after(int id, uint32_t dep) {
  asm volatile("{\n.reg .u32 n;\nor.b32 n, %1, 256;\nmin.u32 n, n, 256;\nbar.sync %0, n;\n}" :: "r"(id), "r"(dep) : "memory");
}
__device__ __forceinline__ uint32_t mapa(uint32_t a, uint32_t r) { uint32_t d; asm("mapa.shared::cluster.u32 %0, %1, %2;" : "=r"(d) : "r"(a), "r"(r)); return d; }
__device__ __forceinline__ void st_tag128(uint4* p, uint32_t a, uint32_t b, uint32_t c, uint32_t tag) {
  asm volatile("{\n.reg .b64 lo, hi;\n.reg .b128 v;\nmov.b64 lo, {%1, %2};\nmov.b64 hi, {%3, %4};\nmov.b128 v, {lo, hi};\nst.relaxed.gpu.global.b128 [%0], v;\n}"
    :: "l"(p), "r"(a), "r"(b), "r"(c), "r"(tag) : "memory");
}
__device__ __forceinline__ void st_tag128_if(bool on, uint4* p, uint32_t a, uint32_t b, uint32_t c, uint32_t tag) {
  asm volatile("{\n.reg .pred q;\n.reg .b64 lo, hi;\n.reg .b128 v;\nsetp.ne.u32 q, %5, 0;\nmov.b64 lo, {%1, %2};\nmov.b64 hi, {%3, %4};\nmov.b128 v, {lo, hi};\n@q st.relaxed.gpu.global.b128 [%0], v;\n}"
    :: "l"(p), "r"(a), "r"(b), "r"(c), "r"(tag), "r"((uint32_t)on) : "memory");
}
__device__ __forceinline__ uint4 ld_tag128(const uint4* p) {
  uint4 v;
  asm volatile("{\n.reg .b64 lo, hi;\n.reg .b128 v;\nld.relaxed.gpu.global.b128 v, [%4];\nmov.b128 {lo, hi}, v;\nmov.b64 {%0, %1}, lo;\nmov.b64 {%2, %3}, hi;\n}"
    : "=r"(v.x), "=r"(v.y), "=r"(v.z), "=r"(v.w) : "l"(p) : "memory");
  return v;
}
__device__ __forceinline__ void st_tag64(uint2* p, float a, uint32_t tag) {
  asm volatile("{\n.reg .b64 v;\nmov.b64 v, {%1, %2};\nst.relaxed.gpu.global.b64 [%0], v;\n}" :: "l"(p), "r"(__float_as_uint(a)), "r"(tag) : "memory");
}
__device__ __forceinline__ uint2 ld_tag64(const uint2* p) {
  uint2 v;
  asm volatile("{\n.reg .b64 v;\nld.relaxed.gpu.global.b64 v, [%2];\nmov.b64 {%0, %1}, v;\n}" : "=r"(v.x), "=r"(v.y) : "l"(p) : "memory");
  return v;
}
__device__ __forceinline__ uint32_t pack_bf16(float lo, float hi) { uint32_t r; asm("cvt.rn.bf16x2.f32 %0, %1, %2;" : "=r"(r) : "f"(hi), "f"(lo)); return r; }
__device__ __forceinline__ uint32_t relu_sq_bf16(float lo, float hi) {
  uint32_t r; asm("{\n.reg .b32 t;\ncvt.rn.relu.bf16x2.f32 t, %1, %2;\nmul.rn.bf16x2 %0, t, t;\n}" : "=r"(r) : "f"(hi), "f"(lo)); return r;
}
__device__ __forceinline__ float bf_lo(uint32_t u) { return __uint_as_float(u << 16); }
__device__ __forceinline__ float bf_hi(uint32_t u) { return __uint_as_float(u & 0xffff0000u); }
__device__ __forceinline__ void stmatrix4(uint32_t addr, uint32_t r0, uint32_t r1, uint32_t r2, uint32_t r3) {
  asm volatile("stmatrix.sync.aligned.m8n8.x4.shared.b16 [%0], {%1, %2, %3, %4};" :: "r"(addr), "r"(r0), "r"(r1), "r"(r2), "r"(r3) : "memory");
}
__device__ __forceinline__ void ldmatrix4(uint32_t addr, uint32_t (&r)[4]) {
  asm volatile("ldmatrix.sync.aligned.m8n8.x4.shared.b16 {%0, %1, %2, %3}, [%4];" : "=r"(r[0]), "=r"(r[1]), "=r"(r[2]), "=r"(r[3]) : "r"(addr) : "memory");
}
__device__ __forceinline__ void stmatrix4_t(uint32_t addr, uint32_t r0, uint32_t r1, uint32_t r2, uint32_t r3) {
  asm volatile("stmatrix.sync.aligned.m8n8.x4.trans.shared.b16 [%0], {%1, %2, %3, %4};" :: "r"(addr), "r"(r0), "r"(r1), "r"(r2), "r"(r3) : "memory");
}
__device__ __forceinline__ void ldmatrix4_t(uint32_t addr, uint32_t (&r)[4]) {
  asm volatile("ldmatrix.sync.aligned.m8n8.x4.trans.shared.b16 {%0, %1, %2, %3}, [%4];" : "=r"(r[0]), "=r"(r[1]), "=r"(r[2]), "=r"(r[3]) : "r"(addr) : "memory");
}
__device__ __forceinline__ uint32_t movmatrix(uint32_t a) { uint32_t d; asm volatile("movmatrix.sync.aligned.m8n8.trans.b16 %0, %1;" : "=r"(d) : "r"(a)); return d; }
__device__ __forceinline__ void mma16816_z(float (&c)[4], uint32_t a0, uint32_t a1, uint32_t a2, uint32_t a3, uint32_t b0, uint32_t b1, const float4& z) {
  asm volatile("mma.sync.aligned.m16n8k16.row.col.f32.bf16.bf16.f32 {%0,%1,%2,%3}, {%4,%5,%6,%7}, {%8,%9}, {%10,%11,%12,%13};"
    : "=f"(c[0]), "=f"(c[1]), "=f"(c[2]), "=f"(c[3]) : "r"(a0), "r"(a1), "r"(a2), "r"(a3), "r"(b0), "r"(b1), "f"(z.x), "f"(z.y), "f"(z.z), "f"(z.w));
}
__device__ __forceinline__ float ex2(float x) { float y; asm("ex2.approx.ftz.f32 %0, %1;" : "=f"(y) : "f"(x)); return y; }
__device__ __forceinline__ float rcp(float x) { float y; asm("rcp.approx.ftz.f32 %0, %1;" : "=f"(y) : "f"(x)); return y; }
__device__ __forceinline__ void mma16816(float (&c)[4], uint32_t a0, uint32_t a1, uint32_t a2, uint32_t a3, uint32_t b0, uint32_t b1) {
  asm volatile("mma.sync.aligned.m16n8k16.row.col.f32.bf16.bf16.f32 {%0,%1,%2,%3}, {%4,%5,%6,%7}, {%8,%9}, {%0,%1,%2,%3};"
    : "+f"(c[0]), "+f"(c[1]), "+f"(c[2]), "+f"(c[3]) : "r"(a0), "r"(a1), "r"(a2), "r"(a3), "r"(b0), "r"(b1));
}
__device__ __forceinline__ void sts128(uint32_t a, uint32_t x, uint32_t y, uint32_t z, uint32_t w) { asm volatile("st.shared.v4.b32 [%0], {%1,%2,%3,%4};" :: "r"(a), "r"(x), "r"(y), "r"(z), "r"(w) : "memory"); }
__device__ __forceinline__ float2 lds64f(uint32_t a) { float2 v; asm volatile("ld.shared.v2.f32 {%0,%1}, [%2];" : "=f"(v.x), "=f"(v.y) : "r"(a) : "memory"); return v; }
__device__ __forceinline__ float4 lds128f(uint32_t a) { float4 v; asm volatile("ld.shared.v4.f32 {%0,%1,%2,%3}, [%4];" : "=f"(v.x), "=f"(v.y), "=f"(v.z), "=f"(v.w) : "r"(a) : "memory"); return v; }
__device__ __forceinline__ void sts32f(uint32_t a, float v) { asm volatile("st.shared.f32 [%0], %1;" :: "r"(a), "f"(v) : "memory"); }
__device__ __forceinline__ void sts64f(uint32_t a, float x, float y) { asm volatile("st.shared.v2.f32 [%0], {%1,%2};" :: "r"(a), "f"(x), "f"(y) : "memory"); }
__device__ __forceinline__ uint32_t lds32(uint32_t a) { uint32_t v; asm volatile("ld.shared.u32 %0, [%1];" : "=r"(v) : "r"(a) : "memory"); return v; }
__device__ __forceinline__ float after(float x, uint32_t d, uint32_t zero) { return __uint_as_float(__float_as_uint(x) | (d & zero)); }
template<int R> __device__ __forceinline__ void reg_alloc() { asm volatile("setmaxnreg.inc.sync.aligned.u32 %0;" :: "n"(R)); }
template<int R> __device__ __forceinline__ void reg_dealloc() { asm volatile("setmaxnreg.dec.sync.aligned.u32 %0;" :: "n"(R)); }

struct Ctx {
  uint32_t sb;
  int m, j, b, rank, wg, w, lane;
};

__device__ __forceinline__ unsigned smem_tag(const Ctx& c) { return lds32(c.sb + OFF_TAG); }
__device__ __forceinline__ int smem_block(const Ctx& c) { return lds32(c.sb + OFF_TAG + 8); }

struct WTile { int map, c0, c2; };
__host__ __device__ constexpr WTile wtile(int type, int j) {
  return WTile{128 * (type < 2 ? 5 : type < 5 ? type + 4 : type + 3), type < 2 ? (j + 8 * type) * 64 : 0,
               type < 2 ? 0 : type == 3 ? 3 * j : type == 4 ? 24 + 2 * j : type == 5 ? 40 + 2 * j : 2 * j};
}
__host__ __device__ constexpr int first_stage(int type, int part) { return ((part == 0 ? 0x2000422 : part == 1 ? 0x2 : 0x2002) >> (4 * type)) & 7; }

enum { A_NEW = 1 << 9, A_QUIET = 1 << 10, A_NONE = 1 << 11, A_PAIR = 2 << 11, A_COPY = 3 << 11 };
struct Plan {
  unsigned epoch[256];
  uint32_t v[8][PLAN_BYTES / 4];
};
constexpr Plan make_plan() {
  Plan plan{};
  for (int j = 0; j < 8; j++)
    for (int g = 4; g < 2 * KB_LAYER; g++) {
      const int layer = g >= KB_LAYER, r = g - layer * KB_LAYER;
      const bool split = (r >= 48 && r < 80) || (layer && r < 32);
      const int q = r - (r >= 48 ? 48 : 0);
      const bool head = split && q < 4, second = split && (head ? q >= 2 : q >= 18), lead = split && !second;
      const int type = split ? (r >= 48 ? 3 : 0) + second : r < 96 ? r >> 4 : 6, t = layer * 7 + type;
      const int step = !split ? r - 16 * type : head ? q & 1 : q - (second ? 16 : 2), n = step - (split && !head ? 2 : 0);
      const bool wide = type < 2 || type == 3;
      const int ns = wide || head ? 4 : 5, lag = type == 2 ? 3 : 4;
      const int e = g - (split && q && q < (r < 48 ? 4 : 6) ? 5 + (r >= 48 && q > 1) : n + 1 > ns ? ns : n + 1 > lag ? n + 1 : lag);
      const int v = (int)(0xfb7d95ea6c842310ull >> (4 * (step & 15))) & 15;
      const int kb = split ? (v < 4 ? (j * 2) ^ v : ((j >> 1) * 4 + v) & 15) : type != 2 || step < 8 ? step : step < 10 ? j ^ step : 8 + (((j & 6) + step) & 7);
      const uint32_t x = kb * 64 + (first_stage(type, head ? 1 : 2 * split) + n) % ns * (163840 / ns);
      const bool local = type == 2 && (step >> 1) == 4;
      const int act = split && step < 4 ? (head || lead ? A_NONE : A_PAIR) : local ? (step == 8 ? A_NONE : A_COPY) : 0;
      const uint32_t piece = type == 6 ? (step < 24 ? step / 3 : (step >> 1) - 4) : (type == 2 ? !local : lead ? step >= 4 : second && step == 2) ? kb : 31;
      const int ea = split && act == A_NONE ? g - 8 - (step == 3) : e;
      const WTile w = wtile(type, j);
      uint32_t* d = plan.v[j] + (g - 4) * 4;
      d[0] = x + ((ea >> 3) & 1) + (ea & 7) * 8 + (act ? 0 : (j & 1) * 8192) + (piece << 27);
      d[1] = (!head ? A_BYTES : lead ? 4 : 0) + (type == 2 || type == 6 ? 256 : t < 2 ? 0 : 128) + act + (n == 0 && !second ? A_NEW : 0) +
             (local && step == 8 ? A_QUIET : 0) + ((uint32_t)(t - second) << 27);
      d[2] = x + ((e >> 3) & 1) + (e & 7) * 8 + (!head || !type ? A_BYTES : wide ? 0 : 24576) + ((uint32_t)w.c2 << 26);
      d[3] = w.c0 + (wide ? 24576 : 16384) + (w.map << 16);
    }
  return plan;
}
__device__ __align__(128) Plan g_plan = make_plan();

template<int NL>
__device__ __forceinline__ void row_stats(const Ctx& c, int t) {
  const int ln = t / 3;
  const unsigned tag = smem_tag(c);
  const int row = c.w * 32 + c.lane + lds32(c.sb + OFF_ZERO);
  float s = 0.f, q = 0.f;
  const uint32_t xr = c.sb + OFF_X + row * 128 + (row & 7) * 16;
#pragma unroll 1
  for (int i = 0; i < 128; i += 16) {
    const float4 v = lds128f(xr ^ i), w = lds128f((xr ^ i) + A_BYTES);
    const float u[8] = {v.x, v.y, v.z, v.w, w.x, w.y, w.z, w.w};
#pragma unroll
    for (int z = 0; z < 16; z++) { const float x = z & 1 ? bf_hi(__float_as_uint(u[z >> 1])) : bf_lo(__float_as_uint(u[z >> 1])); s += x; q = fmaf(x, x, q); }
  }
  if (NL == 8) TL(-1, 6);
  if (NL == 4) mbar_pace(c.sb + OFF_FULL + 8 * SA, ln >> 1);
  const int b = smem_block(c);
  st_tag128(g_stats + (ln * 128 + b) * 128 + row, __float_as_uint(s), __float_as_uint(q), 0u, tag);
  mbar_pace(c.sb + (NL == 4 ? OFF_FULL + 8 * (SB & 7) : OFF_EMPTY + 16), (ln >> 1) ^ 1);
  const uint4* p = g_stats + (ln * 128 + (b & ~7)) * 128 + row;
  for (unsigned it = 0;; it++) {
    bool ok = true;
    s = 0.f; q = 0.f;
#pragma unroll 1
    for (int h = 0; h < 8; h += NL) {
      uint4 v[NL];
#pragma unroll
      for (int i = 0; i < NL; i++) v[i] = ld_tag128(p + (h + i) * 128);
#pragma unroll
      for (int i = 0; i < NL; i++) { ok = ok && v[i].w == tag; s += __uint_as_float(v[i].x); q += __uint_as_float(v[i].y); }
    }
    if (__all_sync(0xffffffffu, ok) || it > SPIN_LIMIT) break;
    __nanosleep(NL == 4 ? 400 : 100);
  }
  const float mean = s * (1.0f / D_);
  const float var = fmaxf(q * (1.0f / D_) - mean * mean, 0.0f);
  sts64f(c.sb + OFF_RST + row * 8, rsqrtf(var + 1e-5f), -mean);
  if ((EXP & 256) && NL == 8) sts32f(c.sb + OFF_TAG + 12, __int_as_float(row + 77));
  if ((EXP & 512) && NL == 4) sts32f(c.sb + OFF_TAG + 12, __int_as_float(row + 77));
  bar_arrive(BAR_EPI + (c.wg ^ 1), 256);
  TL(t - 2, 5);
}

__device__ __forceinline__ uint32_t res_addr(const Ctx& c) {
  return c.sb + OFF_X + ((c.lane >> 4) * 8 + (c.lane & 7)) * 128 + (((2 * c.w + ((c.lane >> 3) & 1)) ^ (c.lane & 7)) << 4);
}

template<int BN, int RES>
__device__ __forceinline__ void mainloop(const Ctx& c, float (&acc)[2][96], int t, int type, int g, int nkb) {
  constexpr int NS = BN == 192 ? 4 : 5, STR = BN == 192 ? 40960 : 32768;
  const bool split = !RES && (BN == 192 ? t > 1 : type == 4), second = BN == 128 || type == 1;
  int st = first_stage(type, split);
  if (split && second) g -= 14;
  const uint32_t rel = mapa(c.sb + OFF_EMPTY, c.lane & 1);
  const uint32_t sb = (c.sb & 0x3ffffu) >> 4;
  const uint32_t hb = BN == 192 && split && type ? 1024 : 0;
  uint32_t da = DESC_A + sb + (split ? OFF_X / 16 : st * (STR / 16)), db = DESC_B + sb + (BN == 128 && split ? 512 : st * (STR / 16) - hb);
  TL(t, 0);
  bar_sync(BAR_START + c.wg, 256);
  if (RES && type == 2) bar_sync(BAR_P1, 256);
  TL(t, 1);
  mbar_wait(c.sb + OFF_FULL + 8 * (g & 7), (g >> 3) & 1);
  TL(t, 2);
  wgmma_fence();
#define MMA(i, k, keep) wgmma_ss<BN, RES ? 2 : keep>(acc[i], da + (k) * 2 + (RES ? 0 : 64 * (i)), db + (k) * 128 + (RES ? 512 * (i) : 0))
  MMA(0, 0, 0); MMA(1, 0, 0); MMA(0, 1, 1); MMA(1, 1, 1);
  wgmma_commit();
  wgmma_fence();
  MMA(0, 2, 1); MMA(1, 2, 1); MMA(0, 3, 1); MMA(1, 3, 1);
  wgmma_commit();
  const int pause = BN == 192 && type == 1 ? (split ? PAUSE2 : PAUSE1) : nkb;
  int kb = 1, lim = split ? 2 : pause, pass = split ? 2 : !RES && type != 1 ? nkb : 0;
  uint32_t other = BAR_START + (c.wg ^ 1), prev = c.lane < 2 ? rel + 8 * (g & 7) : 0;
  asm volatile("" : "+r"(other));
  if (++st == NS) st = 0;
  g++;
  da = DESC_A + sb + (split ? (OFF_X + A_BYTES) / 16 : st * (STR / 16));
  db = DESC_B + sb + (BN == 128 && split ? 3072 : st * (STR / 16) - hb);
#pragma unroll 1
  for (;;) {
    mbar_wait(c.sb + OFF_FULL + 8 * (g & 7), (g >> 3) & 1);
    bool more;
#pragma unroll 1
    do {
      wgmma_fence();
      MMA(0, 0, 1); MMA(1, 0, 1); MMA(0, 1, 1); MMA(1, 1, 1);
      wgmma_commit();
      wgmma_wait<1>();
      if (prev) mbar_arrive_cluster(prev);
      TK(t, kb);
      prev = c.lane < 2 ? rel + 8 * (g & 7) : 0;
      kb++; g++;
      if (++st == NS) st = 0;
      wgmma_fence();
      if (BN == 128 && kb == pass) bar_arrive(other, 256);
      MMA(0, 2, 1); MMA(1, 2, 1);
      if (BN == 192 && kb == pass) bar_arrive(other, 256);
      const uint32_t ok = mbar_test(c.sb + OFF_FULL + 8 * (g & 7), (g >> 3) & 1);
      MMA(0, 3, 1); MMA(1, 3, 1);
      wgmma_commit();
      more = __all_sync(0xffffffffu, ok) && kb != lim;
      da = DESC_A + sb + (RES && type == 2 && kb == 8 ? OFF_STG / 16 : st * (STR / 16));
      db = DESC_B + sb + st * (STR / 16);
    } while (more);
    if (kb != lim) continue;
    if (RES || kb == nkb) break;
    if (BN == 128 || kb == 2) {
      wgmma_wait<0>();
      if (prev) mbar_arrive_cluster(prev);
      TK(t, 16);
      if (second) row_stats<4>(c, t);
      g += second ? 14 : 2;
      st = first_stage(type, 2);
      da = DESC_A + sb + st * (STR / 16); db = DESC_B + sb + st * (STR / 16);
      lim = pause; pass = type != 1 ? nkb : 0; prev = 0;
      bar_sync(BAR_START + c.wg, 256);
    } else {
      bar_sync(BAR_P0, 256); bar_sync(BAR_P1, 256);
      lim = kb == pause ? pause + 2 : nkb;
    }
  }
  if (!RES) return;
#define PAIR(i, n) wgmma_ss<128, 2>(acc[i], da + ((n) >> 2) * 2048 + ((n) & 3) * 2, db + ((n) >> 2) * 2048 + ((n) & 3) * 128 + 512 * (i))
#define PUT(z) do { const float* a = acc[(z) >> 3] + ((z) & 7) * 8; \
    stmatrix4_t(xw + (z) * 2048, pack_bf16(a[0], a[1]), pack_bf16(a[2], a[3]), pack_bf16(a[4], a[5]), pack_bf16(a[6], a[7])); } while (0)
  const uint32_t xw = res_addr(c);
#pragma unroll
  for (int n = 0; n < 4 * SK; n++) {
    if (!(n & 3)) { mbar_wait(c.sb + OFF_FULL + 8 * (8 - SK + n / 4), (g >> 3) & 1); wgmma_fence(); }
    PAIR(0, n);
    if (n == 3) { wgmma_commit(); wgmma_wait<1>(); if (prev) mbar_arrive_cluster(prev); wgmma_fence(); }
  }
  wgmma_commit();
#pragma unroll
  for (int n = 0; n < 4 * SK; n++) {
    if (n == 4 * SK - 2 && t < 13) bar_arrive(other, 256);
    PAIR(1, n);
    wgmma_commit();
#pragma unroll
    for (int z = 0; z < 8; z++) if (z / 4 + 2 == n) PUT(z);
    if (n == 3) bar_arrive(BAR_RES, 160);
    if (n && n < 4 * SK - 1) wgmma_wait<2>();
    if (n > 4 && (n & 3) == 1 && c.lane < 2) mbar_arrive_cluster(rel + 8 * (7 - SK + n / 4));
  }
  wgmma_wait<0>();
  if (c.lane < 2) mbar_arrive_cluster(rel + 56);
  TL(t, 3);
#pragma unroll
  for (int nt = 8; nt < 16; nt++) PUT(nt);
  fence_async_smem();
  __syncwarp();
  asm volatile(ELECT "@p mbarrier.complete_tx.relaxed.cta.shared::cta.b64 [%0], 1;\n}" :: "r"(c.sb + OFF_FULL + 8) : "memory");
  bar_arrive(BAR_RES2, 160);
#undef MMA
#undef PAIR
#undef PUT
}
__device__ __forceinline__ void release(const Ctx& c, int slot, int lanes = 2) {
  if (c.lane < lanes) mbar_arrive_cluster(mapa(c.sb + OFF_EMPTY, c.lane & 1) + 8 * slot);
}
__device__ __forceinline__ void finish(const Ctx& c, int t, int slot) {
  wgmma_wait<0>();
  release(c, slot);
  TL(t, 3);
}

__device__ __forceinline__ void put_halo(uint32_t addr, bool last, uint32_t a, uint32_t b, uint32_t c, uint32_t d) {
  if (!last) stmatrix4(addr, a, b, c, d);
  else asm volatile("stmatrix.sync.aligned.m8n8.x2.shared.b16 [%0], {%1, %2};\nstmatrix.sync.aligned.m8n8.x1.shared.b16 [%0 + 256], {%3};" :: "r"(addr), "r"(a), "r"(b), "r"(c) : "memory");
}

__device__ __forceinline__ void fetch_halo(const Ctx& c, unsigned tag, int tile) {
  const int v = c.w & 1;
  const uint4* src = g_halo + (tile * 128 + c.b - 8) * 352 + v * 160 + c.lane;
  uint4 G[6];
#pragma unroll
  for (int z = 0; z < 6; z++) G[z] = make_uint4(0u, 0u, 0u, 0u);
  bar_sync(BAR_HGO + v, 64);
  for (unsigned it = 0; c.m > 0; it++) {
    bool ok = true;
    if (it && !(tile & 1)) __nanosleep(200);
#pragma unroll
    for (int z = 0; z < 6; z++) { G[z] = ld_tag128(src + z * 32); ok = ok && G[z].w == tag; }
    if (__all_sync(0xffffffffu, ok) || it > SPIN_LIMIT) break;
  }
#pragma unroll
  for (int z = 0; z < 6; z++) put_halo(c.sb + OFF_STG + c.lane * 16 + (z ? (v * 5 + z) * 384 - 128 : v * 1792), z == 5, G[z].x, G[z].y, G[z].z, G[z].w);
  if (!v) sts32f(c.sb + OFF_RST - 256 + c.lane * 8, __uint_as_float(G[0].z));
  __syncwarp();
  mbar_arrive_e(c.sb + OFF_HALO + 8 * v);
}

template<int SKEW>
__device__ __forceinline__ void conv_qkv(const Ctx& c, float (&acc)[2][96], uint32_t (&P)[3][2][4][4], int t) {
  const int lane = c.lane, w = c.w, g = lane >> 2, cc = lane & 3;
  const int layer = t >= 7;
  const uint32_t sb = (c.sb & 0x3ffffu) >> 4, par = layer ^ 1;
  uint32_t da = DESC_A + sb + 7680 + 64, db = DESC_B + sb + 7680;
#define MMA(i, n) if (SKEW) do { wgmma_ss<192, 1>(acc[i], da, db); \
    asm volatile("add.s32 %0, %0, %2;\nadd.s32 %1, %1, %3;" : "+r"(da), "+r"(db) : "r"((n) == 11 ? 5050 : (n) == 7 ? 2554 : (n) == 3 ? -7686 : 2), "r"((n) == 11 ? 4736 : (n) == 7 ? 2176 : (n) == 3 ? -8064 : 128)); } while (0)
  const uint32_t rst = c.sb + OFF_RST + w * 256, csb = c.sb + OFF_CSQ + SKEW * 768 + cc * 16, stg = c.sb + OFF_STG + w * 4096;
  float mu[4];
  uint32_t tag, rs_l;
  uint4* halo;
  bool send;
#define SETUP do { _Pragma("unroll") for (int r = 0; r < 4; r++) mu[r] = __uint_as_float(lds32(rst + (8 * r + g) * 8 + 4)); \
    tag = smem_tag(c); rs_l = lds32(rst + lane * 8); \
    const int b = smem_block(c); \
    halo = g_halo + ((layer * 2 + SKEW) * 128 + b) * 352 + lane; send = w == 3 && b < 120; \
    if (SKEW) asm volatile("" : "+l"(halo)); } while (0)
  if (SKEW) {
    mbar_wait(c.sb + OFF_FULL + 40, par);
    wgmma_fence();
    MMA(1, 0); MMA(1, 1); MMA(1, 2); MMA(1, 3);
    wgmma_commit();
    wgmma_wait<1>();
    release(c, 4);
    SETUP;
    mbar_wait(c.sb + OFF_FULL + 48, par);
  } else finish(c, t, layer ? 1 : 7);
  MMA(1, 4); MMA(1, 5);
  bar_sync(BAR_EPI + c.wg, 256);
  MMA(1, 6);
  mbar_wait(c.sb + OFF_TBL + 8 * SKEW, 0);
  MMA(1, 7);
  if (SKEW) mbar_wait(c.sb + OFF_FULL + 56, par);
  MMA(1, 8);
  bar_sync(BAR_FREE, 160);
  MMA(1, 9);
  if (!SKEW) SETUP;
  float4 cs = lds128f(csb + 4 * 64);
  if (SKEW) {
    MMA(1, 10); MMA(1, 11);
    wgmma_commit();
    MMA(0, 0);
    wgmma_commit();
    MMA(0, 1);
    wgmma_commit();
    wgmma_wait<2>();
  }
#define CONV(i, np) do { _Pragma("unroll") for (int z = 0; z < 4; z++) { const int nt = 2 * (np) + (z >> 1), h = z & 1; \
    const float m = mu[2 * h + (i)]; \
    P[nt >> 3][(nt >> 2) & 1][2 * h + (i)][nt & 3] = pack_bf16(fmaf(z >> 1 ? cs.z : cs.x, m, acc[i][4 * nt + 2 * h]), \
                                                                     fmaf(z >> 1 ? cs.w : cs.y, m, acc[i][4 * nt + 2 * h + 1])); } } while (0)
#define HM(u) P[1 + (((u) >> 4) & 1)][((u) >> 3) & 1][((u) & 2) + 1][(((u) >> 1) & 2) + ((u) & 1)]
#define HW(u) ((u) == 2 ? rs_l : HM((u) - ((u) > 2)))
#pragma unroll
  for (int n = 0; n < 12; n++) {
    const int np = (n + 4) % 12;
    if (SKEW && n == HGK && w == 0) bar_arrive(BAR_HGO, 64);
    if (SKEW && n == HGO && w == 0) bar_arrive(BAR_HGO + 1, 64);
    if (SKEW && n == 8) bar_arrive(BAR_START + (c.wg ^ 1), 256);
    if (SKEW && n < 10) { MMA(0, n + 2); wgmma_commit(); }
    CONV(1, np);
    cs = lds128f(csb + (n < 11 ? (n + 5) % 12 : 0) * 64);
#pragma unroll
    for (int z = 0; z < 11; z++)
      if ((3 * z + 1) / 4 == n) {
        st_tag128_if(send, halo + z * 32, HW(3 * z), HW(3 * z + 1), HW(3 * z + 2), tag);
        put_halo(stg + 4096 + lane * 16 + (z ? z * 384 - 128 : 0), z == 10, HW(3 * z), HW(3 * z + 1), HW(3 * z + 2), tag);
      }
    if (SKEW && n < 10) wgmma_wait<2>();
    if (SKEW && (n == 3 || n == 7)) release(c, 5 + (n >> 2));
  }
#undef MMA
#undef HW
#undef SETUP
#undef HM
  if (SKEW) {
    wgmma_wait<0>();
    release(c, 7, w ? 2 : 0);
    TL(t, 3);
  }
#pragma unroll
  for (int np = 0; np < 12; np++) {
    CONV(0, np);
    if (!SKEW && np == HG1 && w == 0) { bar_arrive(BAR_HGO, 64); bar_arrive(BAR_HGO + 1, 64); }
    if (np < 11) cs = lds128f(csb + (np + 1) * 64);
  }
#undef CONV
}

__device__ __forceinline__ void epi_qkv(const Ctx& c, float (&acc)[2][96], int t, int q) {
  const int lane = c.lane, w = c.w, g = lane >> 2, cc = lane & 3;
  uint32_t P[3][2][4][4];
  if (q) conv_qkv<1>(c, acc, P, t); else conv_qkv<0>(c, acc, P, t);
  const uint32_t rst = c.sb + OFF_RST + w * 256, stg = c.sb + OFF_STG + w * 4096;
  const bool nohalo = w == 0 && smem_block(c) < 8;
#pragma unroll
  for (int z = 0; z < 16; z++) P[2][z >> 3][(z >> 1) & 2][z & 3] = movmatrix(P[2][z >> 3][(z >> 1) & 2][z & 3]);
  uint32_t K1[4][4], V1[4][4];
  const uint32_t hl = stg + (lane & 15) * 16 + (lane >> 4) * 512;
#define HZ(z) (((z) >> 1) * 1024 + ((z) & 1) * 256)
  __syncwarp();
#pragma unroll
  for (int z = 0; z < 4; z++) { ldmatrix4(hl + 4096 + HZ(z), K1[z]); ldmatrix4_t(hl + 4096 + 2048 + HZ(z), V1[z]); }
  TL(t, 9);
  bar_sync(BAR_WG + c.wg, 128);
  if (w == 0) { TL(t, 8); mbar_wait(c.sb + OFF_HALO, q); release(c, 7, 2 * q); }
  uint32_t HK[4][4], HV[4][4];
#pragma unroll
  for (int z = 0; z < 4; z++) ldmatrix4(hl + HZ(z), HK[z]);
  const bool far0 = 2 * cc > g, far1 = 2 * cc + 1 > g;
  float rk[4][2], sc[4][2];
#pragma unroll
  for (int r = 0; r < 4; r++) {
    const float rq = __uint_as_float(lds32(rst + (8 * r + g) * 8)) * (0.17677669529663687f * 1.4426950408889634f);
    const int back = r & 1 ? 64 : 192;
    rk[r][0] = __uint_as_float(lds32(rst + r * 64 + cc * 16 - (far0 ? back : 0)));
    rk[r][1] = __uint_as_float(lds32(rst + r * 64 + cc * 16 + 8 - (far1 ? back : 0)));
    sc[r][0] = rq * rk[r][0]; sc[r][1] = rq * rk[r][1];
  }
  TL(t, 4);
  float S[4][3][4];
  if (q == 0) bar_sync(BAR_P0, 256);
  float4 zero = lds128f(c.sb + OFF_ZERO);
#pragma unroll
  for (int k = 0; k < 2; k++)
#pragma unroll
    for (int z = 0; z < 4; z++) {
      const uint32_t* qa = P[0][z >> 1][2 * (z & 1)]; const uint32_t* qb = P[0][z >> 1][2 * (z & 1) + 1];
      const uint32_t* kk[3] = {HK[z], P[1][z >> 1][2 * (z & 1)], K1[z]};
#pragma unroll
      for (int n = 0; n < 3; n++) {
        if (k == 0) mma16816_z(S[z][n], qa[0], qb[0], qa[1], qb[1], kk[n][0], kk[n][1], zero);
        else mma16816(S[z][n], qa[2], qb[2], qa[3], qb[3], kk[n][2], kk[n][3]);
        if (q == 0 && k * 12 + z * 3 + n + 1 == NS) bar_arrive_here(BAR_P1, S[0][0][0], zero.x);
      }
    }
  TL(t, 10);
  const uint32_t fmask = (far0 ? 0xffffu : 0u) | (far1 ? 0xffff0000u : 0u);
  uint32_t pf[4][2], pn[4][2];
#pragma unroll
  for (int z = 0; z < 4; z++)
#pragma unroll
    for (int i = 0; i < 2; i++) {
      const int r = 2 * (z & 1) + i;
      float l0 = (far0 ? S[z][i][2 * i] : S[z][i + 1][2 * i]) * sc[r][0];
      float l1 = (far1 ? S[z][i][2 * i + 1] : S[z][i + 1][2 * i + 1]) * sc[r][1];
      if (i == 0 && nohalo) { const float neg = -1e9f * 1.4426950408889634f; if (far0) l0 = neg; if (far1) l1 = neg; }
      float mx = fmaxf(l0, l1);
      mx = fmaxf(mx, __shfl_xor_sync(0xffffffffu, mx, 1));
      mx = fmaxf(mx, __shfl_xor_sync(0xffffffffu, mx, 2));
      l0 = ex2(l0 - mx); l1 = ex2(l1 - mx);
      float sum = l0 + l1;
      l0 *= rk[r][0]; l1 *= rk[r][1];
      sum += __shfl_xor_sync(0xffffffffu, sum, 1);
      sum += __shfl_xor_sync(0xffffffffu, sum, 2);
      sum = rcp(sum);
      const uint32_t u = pack_bf16(l0 * sum, l1 * sum);
      pf[z][i] = u & fmask; pn[z][i] = u & ~fmask;
    }
  float O[4][2][2][4];
  TL(t, 11);
  if (w == 0) { mbar_wait(c.sb + OFF_HALO + 8, q); TL(t, 12); }
#pragma unroll
  for (int z = 0; z < 4; z++) ldmatrix4_t(hl + 2048 + HZ(z), HV[z]);
#undef HZ
  if (q == 0) bar_sync_after(BAR_P0, (pn[0][0] | pn[0][1] | pn[1][0]) | (pn[1][1] | pn[2][0] | pn[2][1]) | (pn[3][0] | pn[3][1]));
  zero = lds128f(c.sb + OFF_ZERO);
#pragma unroll
  for (int z = 0; z < 4; z++)
#pragma unroll
    for (int d = 0; d < 2; d++) {
      const uint32_t* v0 = P[2][z >> 1][2 * (z & 1)] + 2 * d;
      mma16816_z(O[z][0][d], HV[z][2 * d], HV[z][2 * d + 1], v0[0], v0[1], pf[z][0], pn[z][0], zero);
      mma16816_z(O[z][1][d], v0[0], v0[1], V1[z][2 * d], V1[z][2 * d + 1], pf[z][1], pn[z][1], zero);
      if (z * 4 + d * 2 + 2 == NP) bar_arrive_here(BAR_P1, O[0][0][0][0], zero.x);
    }
  TL(t, 5);
#pragma unroll
  for (int nt = 0; nt < 8; nt++) {
    uint32_t u[4];
#pragma unroll
    for (int r = 0; r < 4; r++) { const float* o = O[2 * (nt >> 2) + (r >> 1)][r & 1][(nt >> 1) & 1] + 2 * (nt & 1); u[r] = pack_bf16(o[0], o[1]); }
    stmatrix4_t(stg + lane * 128 + ((nt ^ (lane & 7)) << 4), u[0], u[1], u[2], u[3]);
  }
  bar_arrive(BAR_READY, 160);
  TL(t, 13);
}

template<int CH>
__device__ __forceinline__ void epi_up(const Ctx& c, float (&acc)[2][96], int type) {
  const int lane = c.lane, w = c.w, g = lane >> 2, cc = lane & 3;
  float rs[4], nm[4];
#pragma unroll
  for (int r = 0; r < 4; r++) { const float2 v = lds64f(c.sb + OFF_RST + (w * 32 + 8 * r + g) * 8); rs[r] = v.x; nm[r] = v.x * v.y; }
  const int loc0 = type == 3 ? 0 : (type == 4 ? 192 : 320);
  const uint32_t cb = c.sb + OFF_UP + loc0 * 8 + cc * 16;
  const uint32_t zero = lds32(c.sb + OFF_ZERO);
  uint32_t d[2] = {0u, 0u};
  const uint32_t stg = c.sb + OFF_STG + w * 4096;
#pragma unroll
  for (int ch = CH; ch < (CH ? 3 : 2); ch++) {
    uint32_t P[8][4];
#pragma unroll
    for (int n8 = 0; n8 < 8; n8++) {
      const int nt = ch * 8 + n8;
      const float4 cv = lds128f(cb + nt * 64);
#pragma unroll
      for (int r = 0; r < 4; r++) {
        const float m = after(nm[r], d[r & 1], zero);
        d[r & 1] = P[n8][r] = relu_sq_bf16(fmaf(acc[r & 1][4 * nt + 2 * (r >> 1)], rs[r], fmaf(cv.x, m, cv.z)),
                                           fmaf(acc[r & 1][4 * nt + 2 * (r >> 1) + 1], rs[r], fmaf(cv.y, m, cv.w)));
      }
    }
    bar_sync(BAR_FREE, 160);
#pragma unroll
    for (int n8 = 0; n8 < 8; n8++)
      stmatrix4(stg + lane * 128 + ((n8 ^ (lane & 7)) << 4), P[n8][0], P[n8][1], P[n8][2], P[n8][3]);
    bar_arrive(BAR_READY, 160);
  }
}

__device__ __forceinline__ void init_res(const Ctx& c, float (&acc)[2][96], int t, bool bias) {
  if (t == 2) mbar_wait(c.sb + OFF_XBAR, 0);
  uint32_t xb = res_addr(c);
  const uint32_t zero = lds32(c.sb + OFF_ZERO);
  float b[4];
#pragma unroll
  for (int r = 0; r < 4; r++) b[r] = bias ? __uint_as_float(lds32(c.sb + OFF_B2 + (r >> 1) * 256 + c.w * 64 + (r & 1) * 32 + (c.lane >> 2) * 4)) : 0.f;
#pragma unroll
  for (int z = 0; z < 16; z++) {
    uint32_t u[4];
    asm volatile("{\n.reg .pred p;\nSTAY:\nldmatrix.sync.aligned.m8n8.x4.trans.shared.b16 {%0, %1, %2, %3}, [%4];\nsetp.lt.u32 p, %0, %5;\n@p bra.uni STAY;\n}"
      : "=r"(u[0]), "=r"(u[1]), "=r"(u[2]), "=r"(u[3]) : "r"(xb + z * 2048), "r"(zero) : "memory");
#pragma unroll
    for (int r = 0; r < 4; r++) {
      float* a = acc[z >> 3] + (z & 7) * 8 + 2 * r;
      a[0] = bf_lo(u[r]) + b[(z >> 3) * 2 + (r & 1)];
      a[1] = bf_hi(u[r]) + b[(z >> 3) * 2 + (r & 1)];
      asm volatile("" : "+f"(a[0]), "+f"(a[1]));
    }
  }
}

__device__ __forceinline__ void load_table(const Ctx& c, const Params& p, int part, unsigned tag) {
  const int i0 = (part < 4 ? part * 192 : 704) + c.lane, n = part < 3 ? 6 : 4;
  const uint2* src = g_cs + c.j * NCS + i0;
  const uint32_t dst = c.sb + OFF_CSQ + (i0 & 1) * 4 + (part < 2 ? (i0 >> 4) * 64 + (i0 & 6) * 8 + (i0 & 8) : 1536 + ((i0 - 384) >> 1) * 16);
  const __nv_bfloat16* bias = p.b1 + (part == 2 ? c.j * 192 : (part == 3 ? 1536 : 2560) + c.j * 128) + c.lane;
  float v[6];
  if (part >= 2) {
#pragma unroll
    for (int k = 0; k < 6; k++) if (k < n) sts32f(dst + k * 256 + 8, __bfloat162float(bias[k * 32]));
  }
  for (unsigned it = 0;; it++) {
    bool ok = true;
#pragma unroll
    for (int k = 0; k < 6; k++) { const uint2 a = ld_tag64(src + (k < n ? k * 32 : 0)); ok = ok && a.y == tag; v[k] = __uint_as_float(a.x); }
    if (__all_sync(0xffffffffu, ok) || it > SPIN_LIMIT) break;
    __nanosleep(200);
  }
#pragma unroll
  for (int k = 0; k < 6; k++) if (k < n) sts32f(dst + k * (part < 2 ? 128 : 256), v[k]);
  __syncwarp();
}

__device__ __forceinline__ void colsum_cta(const Ctx& c, const Params& p, unsigned* epoch) {
  if (c.wg < 2) mbar_init_e(c.sb + OFF_FULL + 32 * c.wg + 8 * c.w, 1);
  sts32f(c.sb + OFF_STG + threadIdx.x * 4, __uint_as_float(0x3f803f80u));
  fence_async_smem();
  __syncthreads();
  if (c.wg == 2) return;
  const unsigned tag = *(volatile unsigned*)epoch + 1;
  const int j = (blockIdx.x - 128) * 2 + c.wg;
  const uint32_t ring = c.sb + c.wg * 98304, full = c.sb + OFF_FULL + 32 * c.wg;
  const uint64_t ones = (uint64_t)(((c.sb + OFF_STG) & 0x3ffffu) >> 4) | (8u << 16) | ((uint64_t)16u << 32);
  float d[3][4];
#pragma unroll 1
  for (int n = -4; n < 80; n++) {
    if (n >= 0) {
      mbar_wait(full + 8 * (n & 3), (n >> 2) & 1);
      const uint64_t da = (uint64_t)(((ring + (n & 3) * 24576) & 0x3ffffu) >> 4) | (64u << 16) | ((uint64_t)(64u | (1u << 30)) << 32);
      wgmma_fence();
#pragma unroll
      for (int k = 0; k < 4; k++)
#pragma unroll
        for (int z = 0; z < 3; z++)
          asm volatile("{\n.reg .pred p;\nsetp.ne.b32 p, %6, 0;\nwgmma.mma_async.sync.aligned.m64n8k16.f32.bf16.bf16 {%0,%1,%2,%3}, %4, %5, p, 1, 1, 1, 0;\n}"
            : "+f"(d[z][0]), "+f"(d[z][1]), "+f"(d[z][2]), "+f"(d[z][3]) : "l"(da + z * 512 + k * 128), "l"(ones), "r"((n & 15) | k));
      wgmma_commit();
      wgmma_wait<0>();
      bar_sync(BAR_WG + c.wg, 128);
      if ((n & 15) == 15 && (c.lane & 3) < 2) {
        const int u = n >> 4;
        uint2* out = g_cs + j * NCS + (u < 4 ? u * 192 : 704) + c.w * 16 + (c.lane >> 2) + (c.lane & 1) * 8;
#pragma unroll
        for (int z = 0; z < 3; z++) if (z < 2 || u < 3) st_tag64(out + z * 64, (c.lane & 1) ? d[z][2] : d[z][0], tag);
      }
      __syncwarp();
    }
    if (c.w == 0 && n < 76) {
      const int u = (n + 4) >> 4;
      const WTile w = wtile(u + (u >= 2), j);
      mbar_expect_e(full + 8 * (n & 3), u < 3 ? 24576 : 16384);
      tma_ld3_e(ring + (n & 3) * 24576, (const CUtensorMap*)((const char*)&p + w.map), full + 8 * (n & 3), w.c0, ((n + 4) & 15) * 64, w.c2);
    }
  }
  bar_sync(BAR_START, 256);
  if (threadIdx.x == 0) *epoch = tag;
}

__device__ __forceinline__ void place(Ctx& c, uint32_t slot) {
  const int row = slot < 32 ? slot >> 3 : slot < 60 ? ((slot - 4) * 37) >> 8 : slot - 56;
  const int gpc = slot < 60 ? slot - row * (slot < 32 ? 8 : 7) - (slot < 32 ? 0 : 3) : 0;
  c.m = (gpc & 1) * 8 + row;
  c.j = (gpc & 6) + c.rank; c.b = c.m * 8 + c.j;
}

__global__ void __cluster_dims__(2, 1, 1) __launch_bounds__(384, 1) fused_kernel(unsigned* const epochs, const char* const x0, const char* const w0, const __grid_constant__ Params p) {
  extern __shared__ uint8_t smem_raw[];
  const int tid = threadIdx.x;
  Ctx c;
  c.sb = (smem_u32(smem_raw) + 1023) & ~1023u;
  const int k = __shfl_sync(0xffffffffu, tid >> 5, 0);
  c.wg = k >> 2; c.w = k & 3; c.lane = tid & 31;
  c.rank = blockIdx.x & 1;
  if (blockIdx.x >= 128) { colsum_cta(c, p, epochs + blockIdx.x); return; }
  uint32_t slot; asm volatile("mov.u32 %0, %%smid;" : "=r"(slot));
  slot = __shfl_sync(0xffffffffu, slot < 120 ? slot >> 1 : 60 + ((slot >> 1) & 3), 0);
  if (c.wg == 2) {
    const bool claim = tid == 320 && c.rank == 0;
    unsigned epoch, old;
    asm volatile("{\n.reg .pred p;\nsetp.ne.u32 p, %4, 0;\nmov.u32 %0, 0;\nmov.u32 %1, 0;\n@p atom.relaxed.gpu.global.add.u32 %0, [%2], 1;\n@p ld.relaxed.gpu.global.u32 %1, [%3];\n}"
      : "=r"(old), "=r"(epoch) : "l"(epochs + 132 + slot + c.lane), "l"(epochs + blockIdx.x), "r"((uint32_t)claim) : "memory");
    reg_dealloc<40>();
#pragma unroll 1
    for (int pass = 0;; pass++) {
      place(c, slot);
      if (c.w == 1) {
        asm volatile(ELECT "@p mbarrier.init.shared::cta.b64 [%0], 2;\n@p mbarrier.init.shared::cta.b64 [%0 + 8], 2;\n"
          "@p mbarrier.init.shared::cta.b64 [%0 + 16], 2;\n@p mbarrier.init.shared::cta.b64 [%0 + 24], 2;\n}" :: "r"(c.sb + OFF_FULL) : "memory");
        fence_async_smem();
        if (!pass) asm volatile("fence.mbarrier_init.release.cluster;\nbarrier.cluster.arrive.relaxed.aligned;" ::: "memory");
#pragma unroll 1
        for (int s = pass ? 0 : 2; s < 4; s++) {
          const uint32_t full = c.sb + OFF_FULL + 8 * s, dst = c.sb + (s ^ 2) * 40960;
          mbar_expect_e(full, 40960);
          tma_ld4_e(dst, &p.ld_x, full, s * 64, c.m * 4);
          tma_ld4_e(dst + 8192, &p.ld_x, full, s * 64, c.m * 4 + 2);
          tma_ld3_e(dst + A_BYTES, &p.w_qkv, full, c.j * 64, s * 64, 0);
          mbar_arrive_e(full);
        }
      } else if (!pass) {
        if (c.w == 2) { mbar_init_e(c.sb + OFF_SLOT, 1); mbar_expect_e(c.sb + OFF_SLOT, 8); }
        asm volatile("fence.mbarrier_init.release.cluster;\nbarrier.cluster.arrive.relaxed.aligned;" ::: "memory");
      }
      if (c.w == 0) {
        asm volatile("cp.async.wait_all;" ::: "memory");
#pragma unroll
        for (int i = 0; i < PLAN_BYTES; i += 512)
          asm volatile("cp.async.cg.shared.global [%0], [%1], 16;" :: "r"(c.sb + OFF_PLAN + c.lane * 16 + i), "l"(epochs + 256 + c.j * (PLAN_BYTES / 4) + c.lane * 4 + i / 4) : "memory");
      }
      if (c.w == 3) sts32f(c.sb + OFF_TAG + 8, __int_as_float(c.b));
      if (pass) { bar_sync(BAR_START, 256); break; }
      asm volatile("barrier.cluster.wait.aligned;" ::: "memory");
      if (claim) {
        uint32_t s = slot;
        for (int it = 0; old != epoch && it < 64; it++) { atomicSub(epochs + 132 + s, 1u); s = (s + 1) & 63; old = atomicAdd(epochs + 132 + s, 1u); }
#pragma unroll
        for (int r = 0; r < 2; r++)
          asm volatile("{\n.reg .u32 t;\nadd.u32 t, %1, 1;\nst.async.weak.shared::cluster.mbarrier::complete_tx::bytes.v2.b32 [%0], {t, %2}, [%3];\n}"
            :: "r"(mapa(c.sb + OFF_TAG, r)), "r"(old), "r"(s), "r"(mapa(c.sb + OFF_SLOT, r)) : "memory");
      }
      __syncwarp();
      mbar_wait(c.sb + OFF_SLOT, 0);
      const uint32_t got = __shfl_sync(0xffffffffu, lds32(c.sb + OFF_TAG + 4), 0);
      if (got == slot) {
        bar_arrive(BAR_START, 256);
#pragma unroll 1
        for (int s = 0; s < 16 && c.w == 3; s += 8) {
          mbar_wait(c.sb + OFF_PRE + s, 0);
          PTL(12, 12 + s / 8);
          fence_async_smem();
          if (c.lane < 2) asm volatile("mbarrier.arrive.shared::cta.b64 _, [%0];" :: "r"(c.sb + OFF_FULL + s) : "memory");
        }
        break;
      }
      slot = got;
      if (c.w == 1)
#pragma unroll 1
        for (int s = 0; s < 4; s++) { mbar_wait(c.sb + (s < 2 ? OFF_PRE : OFF_FULL) + 8 * s, 0); asm volatile(ELECT "@p mbarrier.inval.shared::cta.b64 [%0];\n}" :: "r"(c.sb + OFF_FULL + 8 * s) : "memory"); }
    }
    const unsigned tag = smem_tag(c);
    if (c.w < 2) { asm volatile("cp.async.wait_all;" ::: "memory"); bar_sync(BAR_COPY, 64); PTL(14, 13); }
    if (c.w == 0) {
      const char* fp = (const char*)(g_flags + c.m * 32 + c.lane);
      unsigned ready = 1u << 31;
      float2 nx = lds64f(c.sb + OFF_PLAN);
#pragma unroll 1
      for (int g = 4; g < 2 * KB_LAYER; g++) {
        const uint32_t x = __float_as_uint(nx.x), y = __float_as_uint(nx.y);
        nx = lds64f(c.sb + OFF_PLAN + g * 16 - 48);
        if (y & A_NEW) ready = 1u << 31;
        for (unsigned it = 0; !((ready >> (x >> 27)) & 1) && it < SPIN_LIMIT; it++) {
          unsigned v; asm volatile("ld.relaxed.gpu.global.u32 %0, [%1];" : "=r"(v) : "l"(fp + (y >> 16)) : "memory");
          ready |= __ballot_sync(0xffffffffu, v == tag);
          asm volatile("fence.proxy.async.global;" ::: "memory");
        }
        mbar_wait(c.sb + OFF_EMPTY + (x & 0x38), x & 1);
        const uint32_t full = c.sb + OFF_FULL + 8 * (g & 7), dst = c.sb + (x & 0x3e000);
        const CUtensorMap* mp = (const CUtensorMap*)((const char*)&p + (y & 0x180));
        if (!(y & A_QUIET)) mbar_expect_e(full, y & 0x4004);
        if (!(y & A_COPY)) tma_ld4_mc_e(dst, mp, full, x & 0xfc0, c.m * 4 + c.rank * 2);
        else if (!(y & A_NONE)) { tma_ld4_e(dst, mp, full, x & 0xfc0, c.m * 4); tma_ld4_e(dst + 8192, mp, full, x & 0xfc0, c.m * 4 + 2); }
        else if (y & A_PAIR) {
          const uint32_t peer = mapa(c.sb, c.rank ^ 1);
          mbar_wait(c.sb + OFF_FULL, g < KB_LAYER);
          dsmem_copy_e(peer + 3 * 32768, c.sb + OFF_STG, peer + OFF_FULL + 8);
        }
      }
    } else if (c.w == 1) {
      float2 nx = lds64f(c.sb + OFF_PLAN + 8);
#pragma unroll 1
      for (int g = 4; g < 2 * KB_LAYER; g++) {
        const uint32_t x = __float_as_uint(nx.x), y = __float_as_uint(nx.y);
        nx = lds64f(c.sb + OFF_PLAN + g * 16 - 40);
        mbar_wait(c.sb + OFF_EMPTY + (x & 0x38), x & 1);
        const uint32_t full = c.sb + OFF_FULL + 8 * (g & 7);
        mbar_expect_e(full, y & 0x6000);
        tma_ld3_e(c.sb + (x & 0x3e000), (const CUtensorMap*)((const char*)&p + (y >> 16)), full, y & 0x3c0, x & 0xfc0, x >> 26);
      }
    } else if (c.w == 2) {
      mbar_pace(c.sb + OFF_EMPTY + 56, 0);
#pragma unroll 1
      for (int z = 0; z < 44; z++) st_tag128(g_halo + ((z & 3) * 128 + c.b) * 352 + (z >> 2) * 32 + c.lane, 0u, 0u, 0u, 0u);
      bar_arrive(BAR_FREE, 160);
#pragma unroll 1
      for (int t = 0; t < 14; t++) {
        const int layer = t >= 7, type = t - layer * 7;
        const int slab = c.m * 4;
        unsigned* flag = g_flags + c.m * 32 + c.j;
        if (type == 2 || type == 6) {
          flag += (t + 1) * 512 + c.j;
          bar_sync(BAR_RES, 160);
          fence_async_smem();
          asm volatile(ELECT "@p mbarrier.complete_tx.relaxed.cta.shared::cta.b64 [%0], 4;\n}" :: "r"(c.sb + OFF_FULL) : "memory");
          tma_st4_e(&p.st_out, c.sb + OFF_X, c.j * 128, slab);
          if (t < 13) {
            bulk_wait_read_e();
            PTL(t, 8);
            publish_e(flag++, tag);
            PTL(t, 9);
            mbar_wait(c.sb + OFF_FULL + 8, t != 2);
            mbar_wait(c.sb + OFF_EMPTY + 56, t == 2);
#pragma unroll
            for (int h = 0; h < 2; h++) tma_ld4_mc_e(c.sb + 3 * 40960 + h * 8192, &p.ld_out, c.sb + OFF_FULL + 40, c.j * 128, slab + 2 * h, 2 - c.rank);
          }
          if (t == 13) bar_sync(BAR_RES2, 160);
          tma_st4_e(&p.ld_out, c.sb + OFF_X + A_BYTES, c.j * 128 + 64, slab);
          if (t < 13) mbar_pace(c.sb + OFF_FULL + 48, t != 2);
          tma_st4_e(&p.ld_out, c.sb + OFF_X + A_BYTES + 8192, c.j * 128 + 64, slab + 2);
          bulk_wait_read_e();
          PTL(t, 11);
        } else {
          flag += (layer * 7 + (type < 2 ? 2 : 6)) * 512 + (type < 2 ? type : type - 3) * 8;
          const int col = type < 2 ? (c.j + 8 * type) * 64 : type == 3 ? c.j * 192 : (type == 4 ? 1536 : 2560) + c.j * 128;
#pragma unroll 1
          for (int ch = type == 3 ? -1 : 0; ch < (type < 2 ? 1 : 2); ch++) {
            if (type < 2) fetch_halo(c, tag, layer * 2 + type);
            bar_sync(BAR_READY, 160);
            fence_async_smem();
#pragma unroll 1
            for (int z = 0; z < 4; z++) {
              if (z && type != 1) bulk_wait_read_e();
              tma_st4_e(&p.st_h, c.sb + OFF_STG + z * 4096, col + (ch < 0 ? 128 : ch * 64), slab + z);
            }
            if (type == 1) { mbar_wait(c.sb + OFF_FULL, layer); mbar_arrive_e(c.sb + OFF_FULL); }
            bulk_wait_read_e();
            if (t < 12 || ch == 0) bar_arrive(BAR_FREE, 160);
          }
          PTL(t, 14);
        }
        if (t < 13) publish_e(flag, tag);
        PTL(t, 6);
      }
      if (c.lane == 0) epochs[blockIdx.x] = tag;
    } else {
      mbar_pace(c.sb + OFF_EMPTY + 8 * (c.m & 3), 0);
      PTL(14, 14);
      mbar_expect_e(c.sb + OFF_XBAR, 32768);
#pragma unroll
      for (int i = 0; i < 4; i++) tma_ld4_e(c.sb + OFF_X + i * 8192, &p.ld_x, c.sb + OFF_XBAR, c.j * 128 + (i >> 1) * 64, c.m * 4 + (i & 1) * 2);
#pragma unroll
      for (int i = 0; i < 4; i++) sts32f(c.sb + OFF_B2 + i * 128 + c.lane * 4, __bfloat162float(p.b2[c.j * 128 + i * 32 + c.lane]));
#pragma unroll 1
      for (int part = 0; part < 7; part++) {
        if (part < 5) {
          load_table(c, p, part, tag);
          mbar_arrive_e(c.sb + OFF_TBL + 8 * part);
          PTL(part, 7);
        }
        if (part < 2 || part > 4) fetch_halo(c, tag, part < 2 ? part : part - 3);
        if ((0x52 >> part) & 1) {
          const uint32_t peer = mapa(c.sb, c.rank ^ 1);
          bar_sync(BAR_RES2, 160);
          mbar_wait(c.sb + OFF_EMPTY + 56, part == 1);
          dsmem_copy_e(peer + 2 * 40960, c.sb + OFF_X + A_BYTES, peer + OFF_FULL + 32);
        }
      }
    }
  } else {
    place(c, slot);
    const int r = tid >> 3;
    const uint32_t dst = c.sb + 2 * 40960 + r * 128 + ((tid ^ r) & 7) * 16;
    const char* ga = x0 + (c.m * 128 + (r & 15) * 2 + c.wg) * 2048 + (tid & 7) * 16;
    const char* gb = w0 + r * 6144 + c.j * 128 + (tid & 7) * 16;
#pragma unroll
    for (int s = 0; s < 2; s++) {
#pragma unroll
      for (int i = 0; i < 10; i++)
        asm volatile("cp.async.cg.shared.global [%0], [%1], 16;" :: "r"(dst + s * 40960 + i * 4096),
          "l"(i < 4 ? ga + i * 65536 + s * 128 : gb + (2 * s + (i & 1)) * (32 * 6144) + (i / 2 - 2) * 2048) : "memory");
      if (!s) {
        mbar_init_e(c.sb + OFF_EMPTY + 8 * k, 8);
        mbar_init_e(c.sb + (k < 4 ? OFF_XBAR : OFF_FULL) + 8 * k, k < 4 ? 1 : 2);
        if (k < 7) mbar_init_e(c.sb + OFF_XBAR + 32 + 8 * k, k > 4 ? 256 : 1);
        else sts128(c.sb + OFF_ZERO, 0u, 0u, 0u, 0u);
        asm volatile("fence.mbarrier_init.release.cluster;\nbarrier.cluster.arrive.relaxed.aligned;" ::: "memory");
        bar_sync(BAR_EPI, 256);
      }
      asm volatile("cp.async.mbarrier.arrive.noinc.shared::cta.b64 [%0];" :: "r"(c.sb + OFF_PRE + 8 * s) : "memory");
    }
    asm volatile("barrier.cluster.wait.aligned;" ::: "memory");
    reg_alloc<232>();
    if (c.wg) { mbar_wait(c.sb + OFF_XBAR, 0); TL(-1, 4); row_stats<8>(c, 1); }
#pragma unroll 1
    for (int t = c.wg; t < 14; t += 2) {
      const int layer = t >= 7, type = t - layer * 7;
      const int g0 = layer * KB_LAYER + type * 16;
      float acc[2][96];
      if (type == 2 || type == 6) {
        init_res(c, acc, t, type == 6);
        mainloop<128, 1>(c, acc, t, type, g0, (type == 6 ? 56 : 16) - SK);
        if (t == 13) asm volatile("barrier.cluster.arrive.relaxed.aligned;" ::: "memory");
        TL(t, 4);
        continue;
      }
      if (type < 4) {
        mainloop<192, 0>(c, acc, t, type, g0, type == 1 ? 13 : 16);
        if (type < 2) { epi_qkv(c, acc, t, type); goto done; }
        finish(c, t, 1);
        bar_sync(BAR_EPI + c.wg, 256);
        mbar_wait(c.sb + OFF_TBL + 16, 0);
        epi_up<2>(c, acc, type);
      } else {
        mainloop<128, 0>(c, acc, t, type, g0, 16);
        finish(c, t, 7);
        bar_sync(BAR_EPI + c.wg, 256);
        mbar_wait(c.sb + OFF_TBL + 8 * (type - 1), 0);
      }
      epi_up<0>(c, acc, type);
      TL(t, 4);
    done:
      if (type != 1 && type != 5) bar_arrive(BAR_EPI + (c.wg ^ 1), 256);
    }
    if (c.wg == 1) {
      asm volatile("barrier.cluster.wait.aligned;" ::: "memory");
    }
  }
}

typedef CUresult (*EncodeFn)(CUtensorMap*, CUtensorMapDataType, cuuint32_t, void*, const cuuint64_t*, const cuuint64_t*,
                             const cuuint32_t*, const cuuint32_t*, CUtensorMapInterleave, CUtensorMapSwizzle,
                             CUtensorMapL2promotion, CUtensorMapFloatOOBfill);

void make_map(EncodeFn fn, CUtensorMap* m, const void* ptr, int rank, const cuuint64_t* dims, const cuuint64_t* strides, const cuuint32_t* box) {
  const cuuint32_t es[4] = {1, 1, 1, 1};
  fn(m, CU_TENSOR_MAP_DATA_TYPE_BFLOAT16, rank, const_cast<void*>(ptr), dims, strides, box, es, CU_TENSOR_MAP_INTERLEAVE_NONE,
     CU_TENSOR_MAP_SWIZZLE_128B, CU_TENSOR_MAP_L2_PROMOTION_L2_128B, CU_TENSOR_MAP_FLOAT_OOB_FILL_NONE);
}
void map_rows(EncodeFn fn, CUtensorMap* m, const void* ptr, int cols, int rows, int box_slabs, bool tokens) {
  const cuuint64_t rb = (cuuint64_t)cols * 2;
  const cuuint64_t dims[4] = {(cuuint64_t)cols, 16, 2, (cuuint64_t)(rows / 32)};
  const cuuint64_t st[3] = {tokens ? 2 * rb : rb, tokens ? rb : 16 * rb, 32 * rb};
  const cuuint32_t box[4] = {64, 16, 2, (cuuint32_t)box_slabs};
  make_map(fn, m, ptr, 4, dims, st, box);
}
void map_w(EncodeFn fn, CUtensorMap* m, const void* ptr, int K, int N, int inner, int nch) {
  const cuuint64_t dims[3] = {(cuuint64_t)inner, (cuuint64_t)K, (cuuint64_t)(N / inner)}, st[2] = {(cuuint64_t)N * 2, (cuuint64_t)inner * 2};
  const cuuint32_t box[3] = {64, 64, (cuuint32_t)nch};
  make_map(fn, m, ptr, 3, dims, st, box);
}

}

extern "C" void kernel_launch(void* const* d_in, const int* in_sizes, int n_in, void* d_out, int out_size) {
  (void)in_sizes; (void)n_in; (void)out_size;
  Params p;
  p.b1 = (const __nv_bfloat16*)d_in[5]; p.b2 = (const __nv_bfloat16*)d_in[7];
  void* fnp = nullptr; cudaDriverEntryPointQueryResult qr;
  cudaGetDriverEntryPoint("cuTensorMapEncodeTiled", &fnp, cudaEnableDefault, &qr);
  EncodeFn fn = (EncodeFn)fnp;
  void *h, *epochs;
  cudaGetSymbolAddress(&h, g_h);
  cudaGetSymbolAddress(&epochs, g_plan);
  map_rows(fn, &p.ld_x, d_in[0], D_, S_, 2, true);
  map_rows(fn, &p.ld_out, d_out, D_, S_, 2, true);
  map_rows(fn, &p.ld_h, h, F_, S_, 2, false);
  map_rows(fn, &p.st_h, h, F_, S_, 1, false);
  map_rows(fn, &p.st_out, d_out, D_, S_, 4, true);
  map_w(fn, &p.w_qkv, d_in[1], D_, 3 * D_, D_, 3);
  map_w(fn, &p.w_o, d_in[2], D_, D_, 64, 2);
  map_w(fn, &p.w_1a, d_in[4], D_, F_, 64, 3);
  map_w(fn, &p.w_1b, d_in[4], D_, F_, 64, 2);
  map_w(fn, &p.w_2, d_in[6], F_, D_, 64, 2);
  cudaFuncSetAttribute(fused_kernel, cudaFuncAttributeMaxDynamicSharedMemorySize, SMEM_BYTES);
  fused_kernel<<<132, 384, SMEM_BYTES>>>((unsigned*)epochs, (const char*)d_in[0], (const char*)d_in[1], p);
}
```

```cpp
#include <cuda_runtime.h>
#include <cuda_bf16.h>
#include <cuda.h>
#include <stdint.h>

#define EXP 0
namespace {

constexpr int S_ = 2048, D_ = 1024, F_ = 3584;
constexpr int A_BYTES = 16384;
constexpr int OFF_X   = 163840;
constexpr int OFF_STG = OFF_X + 32768;
constexpr int OFF_CSQ = OFF_STG + 20480;
constexpr int OFF_UP  = OFF_CSQ + 1536;
constexpr int OFF_B2  = OFF_UP + 3584;
constexpr int OFF_RST = OFF_B2 + 512 + 256;
constexpr int OFF_FULL = OFF_RST + 1024;
constexpr int OFF_EMPTY = OFF_FULL + 64;
constexpr int OFF_XBAR = OFF_EMPTY + 64;
constexpr int OFF_TBL = OFF_XBAR + 8;
constexpr int OFF_HALO = OFF_XBAR + 48;
constexpr int OFF_SLOT = OFF_XBAR + 88;
constexpr int OFF_IDLE = OFF_XBAR + 64;
constexpr int OFF_PRE = OFF_XBAR + 72;
constexpr int OFF_ZERO = OFF_XBAR + 96;
constexpr int OFF_TAG = OFF_ZERO + 16;
constexpr int OFF_PLAN = OFF_TAG + 16, PLAN_BYTES = 5120;
constexpr int SMEM_BYTES = OFF_PLAN + PLAN_BYTES + 48 + 1024;
constexpr int KB_LAYER = 6 * 16 + 56;
constexpr int NCS = 384 + 448;
constexpr unsigned SPIN_LIMIT = 1u << 20;
constexpr int NS = 12, NP = 8, SA = 7, SB = 11, PAUSE1 = 7, PAUSE2 = 8, HGK = 8, HGO = 11, HG1 = 3;
constexpr int SK = 3;
constexpr uint32_t DESC_A = 1u << 16, DESC_B = (512u << 16) + A_BYTES / 16;
enum { BAR_START = 1, BAR_EPI = 3, BAR_WG = 5, BAR_P0 = 7, BAR_P1 = 8, BAR_RES = 9, BAR_READY = 10, BAR_FREE = 11, BAR_COPY = 12, BAR_RES2 = 13, BAR_HGO = 14 };

struct Params {
  CUtensorMap ld_x, ld_out, ld_h, st_h, st_out, w_qkv, w_o, w_1a, w_1b, w_2;
  const __nv_bfloat16 *b1, *b2;
};

__device__ __align__(1024) __nv_bfloat16 g_h[S_ * F_];
__device__ __align__(128) uint4 g_stats[4 * S_ * 8];
__device__ __align__(128) uint2 g_cs[8 * NCS];
__device__ __align__(128) uint4 g_halo[4 * 128 * 11 * 32];
__device__ __align__(128) unsigned g_flags[14 * 16 * 32];
#define TL(t, e)
#define PTL(t, e)
#if !defined(TIMELINE) || !(EXP & 8)
#undef TK
#define TK(t, k)
#endif

template<int N, int KEEP> __device__ __forceinline__ void wgmma_ss(float (&d)[96], uint32_t da, uint32_t db);
template<> __device__ __forceinline__ void wgmma_ss<128, 0>(float (&d)[96], uint32_t da, uint32_t db) {
  asm volatile("{\n.reg .pred p;\n.reg .b64 a, b;\nsetp.ne.b32 p, 0, 0;\nmov.b64 a, {%64, 0x40000080};\nmov.b64 b, {%65, 0x40000040};\nwgmma.mma_async.sync.aligned.m64n128k16.f32.bf16.bf16 {%0, %1, %2, %3, %4, %5, %6, %7, %8, %9, %10, %11, %12, %13, %14, %15, %16, %17, %18, %19, %20, %21, %22, %23, %24, %25, %26, %27, %28, %29, %30, %31, %32, %33, %34, %35, %36, %37, %38, %39, %40, %41, %42, %43, %44, %45, %46, %47, %48, %49, %50, %51, %52, %53, %54, %55, %56, %57, %58, %59, %60, %61, %62, %63}, a, b, p, 1, 1, 0, 1;\n}"
    : "=f"(d[0]), "=f"(d[1]), "=f"(d[2]), "=f"(d[3]), "=f"(d[4]), "=f"(d[5]), "=f"(d[6]), "=f"(d[7]), "=f"(d[8]), "=f"(d[9]), "=f"(d[10]), "=f"(d[11]), "=f"(d[12]), "=f"(d[13]), "=f"(d[14]), "=f"(d[15]), "=f"(d[16]), "=f"(d[17]), "=f"(d[18]), "=f"(d[19]), "=f"(d[20]), "=f"(d[21]), "=f"(d[22]), "=f"(d[23]), "=f"(d[24]), "=f"(d[25]), "=f"(d[26]), "=f"(d[27]), "=f"(d[28]), "=f"(d[29]), "=f"(d[30]), "=f"(d[31]), "=f"(d[32]), "=f"(d[33]), "=f"(d[34]), "=f"(d[35]), "=f"(d[36]), "=f"(d[37]), "=f"(d[38]), "=f"(d[39]), "=f"(d[40]), "=f"(d[41]), "=f"(d[42]), "=f"(d[43]), "=f"(d[44]), "=f"(d[45]), "=f"(d[46]), "=f"(d[47]), "=f"(d[48]), "=f"(d[49]), "=f"(d[50]), "=f"(d[51]), "=f"(d[52]), "=f"(d[53]), "=f"(d[54]), "=f"(d[55]), "=f"(d[56]), "=f"(d[57]), "=f"(d[58]), "=f"(d[59]), "=f"(d[60]), "=f"(d[61]), "=f"(d[62]), "=f"(d[63])
    : "r"(da), "r"(db));
}
template<> __device__ __forceinline__ void wgmma_ss<128, 1>(float (&d)[96], uint32_t da, uint32_t db) {
  asm volatile("{\n.reg .pred p;\n.reg .b64 a, b;\nsetp.ne.b32 p, 1, 0;\nmov.b64 a, {%64, 0x40000080};\nmov.b64 b, {%65, 0x40000040};\nwgmma.mma_async.sync.aligned.m64n128k16.f32.bf16.bf16 {%0, %1, %2, %3, %4, %5, %6, %7, %8, %9, %10, %11, %12, %13, %14, %15, %16, %17, %18, %19, %20, %21, %22, %23, %24, %25, %26, %27, %28, %29, %30, %31, %32, %33, %34, %35, %36, %37, %38, %39, %40, %41, %42, %43, %44, %45, %46, %47, %48, %49, %50, %51, %52, %53, %54, %55, %56, %57, %58, %59, %60, %61, %62, %63}, a, b, p, 1, 1, 0, 1;\n}"
    : "+f"(d[0]), "+f"(d[1]), "+f"(d[2]), "+f"(d[3]), "+f"(d[4]), "+f"(d[5]), "+f"(d[6]), "+f"(d[7]), "+f"(d[8]), "+f"(d[9]), "+f"(d[10]), "+f"(d[11]), "+f"(d[12]), "+f"(d[13]), "+f"(d[14]), "+f"(d[15]), "+f"(d[16]), "+f"(d[17]), "+f"(d[18]), "+f"(d[19]), "+f"(d[20]), "+f"(d[21]), "+f"(d[22]), "+f"(d[23]), "+f"(d[24]), "+f"(d[25]), "+f"(d[26]), "+f"(d[27]), "+f"(d[28]), "+f"(d[29]), "+f"(d[30]), "+f"(d[31]), "+f"(d[32]), "+f"(d[33]), "+f"(d[34]), "+f"(d[35]), "+f"(d[36]), "+f"(d[37]), "+f"(d[38]), "+f"(d[39]), "+f"(d[40]), "+f"(d[41]), "+f"(d[42]), "+f"(d[43]), "+f"(d[44]), "+f"(d[45]), "+f"(d[46]), "+f"(d[47]), "+f"(d[48]), "+f"(d[49]), "+f"(d[50]), "+f"(d[51]), "+f"(d[52]), "+f"(d[53]), "+f"(d[54]), "+f"(d[55]), "+f"(d[56]), "+f"(d[57]), "+f"(d[58]), "+f"(d[59]), "+f"(d[60]), "+f"(d[61]), "+f"(d[62]), "+f"(d[63])
    : "r"(da), "r"(db));
}
template<> __device__ __forceinline__ void wgmma_ss<192, 0>(float (&d)[96], uint32_t da, uint32_t db) {
  asm volatile("{\n.reg .pred p;\n.reg .b64 a, b;\nsetp.ne.b32 p, 0, 0;\nmov.b64 a, {%96, 0x40000080};\nmov.b64 b, {%97, 0x40000040};\nwgmma.mma_async.sync.aligned.m64n192k16.f32.bf16.bf16 {%0, %1, %2, %3, %4, %5, %6, %7, %8, %9, %10, %11, %12, %13, %14, %15, %16, %17, %18, %19, %20, %21, %22, %23, %24, %25, %26, %27, %28, %29, %30, %31, %32, %33, %34, %35, %36, %37, %38, %39, %40, %41, %42, %43, %44, %45, %46, %47, %48, %49, %50, %51, %52, %53, %54, %55, %56, %57, %58, %59, %60, %61, %62, %63, %64, %65, %66, %67, %68, %69, %70, %71, %72, %73, %74, %75, %76, %77, %78, %79, %80, %81, %82, %83, %84, %85, %86, %87, %88, %89, %90, %91, %92, %93, %94, %95}, a, b, p, 1, 1, 0, 1;\n}"
    : "=f"(d[0]), "=f"(d[1]), "=f"(d[2]), "=f"(d[3]), "=f"(d[4]), "=f"(d[5]), "=f"(d[6]), "=f"(d[7]), "=f"(d[8]), "=f"(d[9]), "=f"(d[10]), "=f"(d[11]), "=f"(d[12]), "=f"(d[13]), "=f"(d[14]), "=f"(d[15]), "=f"(d[16]), "=f"(d[17]), "=f"(d[18]), "=f"(d[19]), "=f"(d[20]), "=f"(d[21]), "=f"(d[22]), "=f"(d[23]), "=f"(d[24]), "=f"(d[25]), "=f"(d[26]), "=f"(d[27]), "=f"(d[28]), "=f"(d[29]), "=f"(d[30]), "=f"(d[31]), "=f"(d[32]), "=f"(d[33]), "=f"(d[34]), "=f"(d[35]), "=f"(d[36]), "=f"(d[37]), "=f"(d[38]), "=f"(d[39]), "=f"(d[40]), "=f"(d[41]), "=f"(d[42]), "=f"(d[43]), "=f"(d[44]), "=f"(d[45]), "=f"(d[46]), "=f"(d[47]), "=f"(d[48]), "=f"(d[49]), "=f"(d[50]), "=f"(d[51]), "=f"(d[52]), "=f"(d[53]), "=f"(d[54]), "=f"(d[55]), "=f"(d[56]), "=f"(d[57]), "=f"(d[58]), "=f"(d[59]), "=f"(d[60]), "=f"(d[61]), "=f"(d[62]), "=f"(d[63]), "=f"(d[64]), "=f"(d[65]), "=f"(d[66]), "=f"(d[67]), "=f"(d[68]), "=f"(d[69]), "=f"(d[70]), "=f"(d[71]), "=f"(d[72]), "=f"(d[73]), "=f"(d[74]), "=f"(d[75]), "=f"(d[76]), "=f"(d[77]), "=f"(d[78]), "=f"(d[79]), "=f"(d[80]), "=f"(d[81]), "=f"(d[82]), "=f"(d[83]), "=f"(d[84]), "=f"(d[85]), "=f"(d[86]), "=f"(d[87]), "=f"(d[88]), "=f"(d[89]), "=f"(d[90]), "=f"(d[91]), "=f"(d[92]), "=f"(d[93]), "=f"(d[94]), "=f"(d[95])
    : "r"(da), "r"(db));
}
template<> __device__ __forceinline__ void wgmma_ss<192, 1>(float (&d)[96], uint32_t da, uint32_t db) {
  asm volatile("{\n.reg .pred p;\n.reg .b64 a, b;\nsetp.ne.b32 p, 1, 0;\nmov.b64 a, {%96, 0x40000080};\nmov.b64 b, {%97, 0x40000040};\nwgmma.mma_async.sync.aligned.m64n192k16.f32.bf16.bf16 {%0, %1, %2, %3, %4, %5, %6, %7, %8, %9, %10, %11, %12, %13, %14, %15, %16, %17, %18, %19, %20, %21, %22, %23, %24, %25, %26, %27, %28, %29, %30, %31, %32, %33, %34, %35, %36, %37, %38, %39, %40, %41, %42, %43, %44, %45, %46, %47, %48, %49, %50, %51, %52, %53, %54, %55, %56, %57, %58, %59, %60, %61, %62, %63, %64, %65, %66, %67, %68, %69, %70, %71, %72, %73, %74, %75, %76, %77, %78, %79, %80, %81, %82, %83, %84, %85, %86, %87, %88, %89, %90, %91, %92, %93, %94, %95}, a, b, p, 1, 1, 0, 1;\n}"
    : "+f"(d[0]), "+f"(d[1]), "+f"(d[2]), "+f"(d[3]), "+f"(d[4]), "+f"(d[5]), "+f"(d[6]), "+f"(d[7]), "+f"(d[8]), "+f"(d[9]), "+f"(d[10]), "+f"(d[11]), "+f"(d[12]), "+f"(d[13]), "+f"(d[14]), "+f"(d[15]), "+f"(d[16]), "+f"(d[17]), "+f"(d[18]), "+f"(d[19]), "+f"(d[20]), "+f"(d[21]), "+f"(d[22]), "+f"(d[23]), "+f"(d[24]), "+f"(d[25]), "+f"(d[26]), "+f"(d[27]), "+f"(d[28]), "+f"(d[29]), "+f"(d[30]), "+f"(d[31]), "+f"(d[32]), "+f"(d[33]), "+f"(d[34]), "+f"(d[35]), "+f"(d[36]), "+f"(d[37]), "+f"(d[38]), "+f"(d[39]), "+f"(d[40]), "+f"(d[41]), "+f"(d[42]), "+f"(d[43]), "+f"(d[44]), "+f"(d[45]), "+f"(d[46]), "+f"(d[47]), "+f"(d[48]), "+f"(d[49]), "+f"(d[50]), "+f"(d[51]), "+f"(d[52]), "+f"(d[53]), "+f"(d[54]), "+f"(d[55]), "+f"(d[56]), "+f"(d[57]), "+f"(d[58]), "+f"(d[59]), "+f"(d[60]), "+f"(d[61]), "+f"(d[62]), "+f"(d[63]), "+f"(d[64]), "+f"(d[65]), "+f"(d[66]), "+f"(d[67]), "+f"(d[68]), "+f"(d[69]), "+f"(d[70]), "+f"(d[71]), "+f"(d[72]), "+f"(d[73]), "+f"(d[74]), "+f"(d[75]), "+f"(d[76]), "+f"(d[77]), "+f"(d[78]), "+f"(d[79]), "+f"(d[80]), "+f"(d[81]), "+f"(d[82]), "+f"(d[83]), "+f"(d[84]), "+f"(d[85]), "+f"(d[86]), "+f"(d[87]), "+f"(d[88]), "+f"(d[89]), "+f"(d[90]), "+f"(d[91]), "+f"(d[92]), "+f"(d[93]), "+f"(d[94]), "+f"(d[95])
    : "r"(da), "r"(db));
}
template<> __device__ __forceinline__ void wgmma_ss<128, 2>(float (&d)[96], uint32_t da, uint32_t db) {
  asm volatile("{\n.reg .pred p;\n.reg .b64 a, b;\nsetp.ne.b32 p, 2, 0;\nmov.b64 a, {%64, 0x40000040};\nmov.b64 b, {%65, 0x40000040};\nwgmma.mma_async.sync.aligned.m64n128k16.f32.bf16.bf16 {%0, %1, %2, %3, %4, %5, %6, %7, %8, %9, %10, %11, %12, %13, %14, %15, %16, %17, %18, %19, %20, %21, %22, %23, %24, %25, %26, %27, %28, %29, %30, %31, %32, %33, %34, %35, %36, %37, %38, %39, %40, %41, %42, %43, %44, %45, %46, %47, %48, %49, %50, %51, %52, %53, %54, %55, %56, %57, %58, %59, %60, %61, %62, %63}, b, a, p, 1, 1, 1, 0;\n}"
    : "+f"(d[0]), "+f"(d[1]), "+f"(d[2]), "+f"(d[3]), "+f"(d[4]), "+f"(d[5]), "+f"(d[6]), "+f"(d[7]), "+f"(d[8]), "+f"(d[9]), "+f"(d[10]), "+f"(d[11]), "+f"(d[12]), "+f"(d[13]), "+f"(d[14]), "+f"(d[15]), "+f"(d[16]), "+f"(d[17]), "+f"(d[18]), "+f"(d[19]), "+f"(d[20]), "+f"(d[21]), "+f"(d[22]), "+f"(d[23]), "+f"(d[24]), "+f"(d[25]), "+f"(d[26]), "+f"(d[27]), "+f"(d[28]), "+f"(d[29]), "+f"(d[30]), "+f"(d[31]), "+f"(d[32]), "+f"(d[33]), "+f"(d[34]), "+f"(d[35]), "+f"(d[36]), "+f"(d[37]), "+f"(d[38]), "+f"(d[39]), "+f"(d[40]), "+f"(d[41]), "+f"(d[42]), "+f"(d[43]), "+f"(d[44]), "+f"(d[45]), "+f"(d[46]), "+f"(d[47]), "+f"(d[48]), "+f"(d[49]), "+f"(d[50]), "+f"(d[51]), "+f"(d[52]), "+f"(d[53]), "+f"(d[54]), "+f"(d[55]), "+f"(d[56]), "+f"(d[57]), "+f"(d[58]), "+f"(d[59]), "+f"(d[60]), "+f"(d[61]), "+f"(d[62]), "+f"(d[63])
    : "r"(da), "r"(db));
}

__device__ __forceinline__ uint32_t smem_u32(const void* p) { return (uint32_t)__cvta_generic_to_shared(p); }
__device__ __forceinline__ void mbar_arrive_cluster(uint32_t bar) { asm volatile("mbarrier.arrive.shared::cluster.b64 _, [%0];" :: "r"(bar) : "memory"); }
__device__ __forceinline__ void mbar_wait(uint32_t bar, uint32_t parity) {
  asm volatile(
    "{\n.reg .pred p;\n.reg .u32 n;\n"
    "mbarrier.try_wait.parity.shared::cta.b64 p, [%0], %1;\n"
    "@p bra.uni WAIT_DONE;\n"
    "mov.u32 n, 0;\n"
    "WAIT_LOOP:\n"
    "mbarrier.try_wait.parity.shared::cta.b64 p, [%0], %1;\n"
    "@p bra.uni WAIT_DONE;\n"
    "add.u32 n, n, 1;\n"
    "setp.lt.u32 p, n, 0x100000;\n"
    "@p bra.uni WAIT_LOOP;\n"
    "trap;\n"
    "WAIT_DONE:\n}" :: "r"(bar), "r"(parity) : "memory");
}
__device__ __forceinline__ void mbar_pace(uint32_t bar, uint32_t parity) {
  asm volatile(
    "{\n.reg .pred p;\n.reg .u32 n;\nmov.u32 n, 0;\n"
    "PACE_LOOP:\n"
    "mbarrier.try_wait.parity.shared::cta.b64 p, [%0], %1, 1000;\n"
    "add.u32 n, n, 1;\n"
    "setp.lt.and.u32 p, n, 16, !p;\n"
    "@p bra.uni PACE_LOOP;\n}" :: "r"(bar), "r"(parity) : "memory");
}
__device__ __forceinline__ uint32_t mbar_test(uint32_t bar, uint32_t parity) {
  uint32_t ok;
  asm volatile("{\n.reg .pred p;\nmbarrier.test_wait.parity.shared::cta.b64 p, [%1], %2;\nselp.u32 %0, 1, 0, p;\n}" : "=r"(ok) : "r"(bar), "r"(parity) : "memory");
  return ok;
}
#define ELECT "{\n.reg .pred p;\nelect.sync _|p, 0xffffffff;\n"
__device__ __forceinline__ void mbar_init_e(uint32_t bar, uint32_t cnt) { asm volatile(ELECT "@p mbarrier.init.shared::cta.b64 [%0], %1;\n}" :: "r"(bar), "r"(cnt) : "memory"); }
__device__ __forceinline__ void mbar_arrive_e(uint32_t bar) { asm volatile(ELECT "@p mbarrier.arrive.shared::cta.b64 _, [%0];\n}" :: "r"(bar) : "memory"); }
__device__ __forceinline__ void mbar_expect_e(uint32_t bar, uint32_t bytes) { asm volatile(ELECT "@p mbarrier.arrive.expect_tx.shared::cta.b64 _, [%0], %1;\n}" :: "r"(bar), "r"(bytes) : "memory"); }
__device__ __forceinline__ void tma_ld4_e(uint32_t dst, const CUtensorMap* m, uint32_t bar, int c0, int c3) {
  asm volatile(ELECT "@p cp.async.bulk.tensor.4d.shared::cluster.global.mbarrier::complete_tx::bytes [%0], [%1, {%3, %5, %5, %4}], [%2];\n}"
    :: "r"(dst), "l"(m), "r"(bar), "r"(c0), "r"(c3), "r"(0) : "memory");
}
__device__ __forceinline__ void tma_ld4_mc_e(uint32_t dst, const CUtensorMap* m, uint32_t bar, int c0, int c3, uint16_t mask = 3) {
  asm volatile(ELECT "@p cp.async.bulk.tensor.4d.shared::cluster.global.mbarrier::complete_tx::bytes.multicast::cluster [%0], [%1, {%3, %5, %5, %4}], [%2], %6;\n}"
    :: "r"(dst), "l"(m), "r"(bar), "r"(c0), "r"(c3), "r"(0), "h"(mask) : "memory");
}
__device__ __forceinline__ void tma_ld3_e(uint32_t dst, const CUtensorMap* m, uint32_t bar, int c0, int c1, int c2) {
  asm volatile(ELECT "@p cp.async.bulk.tensor.3d.shared::cluster.global.mbarrier::complete_tx::bytes [%0], [%1, {%3, %4, %5}], [%2];\n}"
    :: "r"(dst), "l"(m), "r"(bar), "r"(c0), "r"(c1), "r"(c2) : "memory");
}
__device__ __forceinline__ void tma_st4_e(const CUtensorMap* m, uint32_t src, int c0, int c3) {
  asm volatile(ELECT "@p cp.async.bulk.tensor.4d.global.shared::cta.bulk_group [%0, {%2, %4, %4, %3}], [%1];\n}"
    :: "l"(m), "r"(src), "r"(c0), "r"(c3), "r"(0) : "memory");
}
__device__ __forceinline__ void dsmem_copy_e(uint32_t dst, uint32_t src, uint32_t bar) {
  asm volatile(ELECT "@p cp.async.bulk.shared::cluster.shared::cta.mbarrier::complete_tx::bytes [%0], [%1], 16384, [%2];\n}"
    :: "r"(dst), "r"(src), "r"(bar) : "memory");
}
__device__ __forceinline__ void bulk_wait_read_e() { asm volatile(ELECT "@p cp.async.bulk.commit_group;\n@p cp.async.bulk.wait_group.read 0;\n}" ::: "memory"); __syncwarp(); }
__device__ __forceinline__ void publish_e(unsigned* flag, unsigned tag) {
  asm volatile(ELECT "@p fence.proxy.async;\n@p st.relaxed.gpu.global.u32 [%0], %1;\n}" :: "l"(flag), "r"(tag) : "memory");
  __syncwarp();
}
__device__ __forceinline__ void fence_async_smem() { asm volatile("fence.proxy.async.shared::cta;" ::: "memory"); }
__device__ __forceinline__ void wgmma_fence() { asm volatile("wgmma.fence.sync.aligned;" ::: "memory"); }
__device__ __forceinline__ void wgmma_commit() { asm volatile("wgmma.commit_group.sync.aligned;" ::: "memory"); }
template<int N> __device__ __forceinline__ void wgmma_wait() { asm volatile("wgmma.wait_group.sync.aligned %0;" :: "n"(N) : "memory"); }
__device__ __forceinline__ void bar_sync(int id, int n) { asm volatile("bar.sync %0, %1;" :: "r"(id), "r"(n) : "memory"); }
__device__ __forceinline__ void bar_arrive(int id, int n) { asm volatile("bar.arrive %0, %1;" :: "r"(id), "r"(n) : "memory"); }
__device__ __forceinline__ void bar_arrive_here(int id, float dep, float zero) {
  asm volatile("{\n.reg .pred p;\n.reg .u32 n;\nsetp.ne.u32 p, %2, 0;\nor.b32 n, %1, 256;\nmin.u32 n, n, 256;\nAGAIN:\nbar.arrive %0, n;\n@p bra.uni AGAIN;\n}"
    :: "r"(id), "r"(__float_as_uint(dep)), "r"(__float_as_uint(zero)) : "memory");
}
__device__ __forceinline__ void bar_sync_after(int id, uint32_t dep) {
  asm volatile("{\n.reg .u32 n;\nor.b32 n, %1, 256;\nmin.u32 n, n, 256;\nbar.sync %0, n;\n}" :: "r"(id), "r"(dep) : "memory");
}
__device__ __forceinline__ uint32_t mapa(uint32_t a, uint32_t r) { uint32_t d; asm("mapa.shared::cluster.u32 %0, %1, %2;" : "=r"(d) : "r"(a), "r"(r)); return d; }
__device__ __forceinline__ void st_tag128(uint4* p, uint32_t a, uint32_t b, uint32_t c, uint32_t tag) {
  asm volatile("{\n.reg .b64 lo, hi;\n.reg .b128 v;\nmov.b64 lo, {%1, %2};\nmov.b64 hi, {%3, %4};\nmov.b128 v, {lo, hi};\nst.relaxed.gpu.global.b128 [%0], v;\n}"
    :: "l"(p), "r"(a), "r"(b), "r"(c), "r"(tag) : "memory");
}
__device__ __forceinline__ void st_tag128_if(bool on, uint4* p, uint32_t a, uint32_t b, uint32_t c, uint32_t tag) {
  asm volatile("{\n.reg .pred q;\n.reg .b64 lo, hi;\n.reg .b128 v;\nsetp.ne.u32 q, %5, 0;\nmov.b64 lo, {%1, %2};\nmov.b64 hi, {%3, %4};\nmov.b128 v, {lo, hi};\n@q st.relaxed.gpu.global.b128 [%0], v;\n}"
    :: "l"(p), "r"(a), "r"(b), "r"(c), "r"(tag), "r"((uint32_t)on) : "memory");
}
__device__ __forceinline__ uint4 ld_tag128(const uint4* p) {
  uint4 v;
  asm volatile("{\n.reg .b64 lo, hi;\n.reg .b128 v;\nld.relaxed.gpu.global.b128 v, [%4];\nmov.b128 {lo, hi}, v;\nmov.b64 {%0, %1}, lo;\nmov.b64 {%2, %3}, hi;\n}"
    : "=r"(v.x), "=r"(v.y), "=r"(v.z), "=r"(v.w) : "l"(p) : "memory");
  return v;
}
__device__ __forceinline__ void st_tag64(uint2* p, float a, uint32_t tag) {
  asm volatile("{\n.reg .b64 v;\nmov.b64 v, {%1, %2};\nst.relaxed.gpu.global.b64 [%0], v;\n}" :: "l"(p), "r"(__float_as_uint(a)), "r"(tag) : "memory");
}
__device__ __forceinline__ uint2 ld_tag64(const uint2* p) {
  uint2 v;
  asm volatile("{\n.reg .b64 v;\nld.relaxed.gpu.global.b64 v, [%2];\nmov.b64 {%0, %1}, v;\n}" : "=r"(v.x), "=r"(v.y) : "l"(p) : "memory");
  return v;
}
__device__ __forceinline__ uint32_t pack_bf16(float lo, float hi) { uint32_t r; asm("cvt.rn.bf16x2.f32 %0, %1, %2;" : "=r"(r) : "f"(hi), "f"(lo)); return r; }
__device__ __forceinline__ uint32_t relu_sq_bf16(float lo, float hi) {
  uint32_t r; asm("{\n.reg .b32 t;\ncvt.rn.relu.bf16x2.f32 t, %1, %2;\nmul.rn.bf16x2 %0, t, t;\n}" : "=r"(r) : "f"(hi), "f"(lo)); return r;
}
__device__ __forceinline__ float bf_lo(uint32_t u) { return __uint_as_float(u << 16); }
__device__ __forceinline__ float bf_hi(uint32_t u) { return __uint_as_float(u & 0xffff0000u); }
__device__ __forceinline__ void stmatrix4(uint32_t addr, uint32_t r0, uint32_t r1, uint32_t r2, uint32_t r3) {
  asm volatile("stmatrix.sync.aligned.m8n8.x4.shared.b16 [%0], {%1, %2, %3, %4};" :: "r"(addr), "r"(r0), "r"(r1), "r"(r2), "r"(r3) : "memory");
}
__device__ __forceinline__ void ldmatrix4(uint32_t addr, uint32_t (&r)[4]) {
  asm volatile("ldmatrix.sync.aligned.m8n8.x4.shared.b16 {%0, %1, %2, %3}, [%4];" : "=r"(r[0]), "=r"(r[1]), "=r"(r[2]), "=r"(r[3]) : "r"(addr) : "memory");
}
__device__ __forceinline__ void stmatrix4_t(uint32_t addr, uint32_t r0, uint32_t r1, uint32_t r2, uint32_t r3) {
  asm volatile("stmatrix.sync.aligned.m8n8.x4.trans.shared.b16 [%0], {%1, %2, %3, %4};" :: "r"(addr), "r"(r0), "r"(r1), "r"(r2), "r"(r3) : "memory");
}
__device__ __forceinline__ void ldmatrix4_t(uint32_t addr, uint32_t (&r)[4]) {
  asm volatile("ldmatrix.sync.aligned.m8n8.x4.trans.shared.b16 {%0, %1, %2, %3}, [%4];" : "=r"(r[0]), "=r"(r[1]), "=r"(r[2]), "=r"(r[3]) : "r"(addr) : "memory");
}
__device__ __forceinline__ uint32_t movmatrix(uint32_t a) { uint32_t d; asm volatile("movmatrix.sync.aligned.m8n8.trans.b16 %0, %1;" : "=r"(d) : "r"(a)); return d; }
__device__ __forceinline__ void mma16816_z(float (&c)[4], uint32_t a0, uint32_t a1, uint32_t a2, uint32_t a3, uint32_t b0, uint32_t b1, const float4& z) {
  asm volatile("mma.sync.aligned.m16n8k16.row.col.f32.bf16.bf16.f32 {%0,%1,%2,%3}, {%4,%5,%6,%7}, {%8,%9}, {%10,%11,%12,%13};"
    : "=f"(c[0]), "=f"(c[1]), "=f"(c[2]), "=f"(c[3]) : "r"(a0), "r"(a1), "r"(a2), "r"(a3), "r"(b0), "r"(b1), "f"(z.x), "f"(z.y), "f"(z.z), "f"(z.w));
}
__device__ __forceinline__ float ex2(float x) { float y; asm("ex2.approx.ftz.f32 %0, %1;" : "=f"(y) : "f"(x)); return y; }
__device__ __forceinline__ float rcp(float x) { float y; asm("rcp.approx.ftz.f32 %0, %1;" : "=f"(y) : "f"(x)); return y; }
__device__ __forceinline__ void mma16816(float (&c)[4], uint32_t a0, uint32_t a1, uint32_t a2, uint32_t a3, uint32_t b0, uint32_t b1) {
  asm volatile("mma.sync.aligned.m16n8k16.row.col.f32.bf16.bf16.f32 {%0,%1,%2,%3}, {%4,%5,%6,%7}, {%8,%9}, {%0,%1,%2,%3};"
    : "+f"(c[0]), "+f"(c[1]), "+f"(c[2]), "+f"(c[3]) : "r"(a0), "r"(a1), "r"(a2), "r"(a3), "r"(b0), "r"(b1));
}
__device__ __forceinline__ void sts128(uint32_t a, uint32_t x, uint32_t y, uint32_t z, uint32_t w) { asm volatile("st.shared.v4.b32 [%0], {%1,%2,%3,%4};" :: "r"(a), "r"(x), "r"(y), "r"(z), "r"(w) : "memory"); }
__device__ __forceinline__ float2 lds64f(uint32_t a) { float2 v; asm volatile("ld.shared.v2.f32 {%0,%1}, [%2];" : "=f"(v.x), "=f"(v.y) : "r"(a) : "memory"); return v; }
__device__ __forceinline__ float4 lds128f(uint32_t a) { float4 v; asm volatile("ld.shared.v4.f32 {%0,%1,%2,%3}, [%4];" : "=f"(v.x), "=f"(v.y), "=f"(v.z), "=f"(v.w) : "r"(a) : "memory"); return v; }
__device__ __forceinline__ void sts32f(uint32_t a, float v) { asm volatile("st.shared.f32 [%0], %1;" :: "r"(a), "f"(v) : "memory"); }
__device__ __forceinline__ void sts64f(uint32_t a, float x, float y) { asm volatile("st.shared.v2.f32 [%0], {%1,%2};" :: "r"(a), "f"(x), "f"(y) : "memory"); }
__device__ __forceinline__ uint32_t lds32(uint32_t a) { uint32_t v; asm volatile("ld.shared.u32 %0, [%1];" : "=r"(v) : "r"(a) : "memory"); return v; }
__device__ __forceinline__ float after(float x, uint32_t d, uint32_t zero) { return __uint_as_float(__float_as_uint(x) | (d & zero)); }
template<int R> __device__ __forceinline__ void reg_alloc() { asm volatile("setmaxnreg.inc.sync.aligned.u32 %0;" :: "n"(R)); }
template<int R> __device__ __forceinline__ void reg_dealloc() { asm volatile("setmaxnreg.dec.sync.aligned.u32 %0;" :: "n"(R)); }

struct Ctx {
  uint32_t sb;
  int m, j, b, rank, wg, w, lane;
};

__device__ __forceinline__ unsigned smem_tag(const Ctx& c) { return lds32(c.sb + OFF_TAG); }
__device__ __forceinline__ int smem_block(const Ctx& c) { return lds32(c.sb + OFF_TAG + 8); }

struct WTile { int map, c0, c2; };
__host__ __device__ constexpr WTile wtile(int type, int j) {
  return WTile{128 * (type < 2 ? 5 : type < 5 ? type + 4 : type + 3), type < 2 ? (j + 8 * type) * 64 : 0,
               type < 2 ? 0 : type == 3 ? 3 * j : type == 4 ? 24 + 2 * j : type == 5 ? 40 + 2 * j : 2 * j};
}
__host__ __device__ constexpr int first_stage(int type, int part) { return ((part == 0 ? 0x2000422 : part == 1 ? 0x2 : 0x2002) >> (4 * type)) & 7; }

enum { A_NEW = 1 << 9, A_QUIET = 1 << 10, A_NONE = 1 << 11, A_PAIR = 2 << 11, A_COPY = 3 << 11 };
struct Plan {
  unsigned epoch[256];
  uint32_t v[8][PLAN_BYTES / 4];
};
constexpr Plan make_plan() {
  Plan plan{};
  for (int j = 0; j < 8; j++)
    for (int g = 4; g < 2 * KB_LAYER; g++) {
      const int layer = g >= KB_LAYER, r = g - layer * KB_LAYER;
      const bool split = (r >= 48 && r < 80) || (layer && r < 32);
      const int q = r - (r >= 48 ? 48 : 0);
      const bool head = split && q < 4, second = split && (head ? q >= 2 : q >= 18), lead = split && !second;
      const int type = split ? (r >= 48 ? 3 : 0) + second : r < 96 ? r >> 4 : 6, t = layer * 7 + type;
      const int step = !split ? r - 16 * type : head ? q & 1 : q - (second ? 16 : 2), n = step - (split && !head ? 2 : 0);
      const bool wide = type < 2 || type == 3;
      const int ns = wide || head ? 4 : 5, lag = type == 2 ? 3 : 4;
      const int e = g - (split && q && q < (r < 48 ? 4 : 6) ? 5 + (r >= 48 && q > 1) : n + 1 > ns ? ns : n + 1 > lag ? n + 1 : lag);
      const int v = (int)(0xfb7d95ea6c842310ull >> (4 * (step & 15))) & 15;
      const int kb = split ? (v < 4 ? (j * 2) ^ v : ((j >> 1) * 4 + v) & 15) : type != 2 || step < 8 ? step : step < 10 ? j ^ step : 8 + (((j & 6) + step) & 7);
      const uint32_t x = kb * 64 + (first_stage(type, head ? 1 : 2 * split) + n) % ns * (163840 / ns);
      const bool local = type == 2 && (step >> 1) == 4;
      const int act = split && step < 4 ? (head || lead ? A_NONE : A_PAIR) : local ? (step == 8 ? A_NONE : A_COPY) : 0;
      const uint32_t piece = type == 6 ? (step < 24 ? step / 3 : (step >> 1) - 4) : (type == 2 ? !local : lead ? step >= 4 : second && step == 2) ? kb : 31;
      const int ea = split && act == A_NONE ? g - 8 - (step == 3) : e;
      const WTile w = wtile(type, j);
      uint32_t* d = plan.v[j] + (g - 4) * 4;
      d[0] = x + ((ea >> 3) & 1) + (ea & 7) * 8 + (act ? 0 : (j & 1) * 8192) + (piece << 27);
      d[1] = (!head ? A_BYTES : lead ? 4 : 0) + (type == 2 || type == 6 ? 256 : t < 2 ? 0 : 128) + act + (n == 0 && !second ? A_NEW : 0) +
             (local && step == 8 ? A_QUIET : 0) + ((uint32_t)(t - second) << 27);
      d[2] = x + ((e >> 3) & 1) + (e & 7) * 8 + (!head || !type ? A_BYTES : wide ? 0 : 24576) + ((uint32_t)w.c2 << 26);
      d[3] = w.c0 + (wide ? 24576 : 16384) + (w.map << 16);
    }
  return plan;
}
__device__ __align__(128) Plan g_plan = make_plan();

template<int NL>
__device__ __forceinline__ void row_stats(const Ctx& c, int t) {
  const int ln = t / 3;
  const unsigned tag = smem_tag(c);
  const int row = c.w * 32 + c.lane + lds32(c.sb + OFF_ZERO);
  float s = 0.f, q = 0.f;
  const uint32_t xr = c.sb + OFF_X + row * 128 + (row & 7) * 16;
#pragma unroll 1
  for (int i = 0; i < 128; i += 16) {
    const float4 v = lds128f(xr ^ i), w = lds128f((xr ^ i) + A_BYTES);
    const float u[8] = {v.x, v.y, v.z, v.w, w.x, w.y, w.z, w.w};
#pragma unroll
    for (int z = 0; z < 16; z++) { const float x = z & 1 ? bf_hi(__float_as_uint(u[z >> 1])) : bf_lo(__float_as_uint(u[z >> 1])); s += x; q = fmaf(x, x, q); }
  }
  if (NL == 8) TL(-1, 6);
  if (NL == 4) mbar_pace(c.sb + OFF_FULL + 8 * SA, ln >> 1);
  const int b = smem_block(c);
  st_tag128(g_stats + (ln * 128 + b) * 128 + row, __float_as_uint(s), __float_as_uint(q), 0u, tag);
  mbar_pace(c.sb + (NL == 4 ? OFF_FULL + 8 * (SB & 7) : OFF_EMPTY + 16), (ln >> 1) ^ 1);
  const uint4* p = g_stats + (ln * 128 + (b & ~7)) * 128 + row;
  for (unsigned it = 0;; it++) {
    bool ok = true;
    s = 0.f; q = 0.f;
#pragma unroll 1
    for (int h = 0; h < 8; h += NL) {
      uint4 v[NL];
#pragma unroll
      for (int i = 0; i < NL; i++) v[i] = ld_tag128(p + (h + i) * 128);
#pragma unroll
      for (int i = 0; i < NL; i++) { ok = ok && v[i].w == tag; s += __uint_as_float(v[i].x); q += __uint_as_float(v[i].y); }
    }
    if (__all_sync(0xffffffffu, ok) || it > SPIN_LIMIT) break;
    __nanosleep(NL == 4 ? 400 : 100);
  }
  const float mean = s * (1.0f / D_);
  const float var = fmaxf(q * (1.0f / D_) - mean * mean, 0.0f);
  sts64f(c.sb + OFF_RST + row * 8, rsqrtf(var + 1e-5f), -mean);
  if ((EXP & 256) && NL == 8) sts32f(c.sb + OFF_TAG + 12, __int_as_float(row + 77));
  if ((EXP & 512) && NL == 4) sts32f(c.sb + OFF_TAG + 12, __int_as_float(row + 77));
  bar_arrive(BAR_EPI + (c.wg ^ 1), 256);
  TL(t - 2, 5);
}

__device__ __forceinline__ uint32_t res_addr(const Ctx& c) {
  return c.sb + OFF_X + ((c.lane >> 4) * 8 + (c.lane & 7)) * 128 + (((2 * c.w + ((c.lane >> 3) & 1)) ^ (c.lane & 7)) << 4);
}

template<int BN, int RES>
__device__ __forceinline__ void mainloop(const Ctx& c, float (&acc)[2][96], int t, int type, int g, int nkb) {
  constexpr int NS = BN == 192 ? 4 : 5, STR = BN == 192 ? 40960 : 32768;
  const bool split = !RES && (BN == 192 ? t > 1 : type == 4), second = BN == 128 || type == 1;
  int st = first_stage(type, split);
  if (split && second) g -= 14;
  const uint32_t rel = mapa(c.sb + OFF_EMPTY, c.lane & 1);
  const uint32_t sb = (c.sb & 0x3ffffu) >> 4;
  const uint32_t hb = BN == 192 && split && type ? 1024 : 0;
  uint32_t da = DESC_A + sb + (split ? OFF_X / 16 : st * (STR / 16)), db = DESC_B + sb + (BN == 128 && split ? 512 : st * (STR / 16) - hb);
  TL(t, 0);
  bar_sync(BAR_START + c.wg, 256);
  if (RES && type == 2) bar_sync(BAR_P1, 256);
  TL(t, 1);
  mbar_wait(c.sb + OFF_FULL + 8 * (g & 7), (g >> 3) & 1);
  TL(t, 2);
  wgmma_fence();
#define MMA(i, k, keep) wgmma_ss<BN, RES ? 2 : keep>(acc[i], da + (k) * 2 + (RES ? 0 : 64 * (i)), db + (k) * 128 + (RES ? 512 * (i) : 0))
  MMA(0, 0, 0); MMA(1, 0, 0); MMA(0, 1, 1); MMA(1, 1, 1);
  wgmma_commit();
  wgmma_fence();
  MMA(0, 2, 1); MMA(1, 2, 1); MMA(0, 3, 1); MMA(1, 3, 1);
  wgmma_commit();
  const int pause = BN == 192 && type == 1 ? (split ? PAUSE2 : PAUSE1) : nkb;
  int kb = 1, lim = split ? 2 : pause, pass = split ? 2 : !RES && type != 1 ? nkb : 0;
  const uint32_t other = BAR_START + (c.wg ^ 1);
  uint32_t prev = 8 * (g & 7);
  if (++st == NS) st = 0;
  g++;
  da = DESC_A + sb + (split ? (OFF_X + A_BYTES) / 16 : st * (STR / 16));
  db = DESC_B + sb + (BN == 128 && split ? 3072 : st * (STR / 16) - hb);
#pragma unroll 1
  for (;;) {
    mbar_wait(c.sb + OFF_FULL + 8 * (g & 7), (g >> 3) & 1);
    bool more;
#pragma unroll 1
    do {
      wgmma_fence();
      MMA(0, 0, 1); MMA(1, 0, 1); MMA(0, 1, 1); MMA(1, 1, 1);
      wgmma_commit();
      wgmma_wait<1>();
      if (c.lane < 2) mbar_arrive_cluster(rel + prev);
      TK(t, kb);
      prev = 8 * (g & 7);
      kb++; g++;
      if (++st == NS) st = 0;
      wgmma_fence();
      if (BN == 128 && !RES && kb == pass) bar_arrive(other, 256);
      MMA(0, 2, 1); MMA(1, 2, 1);
      if (BN == 192 && kb == pass) bar_arrive(other, 256);
      const uint32_t ok = mbar_test(c.sb + OFF_FULL + 8 * (g & 7), (g >> 3) & 1);
      MMA(0, 3, 1); MMA(1, 3, 1);
      wgmma_commit();
      more = ok && kb != lim;
      da = DESC_A + sb + (RES && type == 2 && kb == 8 ? OFF_STG / 16 : st * (STR / 16));
      db = DESC_B + sb + st * (STR / 16);
    } while (more);
    if (kb != lim) continue;
    if (RES || kb == nkb) break;
    if (BN == 128 || kb == 2) {
      wgmma_wait<0>();
      if (c.lane < 2) mbar_arrive_cluster(rel + prev);
      TK(t, 16);
      if (second) row_stats<4>(c, t);
      g += second ? 14 : 2;
      st = first_stage(type, 2);
      da = DESC_A + sb + st * (STR / 16); db = DESC_B + sb + st * (STR / 16);
      lim = pause; pass = type != 1 ? nkb : 0; prev = OFF_IDLE - OFF_EMPTY;
      bar_sync(BAR_START + c.wg, 256);
    } else {
      bar_sync(BAR_P0, 256); bar_sync(BAR_P1, 256);
      lim = kb == pause ? pause + 2 : nkb;
    }
  }
  if (!RES) return;
#define PAIR(i, n) wgmma_ss<128, 2>(acc[i], da + ((n) >> 2) * 2048 + ((n) & 3) * 2, db + ((n) >> 2) * 2048 + ((n) & 3) * 128 + 512 * (i))
#define PUT(z) do { const float* a = acc[(z) >> 3] + ((z) & 7) * 8; \
    stmatrix4_t(xw + (z) * 2048, pack_bf16(a[0], a[1]), pack_bf16(a[2], a[3]), pack_bf16(a[4], a[5]), pack_bf16(a[6], a[7])); } while (0)
  const uint32_t xw = res_addr(c);
#pragma unroll
  for (int n = 0; n < 4 * SK; n++) {
    if (!(n & 3)) { mbar_wait(c.sb + OFF_FULL + 8 * (8 - SK + n / 4), (g >> 3) & 1); wgmma_fence(); }
    PAIR(0, n);
    if (n == 3) { wgmma_commit(); wgmma_wait<1>(); if (c.lane < 2) mbar_arrive_cluster(rel + prev); wgmma_fence(); }
  }
  wgmma_commit();
#pragma unroll
  for (int n = 0; n < 4 * SK; n++) {
    if (n == 4 * SK - 2 && t < 13) bar_arrive(other, 256);
    PAIR(1, n);
    wgmma_commit();
#pragma unroll
    for (int z = 0; z < 8; z++) if (z / 4 + 2 == n) PUT(z);
    if (n == 3) bar_arrive(BAR_RES, 160);
    if (n && n < 4 * SK - 1) wgmma_wait<2>();
    if (n > 4 && (n & 3) == 1 && c.lane < 2) mbar_arrive_cluster(rel + 8 * (7 - SK + n / 4));
  }
  wgmma_wait<0>();
  if (c.lane < 2) mbar_arrive_cluster(rel + 56);
  TL(t, 3);
#pragma unroll
  for (int nt = 8; nt < 16; nt++) PUT(nt);
  fence_async_smem();
  __syncwarp();
  asm volatile(ELECT "@p mbarrier.complete_tx.relaxed.cta.shared::cta.b64 [%0], 1;\n}" :: "r"(c.sb + OFF_FULL + 8) : "memory");
  bar_arrive(BAR_RES2, 160);
#undef MMA
#undef PAIR
#undef PUT
}
__device__ __forceinline__ void release(const Ctx& c, int slot, int lanes = 2) {
  if (c.lane < lanes) mbar_arrive_cluster(mapa(c.sb + OFF_EMPTY, c.lane & 1) + 8 * slot);
}
__device__ __forceinline__ void finish(const Ctx& c, int t, int slot) {
  wgmma_wait<0>();
  release(c, slot);
  TL(t, 3);
}

__device__ __forceinline__ void put_halo(uint32_t addr, bool last, uint32_t a, uint32_t b, uint32_t c, uint32_t d) {
  if (!last) stmatrix4(addr, a, b, c, d);
  else asm volatile("stmatrix.sync.aligned.m8n8.x2.shared.b16 [%0], {%1, %2};\nstmatrix.sync.aligned.m8n8.x1.shared.b16 [%0 + 256], {%3};" :: "r"(addr), "r"(a), "r"(b), "r"(c) : "memory");
}

__device__ __forceinline__ void fetch_halo(const Ctx& c, unsigned tag, int tile) {
  const int v = c.w & 1;
  const uint4* src = g_halo + (tile * 128 + c.b - 8) * 352 + v * 160 + c.lane;
  uint4 G[6];
#pragma unroll
  for (int z = 0; z < 6; z++) G[z] = make_uint4(0u, 0u, 0u, 0u);
  bar_sync(BAR_HGO + v, 64);
  for (unsigned it = 0; c.m > 0; it++) {
    bool ok = true;
    if (it && !(tile & 1)) __nanosleep(200);
#pragma unroll
    for (int z = 0; z < 6; z++) { G[z] = ld_tag128(src + z * 32); ok = ok && G[z].w == tag; }
    if (__all_sync(0xffffffffu, ok) || it > SPIN_LIMIT) break;
  }
#pragma unroll
  for (int z = 0; z < 6; z++) put_halo(c.sb + OFF_STG + c.lane * 16 + (z ? (v * 5 + z) * 384 - 128 : v * 1792), z == 5, G[z].x, G[z].y, G[z].z, G[z].w);
  if (!v) sts32f(c.sb + OFF_RST - 256 + c.lane * 8, __uint_as_float(G[0].z));
  __syncwarp();
  mbar_arrive_e(c.sb + OFF_HALO + 8 * v);
}

template<int SKEW>
__device__ __forceinline__ void conv_qkv(const Ctx& c, float (&acc)[2][96], uint32_t (&P)[3][2][4][4], int t) {
  const int lane = c.lane, w = c.w, g = lane >> 2, cc = lane & 3;
  const int layer = t >= 7;
  const uint32_t sb = (c.sb & 0x3ffffu) >> 4, par = layer ^ 1;
  uint32_t da = DESC_A + sb + 7680 + 64, db = DESC_B + sb + 7680;
#define MMA(i, n) if (SKEW) do { wgmma_ss<192, 1>(acc[i], da, db); \
    asm volatile("add.s32 %0, %0, %2;\nadd.s32 %1, %1, %3;" : "+r"(da), "+r"(db) : "r"((n) == 11 ? 5050 : (n) == 7 ? 2554 : (n) == 3 ? -7686 : 2), "r"((n) == 11 ? 4736 : (n) == 7 ? 2176 : (n) == 3 ? -8064 : 128)); } while (0)
  const uint32_t rst = c.sb + OFF_RST + w * 256, csb = c.sb + OFF_CSQ + SKEW * 768 + cc * 16, stg = c.sb + OFF_STG + w * 4096;
  float mu[4];
  uint32_t tag, rs_l;
  uint4* halo;
  bool send;
#define SETUP do { _Pragma("unroll") for (int r = 0; r < 4; r++) mu[r] = __uint_as_float(lds32(rst + (8 * r + g) * 8 + 4)); \
    tag = smem_tag(c); rs_l = lds32(rst + lane * 8); \
    const int b = smem_block(c); \
    halo = g_halo + ((layer * 2 + SKEW) * 128 + b) * 352 + lane; send = w == 3 && b < 120; \
    if (SKEW) asm volatile("" : "+l"(halo)); } while (0)
  if (SKEW) {
    mbar_wait(c.sb + OFF_FULL + 40, par);
    wgmma_fence();
    MMA(1, 0); MMA(1, 1); MMA(1, 2); MMA(1, 3);
    wgmma_commit();
    wgmma_wait<1>();
    release(c, 4);
    SETUP;
    mbar_wait(c.sb + OFF_FULL + 48, par);
  } else finish(c, t, layer ? 1 : 7);
  MMA(1, 4); MMA(1, 5);
  bar_sync(BAR_EPI + c.wg, 256);
  MMA(1, 6);
  mbar_wait(c.sb + OFF_TBL + 8 * SKEW, 0);
  MMA(1, 7);
  if (SKEW) mbar_wait(c.sb + OFF_FULL + 56, par);
  MMA(1, 8);
  bar_sync(BAR_FREE, 160);
  MMA(1, 9);
  if (!SKEW) SETUP;
  float4 cs = lds128f(csb + 4 * 64);
  if (SKEW) {
    MMA(1, 10); MMA(1, 11);
    wgmma_commit();
    MMA(0, 0);
    wgmma_commit();
    MMA(0, 1);
    wgmma_commit();
    wgmma_wait<2>();
  }
#define CONV(i, np) do { _Pragma("unroll") for (int z = 0; z < 4; z++) { const int nt = 2 * (np) + (z >> 1), h = z & 1; \
    const float m = mu[2 * h + (i)]; \
    P[nt >> 3][(nt >> 2) & 1][2 * h + (i)][nt & 3] = pack_bf16(fmaf(z >> 1 ? cs.z : cs.x, m, acc[i][4 * nt + 2 * h]), \
                                                                     fmaf(z >> 1 ? cs.w : cs.y, m, acc[i][4 * nt + 2 * h + 1])); } } while (0)
#define HM(u) P[1 + (((u) >> 4) & 1)][((u) >> 3) & 1][((u) & 2) + 1][(((u) >> 1) & 2) + ((u) & 1)]
#define HW(u) ((u) == 2 ? rs_l : HM((u) - ((u) > 2)))
#pragma unroll
  for (int n = 0; n < 12; n++) {
    const int np = (n + 4) % 12;
    if (SKEW && n == HGK && w == 0) bar_arrive(BAR_HGO, 64);
    if (SKEW && n == HGO && w == 0) bar_arrive(BAR_HGO + 1, 64);
    if (SKEW && n == 8) bar_arrive(BAR_START + (c.wg ^ 1), 256);
    if (SKEW && n < 10) { MMA(0, n + 2); wgmma_commit(); }
    CONV(1, np);
    cs = lds128f(csb + (n < 11 ? (n + 5) % 12 : 0) * 64);
#pragma unroll
    for (int z = 0; z < 11; z++)
      if ((3 * z + 1) / 4 == n) {
        st_tag128_if(send, halo + z * 32, HW(3 * z), HW(3 * z + 1), HW(3 * z + 2), tag);
        put_halo(stg + 4096 + lane * 16 + (z ? z * 384 - 128 : 0), z == 10, HW(3 * z), HW(3 * z + 1), HW(3 * z + 2), tag);
      }
    if (SKEW && n < 10) wgmma_wait<2>();
    if (SKEW && (n == 3 || n == 7)) release(c, 5 + (n >> 2));
  }
#undef MMA
#undef HW
#undef SETUP
#undef HM
  if (SKEW) {
    wgmma_wait<0>();
    release(c, 7, w ? 2 : 0);
    TL(t, 3);
  }
#pragma unroll
  for (int np = 0; np < 12; np++) {
    CONV(0, np);
    if (!SKEW && np == HG1 && w == 0) { bar_arrive(BAR_HGO, 64); bar_arrive(BAR_HGO + 1, 64); }
    if (np < 11) cs = lds128f(csb + (np + 1) * 64);
  }
#undef CONV
}

__device__ __forceinline__ void epi_qkv(const Ctx& c, float (&acc)[2][96], int t, int q) {
  const int lane = c.lane, w = c.w, g = lane >> 2, cc = lane & 3;
  uint32_t P[3][2][4][4];
  if (q) conv_qkv<1>(c, acc, P, t); else conv_qkv<0>(c, acc, P, t);
  const uint32_t rst = c.sb + OFF_RST + w * 256, stg = c.sb + OFF_STG + w * 4096;
  const bool nohalo = w == 0 && smem_block(c) < 8;
#pragma unroll
  for (int z = 0; z < 16; z++) P[2][z >> 3][(z >> 1) & 2][z & 3] = movmatrix(P[2][z >> 3][(z >> 1) & 2][z & 3]);
  uint32_t K1[4][4], V1[4][4];
  const uint32_t hl = stg + (lane & 15) * 16 + (lane >> 4) * 512;
#define HZ(z) (((z) >> 1) * 1024 + ((z) & 1) * 256)
  __syncwarp();
#pragma unroll
  for (int z = 0; z < 4; z++) { ldmatrix4(hl + 4096 + HZ(z), K1[z]); ldmatrix4_t(hl + 4096 + 2048 + HZ(z), V1[z]); }
  TL(t, 9);
  bar_sync(BAR_WG + c.wg, 128);
  if (w == 0) { TL(t, 8); mbar_wait(c.sb + OFF_HALO, q); release(c, 7, 2 * q); }
  uint32_t HK[4][4], HV[4][4];
#pragma unroll
  for (int z = 0; z < 4; z++) ldmatrix4(hl + HZ(z), HK[z]);
  const bool far0 = 2 * cc > g, far1 = 2 * cc + 1 > g;
  float rk[4][2], sc[4][2];
#pragma unroll
  for (int r = 0; r < 4; r++) {
    const float rq = __uint_as_float(lds32(rst + (8 * r + g) * 8)) * (0.17677669529663687f * 1.4426950408889634f);
    const int back = r & 1 ? 64 : 192;
    rk[r][0] = __uint_as_float(lds32(rst + r * 64 + cc * 16 - (far0 ? back : 0)));
    rk[r][1] = __uint_as_float(lds32(rst + r * 64 + cc * 16 + 8 - (far1 ? back : 0)));
    sc[r][0] = rq * rk[r][0]; sc[r][1] = rq * rk[r][1];
  }
  TL(t, 4);
  float S[4][3][4];
  if (q == 0) bar_sync(BAR_P0, 256);
  float4 zero = lds128f(c.sb + OFF_ZERO);
#pragma unroll
  for (int k = 0; k < 2; k++)
#pragma unroll
    for (int z = 0; z < 4; z++) {
      const uint32_t* qa = P[0][z >> 1][2 * (z & 1)]; const uint32_t* qb = P[0][z >> 1][2 * (z & 1) + 1];
      const uint32_t* kk[3] = {HK[z], P[1][z >> 1][2 * (z & 1)], K1[z]};
#pragma unroll
      for (int n = 0; n < 3; n++) {
        if (k == 0) mma16816_z(S[z][n], qa[0], qb[0], qa[1], qb[1], kk[n][0], kk[n][1], zero);
        else mma16816(S[z][n], qa[2], qb[2], qa[3], qb[3], kk[n][2], kk[n][3]);
        if (q == 0 && k * 12 + z * 3 + n + 1 == NS) bar_arrive_here(BAR_P1, S[0][0][0], zero.x);
      }
    }
  TL(t, 10);
  const uint32_t fmask = (far0 ? 0xffffu : 0u) | (far1 ? 0xffff0000u : 0u);
  uint32_t pf[4][2], pn[4][2];
#pragma unroll
  for (int z = 0; z < 4; z++)
#pragma unroll
    for (int i = 0; i < 2; i++) {
      const int r = 2 * (z & 1) + i;
      float l0 = (far0 ? S[z][i][2 * i] : S[z][i + 1][2 * i]) * sc[r][0];
      float l1 = (far1 ? S[z][i][2 * i + 1] : S[z][i + 1][2 * i + 1]) * sc[r][1];
      if (i == 0 && nohalo) { const float neg = -1e9f * 1.4426950408889634f; if (far0) l0 = neg; if (far1) l1 = neg; }
      float mx = fmaxf(l0, l1);
      mx = fmaxf(mx, __shfl_xor_sync(0xffffffffu, mx, 1));
      mx = fmaxf(mx, __shfl_xor_sync(0xffffffffu, mx, 2));
      l0 = ex2(l0 - mx); l1 = ex2(l1 - mx);
      float sum = l0 + l1;
      l0 *= rk[r][0]; l1 *= rk[r][1];
      sum += __shfl_xor_sync(0xffffffffu, sum, 1);
      sum += __shfl_xor_sync(0xffffffffu, sum, 2);
      sum = rcp(sum);
      const uint32_t u = pack_bf16(l0 * sum, l1 * sum);
      pf[z][i] = u & fmask; pn[z][i] = u & ~fmask;
    }
  float O[4][2][2][4];
  TL(t, 11);
  if (w == 0) { mbar_wait(c.sb + OFF_HALO + 8, q); TL(t, 12); }
#pragma unroll
  for (int z = 0; z < 4; z++) ldmatrix4_t(hl + 2048 + HZ(z), HV[z]);
#undef HZ
  if (q == 0) bar_sync_after(BAR_P0, (pn[0][0] | pn[0][1] | pn[1][0]) | (pn[1][1] | pn[2][0] | pn[2][1]) | (pn[3][0] | pn[3][1]));
  zero = lds128f(c.sb + OFF_ZERO);
#pragma unroll
  for (int z = 0; z < 4; z++)
#pragma unroll
    for (int d = 0; d < 2; d++) {
      const uint32_t* v0 = P[2][z >> 1][2 * (z & 1)] + 2 * d;
      mma16816_z(O[z][0][d], HV[z][2 * d], HV[z][2 * d + 1], v0[0], v0[1], pf[z][0], pn[z][0], zero);
      mma16816_z(O[z][1][d], v0[0], v0[1], V1[z][2 * d], V1[z][2 * d + 1], pf[z][1], pn[z][1], zero);
      if (z * 4 + d * 2 + 2 == NP) bar_arrive_here(BAR_P1, O[0][0][0][0], zero.x);
    }
  TL(t, 5);
#pragma unroll
  for (int nt = 0; nt < 8; nt++) {
    uint32_t u[4];
#pragma unroll
    for (int r = 0; r < 4; r++) { const float* o = O[2 * (nt >> 2) + (r >> 1)][r & 1][(nt >> 1) & 1] + 2 * (nt & 1); u[r] = pack_bf16(o[0], o[1]); }
    stmatrix4_t(stg + lane * 128 + ((nt ^ (lane & 7)) << 4), u[0], u[1], u[2], u[3]);
  }
  bar_arrive(BAR_READY, 160);
  TL(t, 13);
}

template<int CH>
__device__ __forceinline__ void epi_up(const Ctx& c, float (&acc)[2][96], int type) {
  const int lane = c.lane, w = c.w, g = lane >> 2, cc = lane & 3;
  float rs[4], nm[4];
#pragma unroll
  for (int r = 0; r < 4; r++) { const float2 v = lds64f(c.sb + OFF_RST + (w * 32 + 8 * r + g) * 8); rs[r] = v.x; nm[r] = v.x * v.y; }
  const int loc0 = type == 3 ? 0 : (type == 4 ? 192 : 320);
  const uint32_t cb = c.sb + OFF_UP + loc0 * 8 + cc * 16;
  const uint32_t zero = lds32(c.sb + OFF_ZERO);
  uint32_t d[2] = {0u, 0u};
  const uint32_t stg = c.sb + OFF_STG + w * 4096;
#pragma unroll
  for (int ch = CH; ch < (CH ? 3 : 2); ch++) {
    uint32_t P[8][4];
#pragma unroll
    for (int n8 = 0; n8 < 8; n8++) {
      const int nt = ch * 8 + n8;
      const float4 cv = lds128f(cb + nt * 64);
#pragma unroll
      for (int r = 0; r < 4; r++) {
        const float m = after(nm[r], d[r & 1], zero);
        d[r & 1] = P[n8][r] = relu_sq_bf16(fmaf(acc[r & 1][4 * nt + 2 * (r >> 1)], rs[r], fmaf(cv.x, m, cv.z)),
                                           fmaf(acc[r & 1][4 * nt + 2 * (r >> 1) + 1], rs[r], fmaf(cv.y, m, cv.w)));
      }
    }
    bar_sync(BAR_FREE, 160);
#pragma unroll
    for (int n8 = 0; n8 < 8; n8++)
      stmatrix4(stg + lane * 128 + ((n8 ^ (lane & 7)) << 4), P[n8][0], P[n8][1], P[n8][2], P[n8][3]);
    bar_arrive(BAR_READY, 160);
  }
}

__device__ __forceinline__ void init_res(const Ctx& c, float (&acc)[2][96], int t, bool bias) {
  if (t == 2) mbar_wait(c.sb + OFF_XBAR, 0);
  uint32_t xb = res_addr(c);
  const uint32_t zero = lds32(c.sb + OFF_ZERO);
  float b[4];
#pragma unroll
  for (int r = 0; r < 4; r++) b[r] = bias ? __uint_as_float(lds32(c.sb + OFF_B2 + (r >> 1) * 256 + c.w * 64 + (r & 1) * 32 + (c.lane >> 2) * 4)) : 0.f;
#pragma unroll
  for (int z = 0; z < 16; z++) {
    uint32_t u[4];
    asm volatile("{\n.reg .pred p;\nSTAY:\nldmatrix.sync.aligned.m8n8.x4.trans.shared.b16 {%0, %1, %2, %3}, [%4];\nsetp.lt.u32 p, %0, %5;\n@p bra.uni STAY;\n}"
      : "=r"(u[0]), "=r"(u[1]), "=r"(u[2]), "=r"(u[3]) : "r"(xb + z * 2048), "r"(zero) : "memory");
#pragma unroll
    for (int r = 0; r < 4; r++) {
      float* a = acc[z >> 3] + (z & 7) * 8 + 2 * r;
      a[0] = bf_lo(u[r]) + b[(z >> 3) * 2 + (r & 1)];
      a[1] = bf_hi(u[r]) + b[(z >> 3) * 2 + (r & 1)];
      asm volatile("" : "+f"(a[0]), "+f"(a[1]));
    }
  }
}

__device__ __forceinline__ void load_table(const Ctx& c, const Params& p, int part, unsigned tag) {
  const int i0 = (part < 4 ? part * 192 : 704) + c.lane, n = part < 3 ? 6 : 4;
  const uint2* src = g_cs + c.j * NCS + i0;
  const uint32_t dst = c.sb + OFF_CSQ + (i0 & 1) * 4 + (part < 2 ? (i0 >> 4) * 64 + (i0 & 6) * 8 + (i0 & 8) : 1536 + ((i0 - 384) >> 1) * 16);
  const __nv_bfloat16* bias = p.b1 + (part == 2 ? c.j * 192 : (part == 3 ? 1536 : 2560) + c.j * 128) + c.lane;
  float v[6];
  if (part >= 2) {
#pragma unroll
    for (int k = 0; k < 6; k++) if (k < n) sts32f(dst + k * 256 + 8, __bfloat162float(bias[k * 32]));
  }
  for (unsigned it = 0;; it++) {
    bool ok = true;
#pragma unroll
    for (int k = 0; k < 6; k++) { const uint2 a = ld_tag64(src + (k < n ? k * 32 : 0)); ok = ok && a.y == tag; v[k] = __uint_as_float(a.x); }
    if (__all_sync(0xffffffffu, ok) || it > SPIN_LIMIT) break;
    __nanosleep(200);
  }
#pragma unroll
  for (int k = 0; k < 6; k++) if (k < n) sts32f(dst + k * (part < 2 ? 128 : 256), v[k]);
  __syncwarp();
}

__device__ __forceinline__ void colsum_cta(const Ctx& c, const Params& p, unsigned* epoch) {
  if (c.wg < 2) mbar_init_e(c.sb + OFF_FULL + 32 * c.wg + 8 * c.w, 1);
  sts32f(c.sb + OFF_STG + threadIdx.x * 4, __uint_as_float(0x3f803f80u));
  fence_async_smem();
  __syncthreads();
  if (c.wg == 2) return;
  const unsigned tag = *(volatile unsigned*)epoch + 1;
  const int j = (blockIdx.x - 128) * 2 + c.wg;
  const uint32_t ring = c.sb + c.wg * 98304, full = c.sb + OFF_FULL + 32 * c.wg;
  const uint64_t ones = (uint64_t)(((c.sb + OFF_STG) & 0x3ffffu) >> 4) | (8u << 16) | ((uint64_t)16u << 32);
  float d[3][4];
#pragma unroll 1
  for (int n = -4; n < 80; n++) {
    if (n >= 0) {
      mbar_wait(full + 8 * (n & 3), (n >> 2) & 1);
      const uint64_t da = (uint64_t)(((ring + (n & 3) * 24576) & 0x3ffffu) >> 4) | (64u << 16) | ((uint64_t)(64u | (1u << 30)) << 32);
      wgmma_fence();
#pragma unroll
      for (int k = 0; k < 4; k++)
#pragma unroll
        for (int z = 0; z < 3; z++)
          asm volatile("{\n.reg .pred p;\nsetp.ne.b32 p, %6, 0;\nwgmma.mma_async.sync.aligned.m64n8k16.f32.bf16.bf16 {%0,%1,%2,%3}, %4, %5, p, 1, 1, 1, 0;\n}"
            : "+f"(d[z][0]), "+f"(d[z][1]), "+f"(d[z][2]), "+f"(d[z][3]) : "l"(da + z * 512 + k * 128), "l"(ones), "r"((n & 15) | k));
      wgmma_commit();
      wgmma_wait<0>();
      bar_sync(BAR_WG + c.wg, 128);
      if ((n & 15) == 15 && (c.lane & 3) < 2) {
        const int u = n >> 4;
        uint2* out = g_cs + j * NCS + (u < 4 ? u * 192 : 704) + c.w * 16 + (c.lane >> 2) + (c.lane & 1) * 8;
#pragma unroll
        for (int z = 0; z < 3; z++) if (z < 2 || u < 3) st_tag64(out + z * 64, (c.lane & 1) ? d[z][2] : d[z][0], tag);
      }
      __syncwarp();
    }
    if (c.w == 0 && n < 76) {
      const int u = (n + 4) >> 4;
      const WTile w = wtile(u + (u >= 2), j);
      mbar_expect_e(full + 8 * (n & 3), u < 3 ? 24576 : 16384);
      tma_ld3_e(ring + (n & 3) * 24576, (const CUtensorMap*)((const char*)&p + w.map), full + 8 * (n & 3), w.c0, ((n + 4) & 15) * 64, w.c2);
    }
  }
  bar_sync(BAR_START, 256);
  if (threadIdx.x == 0) *epoch = tag;
}

__device__ __forceinline__ void place(Ctx& c, uint32_t slot) {
  const int row = slot < 32 ? slot >> 3 : slot < 60 ? ((slot - 4) * 37) >> 8 : slot - 56;
  const int gpc = slot < 60 ? slot - row * (slot < 32 ? 8 : 7) - (slot < 32 ? 0 : 3) : 0;
  c.m = (gpc & 1) * 8 + row;
  c.j = (gpc & 6) + c.rank; c.b = c.m * 8 + c.j;
}

__global__ void __cluster_dims__(2, 1, 1) __launch_bounds__(384, 1) fused_kernel(unsigned* const epochs, const char* const x0, const char* const w0, const __grid_constant__ Params p) {
  extern __shared__ uint8_t smem_raw[];
  const int tid = threadIdx.x;
  Ctx c;
  c.sb = (smem_u32(smem_raw) + 1023) & ~1023u;
  const int k = __shfl_sync(0xffffffffu, tid >> 5, 0);
  c.wg = k >> 2; c.w = k & 3; c.lane = tid & 31;
  c.rank = blockIdx.x & 1;
  if (blockIdx.x >= 128) { colsum_cta(c, p, epochs + blockIdx.x); return; }
  uint32_t slot; asm volatile("mov.u32 %0, %%smid;" : "=r"(slot));
  slot = __shfl_sync(0xffffffffu, slot < 120 ? slot >> 1 : 60 + ((slot >> 1) & 3), 0);
  if (c.wg == 2) {
    const bool claim = tid == 320 && c.rank == 0;
    unsigned epoch, old;
    asm volatile("{\n.reg .pred p;\nsetp.ne.u32 p, %4, 0;\nmov.u32 %0, 0;\nmov.u32 %1, 0;\n@p atom.relaxed.gpu.global.add.u32 %0, [%2], 1;\n@p ld.relaxed.gpu.global.u32 %1, [%3];\n}"
      : "=r"(old), "=r"(epoch) : "l"(epochs + 132 + slot + c.lane), "l"(epochs + blockIdx.x), "r"((uint32_t)claim) : "memory");
    reg_dealloc<40>();
#pragma unroll 1
    for (int pass = 0;; pass++) {
      place(c, slot);
      if (c.w == 1) {
        asm volatile(ELECT "@p mbarrier.init.shared::cta.b64 [%0], 2;\n@p mbarrier.init.shared::cta.b64 [%0 + 8], 2;\n"
          "@p mbarrier.init.shared::cta.b64 [%0 + 16], 2;\n@p mbarrier.init.shared::cta.b64 [%0 + 24], 2;\n}" :: "r"(c.sb + OFF_FULL) : "memory");
        fence_async_smem();
        if (!pass) asm volatile("fence.mbarrier_init.release.cluster;\nbarrier.cluster.arrive.relaxed.aligned;" ::: "memory");
#pragma unroll 1
        for (int s = pass ? 0 : 2; s < 4; s++) {
          const uint32_t full = c.sb + OFF_FULL + 8 * s, dst = c.sb + (s ^ 2) * 40960;
          mbar_expect_e(full, 40960);
          tma_ld4_e(dst, &p.ld_x, full, s * 64, c.m * 4);
          tma_ld4_e(dst + 8192, &p.ld_x, full, s * 64, c.m * 4 + 2);
          tma_ld3_e(dst + A_BYTES, &p.w_qkv, full, c.j * 64, s * 64, 0);
          mbar_arrive_e(full);
        }
      } else if (!pass) {
        if (c.w == 2) { mbar_init_e(c.sb + OFF_SLOT, 1); mbar_expect_e(c.sb + OFF_SLOT, 8); }
        asm volatile("fence.mbarrier_init.release.cluster;\nbarrier.cluster.arrive.relaxed.aligned;" ::: "memory");
      }
      if (c.w == 0) {
        asm volatile("cp.async.wait_all;" ::: "memory");
#pragma unroll
        for (int i = 0; i < PLAN_BYTES; i += 512)
          asm volatile("cp.async.cg.shared.global [%0], [%1], 16;" :: "r"(c.sb + OFF_PLAN + c.lane * 16 + i), "l"(epochs + 256 + c.j * (PLAN_BYTES / 4) + c.lane * 4 + i / 4) : "memory");
      }
      if (c.w == 3) sts32f(c.sb + OFF_TAG + 8, __int_as_float(c.b));
      if (pass) { bar_sync(BAR_START, 256); break; }
      asm volatile("barrier.cluster.wait.aligned;" ::: "memory");
      if (claim) {
        uint32_t s = slot;
        for (int it = 0; old != epoch && it < 64; it++) { atomicSub(epochs + 132 + s, 1u); s = (s + 1) & 63; old = atomicAdd(epochs + 132 + s, 1u); }
#pragma unroll
        for (int r = 0; r < 2; r++)
          asm volatile("{\n.reg .u32 t;\nadd.u32 t, %1, 1;\nst.async.weak.shared::cluster.mbarrier::complete_tx::bytes.v2.b32 [%0], {t, %2}, [%3];\n}"
            :: "r"(mapa(c.sb + OFF_TAG, r)), "r"(old), "r"(s), "r"(mapa(c.sb + OFF_SLOT, r)) : "memory");
      }
      __syncwarp();
      mbar_wait(c.sb + OFF_SLOT, 0);
      const uint32_t got = __shfl_sync(0xffffffffu, lds32(c.sb + OFF_TAG + 4), 0);
      if (got == slot) {
        bar_arrive(BAR_START, 256);
#pragma unroll 1
        for (int s = 0; s < 16 && c.w == 3; s += 8) {
          mbar_wait(c.sb + OFF_PRE + s, 0);
          PTL(12, 12 + s / 8);
          fence_async_smem();
          if (c.lane < 2) asm volatile("mbarrier.arrive.shared::cta.b64 _, [%0];" :: "r"(c.sb + OFF_FULL + s) : "memory");
        }
        break;
      }
      slot = got;
      if (c.w == 1)
#pragma unroll 1
        for (int s = 0; s < 4; s++) { mbar_wait(c.sb + (s < 2 ? OFF_PRE : OFF_FULL) + 8 * s, 0); asm volatile(ELECT "@p mbarrier.inval.shared::cta.b64 [%0];\n}" :: "r"(c.sb + OFF_FULL + 8 * s) : "memory"); }
    }
    const unsigned tag = smem_tag(c);
    if (c.w < 2) { asm volatile("cp.async.wait_all;" ::: "memory"); bar_sync(BAR_COPY, 64); PTL(14, 13); }
    if (c.w == 0) {
      const char* fp = (const char*)(g_flags + c.m * 32 + c.lane);
      unsigned ready = 1u << 31;
      float2 nx = lds64f(c.sb + OFF_PLAN);
#pragma unroll 1
      for (int g = 4; g < 2 * KB_LAYER; g++) {
        const uint32_t x = __float_as_uint(nx.x), y = __float_as_uint(nx.y);
        nx = lds64f(c.sb + OFF_PLAN + g * 16 - 48);
        if (y & A_NEW) ready = 1u << 31;
        for (unsigned it = 0; !((ready >> (x >> 27)) & 1) && it < SPIN_LIMIT; it++) {
          unsigned v; asm volatile("ld.relaxed.gpu.global.u32 %0, [%1];" : "=r"(v) : "l"(fp + (y >> 16)) : "memory");
          ready |= __ballot_sync(0xffffffffu, v == tag);
          asm volatile("fence.proxy.async.global;" ::: "memory");
        }
        mbar_wait(c.sb + OFF_EMPTY + (x & 0x38), x & 1);
        const uint32_t full = c.sb + OFF_FULL + 8 * (g & 7), dst = c.sb + (x & 0x3e000);
        const CUtensorMap* mp = (const CUtensorMap*)((const char*)&p + (y & 0x180));
        if (!(y & A_QUIET)) mbar_expect_e(full, y & 0x4004);
        if (!(y & A_COPY)) tma_ld4_mc_e(dst, mp, full, x & 0xfc0, c.m * 4 + c.rank * 2);
        else if (!(y & A_NONE)) { tma_ld4_e(dst, mp, full, x & 0xfc0, c.m * 4); tma_ld4_e(dst + 8192, mp, full, x & 0xfc0, c.m * 4 + 2); }
        else if (y & A_PAIR) {
          const uint32_t peer = mapa(c.sb, c.rank ^ 1);
          mbar_wait(c.sb + OFF_FULL, g < KB_LAYER);
          dsmem_copy_e(peer + 3 * 32768, c.sb + OFF_STG, peer + OFF_FULL + 8);
        }
      }
    } else if (c.w == 1) {
      float2 nx = lds64f(c.sb + OFF_PLAN + 8);
#pragma unroll 1
      for (int g = 4; g < 2 * KB_LAYER; g++) {
        const uint32_t x = __float_as_uint(nx.x), y = __float_as_uint(nx.y);
        nx = lds64f(c.sb + OFF_PLAN + g * 16 - 40);
        mbar_wait(c.sb + OFF_EMPTY + (x & 0x38), x & 1);
        const uint32_t full = c.sb + OFF_FULL + 8 * (g & 7);
        mbar_expect_e(full, y & 0x6000);
        tma_ld3_e(c.sb + (x & 0x3e000), (const CUtensorMap*)((const char*)&p + (y >> 16)), full, y & 0x3c0, x & 0xfc0, x >> 26);
      }
    } else if (c.w == 2) {
      if (c.lane == 0) epochs[blockIdx.x] = tag;
      mbar_pace(c.sb + OFF_EMPTY + 56, 0);
#pragma unroll 1
      for (int z = 0; z < 44; z++) st_tag128(g_halo + ((z & 3) * 128 + c.b) * 352 + (z >> 2) * 32 + c.lane, 0u, 0u, 0u, 0u);
      bar_arrive(BAR_FREE, 160);
#pragma unroll 1
      for (int t = 0; t < 14; t++) {
        const int layer = t >= 7, type = t - layer * 7;
        const int slab = c.m * 4;
        unsigned* flag = g_flags + c.m * 32 + c.j;
        if (type == 2 || type == 6) {
          flag += (t + 1) * 512 + c.j;
          bar_sync(BAR_RES, 160);
          fence_async_smem();
          asm volatile(ELECT "@p mbarrier.complete_tx.relaxed.cta.shared::cta.b64 [%0], 4;\n}" :: "r"(c.sb + OFF_FULL) : "memory");
          tma_st4_e(&p.st_out, c.sb + OFF_X, c.j * 128, slab);
          if (t < 13) {
            bulk_wait_read_e();
            PTL(t, 8);
            publish_e(flag++, tag);
            PTL(t, 9);
            mbar_wait(c.sb + OFF_FULL + 8, t != 2);
            mbar_wait(c.sb + OFF_EMPTY + 56, t == 2);
#pragma unroll
            for (int h = 0; h < 2; h++) tma_ld4_mc_e(c.sb + 3 * 40960 + h * 8192, &p.ld_out, c.sb + OFF_FULL + 40, c.j * 128, slab + 2 * h, 2 - c.rank);
          }
          if (t == 13) bar_sync(BAR_RES2, 160);
          tma_st4_e(&p.ld_out, c.sb + OFF_X + A_BYTES, c.j * 128 + 64, slab);
          if (t < 13) mbar_pace(c.sb + OFF_FULL + 48, t != 2);
          tma_st4_e(&p.ld_out, c.sb + OFF_X + A_BYTES + 8192, c.j * 128 + 64, slab + 2);
          bulk_wait_read_e();
          PTL(t, 11);
        } else {
          flag += (layer * 7 + (type < 2 ? 2 : 6)) * 512 + (type < 2 ? type : type - 3) * 8;
          const int col = type < 2 ? (c.j + 8 * type) * 64 : type == 3 ? c.j * 192 : (type == 4 ? 1536 : 2560) + c.j * 128;
#pragma unroll 1
          for (int ch = type == 3 ? -1 : 0; ch < (type < 2 ? 1 : 2); ch++) {
            if (type < 2) fetch_halo(c, tag, layer * 2 + type);
            bar_sync(BAR_READY, 160);
            fence_async_smem();
#pragma unroll 1
            for (int z = 0; z < 4; z++) {
              if (z && type != 1) bulk_wait_read_e();
              tma_st4_e(&p.st_h, c.sb + OFF_STG + z * 4096, col + (ch < 0 ? 128 : ch * 64), slab + z);
            }
            if (type == 1) { mbar_wait(c.sb + OFF_FULL, layer); mbar_arrive_e(c.sb + OFF_FULL); }
            bulk_wait_read_e();
            if (t < 12 || ch == 0) bar_arrive(BAR_FREE, 160);
          }
          PTL(t, 14);
        }
        if (t < 13) publish_e(flag, tag);
        PTL(t, 6);
      }
    } else {
      mbar_pace(c.sb + OFF_EMPTY + 8 * (c.m & 3), 0);
      PTL(14, 14);
      mbar_expect_e(c.sb + OFF_XBAR, 32768);
#pragma unroll
      for (int i = 0; i < 4; i++) tma_ld4_e(c.sb + OFF_X + i * 8192, &p.ld_x, c.sb + OFF_XBAR, c.j * 128 + (i >> 1) * 64, c.m * 4 + (i & 1) * 2);
#pragma unroll
      for (int i = 0; i < 4; i++) sts32f(c.sb + OFF_B2 + i * 128 + c.lane * 4, __bfloat162float(p.b2[c.j * 128 + i * 32 + c.lane]));
#pragma unroll 1
      for (int part = 0; part < 7; part++) {
        if (part < 5) {
          load_table(c, p, part, tag);
          mbar_arrive_e(c.sb + OFF_TBL + 8 * part);
          PTL(part, 7);
        }
        if (part < 2 || part > 4) fetch_halo(c, tag, part < 2 ? part : part - 3);
        if ((0x52 >> part) & 1) {
          const uint32_t peer = mapa(c.sb, c.rank ^ 1);
          bar_sync(BAR_RES2, 160);
          mbar_wait(c.sb + OFF_EMPTY + 56, part == 1);
          dsmem_copy_e(peer + 2 * 40960, c.sb + OFF_X + A_BYTES, peer + OFF_FULL + 32);
        }
      }
    }
  } else {
    place(c, slot);
    const int r = tid >> 3;
    const uint32_t dst = c.sb + 2 * 40960 + r * 128 + ((tid ^ r) & 7) * 16;
    const char* ga = x0 + (c.m * 128 + (r & 15) * 2 + c.wg) * 2048 + (tid & 7) * 16;
    const char* gb = w0 + r * 6144 + c.j * 128 + (tid & 7) * 16;
#pragma unroll
    for (int s = 0; s < 2; s++) {
#pragma unroll
      for (int i = 0; i < 10; i++)
        asm volatile("cp.async.cg.shared.global [%0], [%1], 16;" :: "r"(dst + s * 40960 + i * 4096),
          "l"(i < 4 ? ga + i * 65536 + s * 128 : gb + (2 * s + (i & 1)) * (32 * 6144) + (i / 2 - 2) * 2048) : "memory");
      if (!s) {
        mbar_init_e(c.sb + OFF_EMPTY + 8 * k, 8);
        mbar_init_e(c.sb + (k < 4 ? OFF_XBAR : OFF_FULL) + 8 * k, k < 4 ? 1 : 2);
        if (k < 7) mbar_init_e(c.sb + OFF_XBAR + 32 + 8 * k, k > 4 ? 256 : 1);
        else sts128(c.sb + OFF_ZERO, 0u, 0u, 0u, 0u);
        asm volatile("fence.mbarrier_init.release.cluster;\nbarrier.cluster.arrive.relaxed.aligned;" ::: "memory");
        bar_sync(BAR_EPI, 256);
      }
      asm volatile("cp.async.mbarrier.arrive.noinc.shared::cta.b64 [%0];" :: "r"(c.sb + OFF_PRE + 8 * s) : "memory");
    }
    asm volatile("barrier.cluster.wait.aligned;" ::: "memory");
    reg_alloc<232>();
    if (c.wg) { mbar_wait(c.sb + OFF_XBAR, 0); TL(-1, 4); row_stats<8>(c, 1); }
#pragma unroll 1
    for (int t = c.wg; t < 14; t += 2) {
      const int layer = t >= 7, type = t - layer * 7;
      const int g0 = layer * KB_LAYER + type * 16;
      float acc[2][96];
      if (type == 2 || type == 6) {
        init_res(c, acc, t, type == 6);
        mainloop<128, 1>(c, acc, t, type, g0, (type == 6 ? 56 : 16) - SK);
        if (t == 13) asm volatile("barrier.cluster.arrive.relaxed.aligned;" ::: "memory");
        TL(t, 4);
        continue;
      }
      if (type < 4) {
        mainloop<192, 0>(c, acc, t, type, g0, type == 1 ? 13 : 16);
        if (type < 2) { epi_qkv(c, acc, t, type); goto done; }
        finish(c, t, 1);
        bar_sync(BAR_EPI + c.wg, 256);
        mbar_wait(c.sb + OFF_TBL + 16, 0);
        epi_up<2>(c, acc, type);
      } else {
        mainloop<128, 0>(c, acc, t, type, g0, 16);
        finish(c, t, 7);
        bar_sync(BAR_EPI + c.wg, 256);
        mbar_wait(c.sb + OFF_TBL + 8 * (type - 1), 0);
      }
      epi_up<0>(c, acc, type);
      TL(t, 4);
    done:
      if (type != 1 && type != 5) bar_arrive(BAR_EPI + (c.wg ^ 1), 256);
    }
    if (c.wg == 1) {
      asm volatile("barrier.cluster.wait.aligned;" ::: "memory");
    }
  }
}

typedef CUresult (*EncodeFn)(CUtensorMap*, CUtensorMapDataType, cuuint32_t, void*, const cuuint64_t*, const cuuint64_t*,
                             const cuuint32_t*, const cuuint32_t*, CUtensorMapInterleave, CUtensorMapSwizzle,
                             CUtensorMapL2promotion, CUtensorMapFloatOOBfill);

void make_map(EncodeFn fn, CUtensorMap* m, const void* ptr, int rank, const cuuint64_t* dims, const cuuint64_t* strides, const cuuint32_t* box) {
  const cuuint32_t es[4] = {1, 1, 1, 1};
  fn(m, CU_TENSOR_MAP_DATA_TYPE_BFLOAT16, rank, const_cast<void*>(ptr), dims, strides, box, es, CU_TENSOR_MAP_INTERLEAVE_NONE,
     CU_TENSOR_MAP_SWIZZLE_128B, CU_TENSOR_MAP_L2_PROMOTION_L2_128B, CU_TENSOR_MAP_FLOAT_OOB_FILL_NONE);
}
void map_rows(EncodeFn fn, CUtensorMap* m, const void* ptr, int cols, int rows, int box_slabs, bool tokens) {
  const cuuint64_t rb = (cuuint64_t)cols * 2;
  const cuuint64_t dims[4] = {(cuuint64_t)cols, 16, 2, (cuuint64_t)(rows / 32)};
  const cuuint64_t st[3] = {tokens ? 2 * rb : rb, tokens ? rb : 16 * rb, 32 * rb};
  const cuuint32_t box[4] = {64, 16, 2, (cuuint32_t)box_slabs};
  make_map(fn, m, ptr, 4, dims, st, box);
}
void map_w(EncodeFn fn, CUtensorMap* m, const void* ptr, int K, int N, int inner, int nch) {
  const cuuint64_t dims[3] = {(cuuint64_t)inner, (cuuint64_t)K, (cuuint64_t)(N / inner)}, st[2] = {(cuuint64_t)N * 2, (cuuint64_t)inner * 2};
  const cuuint32_t box[3] = {64, 64, (cuuint32_t)nch};
  make_map(fn, m, ptr, 3, dims, st, box);
}

}

extern "C" void kernel_launch(void* const* d_in, const int* in_sizes, int n_in, void* d_out, int out_size) {
  (void)in_sizes; (void)n_in; (void)out_size;
  Params p;
  p.b1 = (const __nv_bfloat16*)d_in[5]; p.b2 = (const __nv_bfloat16*)d_in[7];
  void* fnp = nullptr; cudaDriverEntryPointQueryResult qr;
  cudaGetDriverEntryPoint("cuTensorMapEncodeTiled", &fnp, cudaEnableDefault, &qr);
  EncodeFn fn = (EncodeFn)fnp;
  void *h, *epochs;
  cudaGetSymbolAddress(&h, g_h);
  cudaGetSymbolAddress(&epochs, g_plan);
  map_rows(fn, &p.ld_x, d_in[0], D_, S_, 2, true);
  map_rows(fn, &p.ld_out, d_out, D_, S_, 2, true);
  map_rows(fn, &p.ld_h, h, F_, S_, 2, false);
  map_rows(fn, &p.st_h, h, F_, S_, 1, false);
  map_rows(fn, &p.st_out, d_out, D_, S_, 4, true);
  map_w(fn, &p.w_qkv, d_in[1], D_, 3 * D_, D_, 3);
  map_w(fn, &p.w_o, d_in[2], D_, D_, 64, 2);
  map_w(fn, &p.w_1a, d_in[4], D_, F_, 64, 3);
  map_w(fn, &p.w_1b, d_in[4], D_, F_, 64, 2);
  map_w(fn, &p.w_2, d_in[6], F_, D_, 64, 2);
  cudaFuncSetAttribute(fused_kernel, cudaFuncAttributeMaxDynamicSharedMemorySize, SMEM_BYTES);
  fused_kernel<<<132, 384, SMEM_BYTES>>>((unsigned*)epochs, (const char*)d_in[0], (const char*)d_in[1], p);
}
```

```cpp
#include <cuda_runtime.h>
#include <cuda_bf16.h>
#include <cuda.h>
#include <stdint.h>

#define EXP 0
namespace {

constexpr int S_ = 2048, D_ = 1024, F_ = 3584;
constexpr int A_BYTES = 16384;
constexpr int OFF_X   = 163840;
constexpr int OFF_STG = OFF_X + 32768;
constexpr int OFF_CSQ = OFF_STG + 20480;
constexpr int OFF_UP  = OFF_CSQ + 1536;
constexpr int OFF_B2  = OFF_UP + 3584;
constexpr int OFF_RST = OFF_B2 + 512 + 256;
constexpr int OFF_FULL = OFF_RST + 1024;
constexpr int OFF_EMPTY = OFF_FULL + 64;
constexpr int OFF_XBAR = OFF_EMPTY + 64;
constexpr int OFF_TBL = OFF_XBAR + 8;
constexpr int OFF_HALO = OFF_XBAR + 48;
constexpr int OFF_SLOT = OFF_XBAR + 88;
constexpr int OFF_IDLE = OFF_XBAR + 64;
constexpr int OFF_PRE = OFF_XBAR + 72;
constexpr int OFF_ZERO = OFF_XBAR + 96;
constexpr int OFF_TAG = OFF_ZERO + 16;
constexpr int OFF_PLAN = OFF_TAG + 16, PLAN_BYTES = 5120;
constexpr int SMEM_BYTES = OFF_PLAN + PLAN_BYTES + 48 + 1024;
constexpr int KB_LAYER = 6 * 16 + 56;
constexpr int NCS = 384 + 448;
constexpr unsigned SPIN_LIMIT = 1u << 20;
constexpr int NS = 12, NP = 8, SA = 7, SB = 11, PAUSE1 = 7, PAUSE2 = 8, HGK = 8, HGO = 11, HG1 = 3;
constexpr int SK = 3;
constexpr uint32_t DESC_A = 1u << 16, DESC_B = (512u << 16) + A_BYTES / 16;
enum { BAR_START = 1, BAR_EPI = 3, BAR_WG = 5, BAR_P0 = 7, BAR_P1 = 8, BAR_RES = 9, BAR_READY = 10, BAR_FREE = 11, BAR_COPY = 12, BAR_RES2 = 13, BAR_HGO = 14 };

struct Params {
  CUtensorMap ld_x, ld_out, ld_h, st_h, st_out, w_qkv, w_o, w_1a, w_1b, w_2;
  const __nv_bfloat16 *b1, *b2;
  char* out;
};

__device__ __align__(1024) __nv_bfloat16 g_h[S_ * F_];
__device__ __align__(128) uint4 g_stats[4 * S_ * 8];
__device__ __align__(128) uint2 g_cs[8 * NCS];
__device__ __align__(128) uint4 g_halo[4 * 128 * 11 * 32];
__device__ __align__(128) unsigned g_flags[14 * 16 * 32];
#define TL(t, e)
#define PTL(t, e)
#if !defined(TIMELINE) || !(EXP & 8)
#undef TK
#define TK(t, k)
#endif

template<int N, int KEEP> __device__ __forceinline__ void wgmma_ss(float (&d)[96], uint32_t da, uint32_t db);
template<> __device__ __forceinline__ void wgmma_ss<128, 0>(float (&d)[96], uint32_t da, uint32_t db) {
  asm volatile("{\n.reg .pred p;\n.reg .b64 a, b;\nsetp.ne.b32 p, 0, 0;\nmov.b64 a, {%64, 0x40000080};\nmov.b64 b, {%65, 0x40000040};\nwgmma.mma_async.sync.aligned.m64n128k16.f32.bf16.bf16 {%0, %1, %2, %3, %4, %5, %6, %7, %8, %9, %10, %11, %12, %13, %14, %15, %16, %17, %18, %19, %20, %21, %22, %23, %24, %25, %26, %27, %28, %29, %30, %31, %32, %33, %34, %35, %36, %37, %38, %39, %40, %41, %42, %43, %44, %45, %46, %47, %48, %49, %50, %51, %52, %53, %54, %55, %56, %57, %58, %59, %60, %61, %62, %63}, a, b, p, 1, 1, 0, 1;\n}"
    : "=f"(d[0]), "=f"(d[1]), "=f"(d[2]), "=f"(d[3]), "=f"(d[4]), "=f"(d[5]), "=f"(d[6]), "=f"(d[7]), "=f"(d[8]), "=f"(d[9]), "=f"(d[10]), "=f"(d[11]), "=f"(d[12]), "=f"(d[13]), "=f"(d[14]), "=f"(d[15]), "=f"(d[16]), "=f"(d[17]), "=f"(d[18]), "=f"(d[19]), "=f"(d[20]), "=f"(d[21]), "=f"(d[22]), "=f"(d[23]), "=f"(d[24]), "=f"(d[25]), "=f"(d[26]), "=f"(d[27]), "=f"(d[28]), "=f"(d[29]), "=f"(d[30]), "=f"(d[31]), "=f"(d[32]), "=f"(d[33]), "=f"(d[34]), "=f"(d[35]), "=f"(d[36]), "=f"(d[37]), "=f"(d[38]), "=f"(d[39]), "=f"(d[40]), "=f"(d[41]), "=f"(d[42]), "=f"(d[43]), "=f"(d[44]), "=f"(d[45]), "=f"(d[46]), "=f"(d[47]), "=f"(d[48]), "=f"(d[49]), "=f"(d[50]), "=f"(d[51]), "=f"(d[52]), "=f"(d[53]), "=f"(d[54]), "=f"(d[55]), "=f"(d[56]), "=f"(d[57]), "=f"(d[58]), "=f"(d[59]), "=f"(d[60]), "=f"(d[61]), "=f"(d[62]), "=f"(d[63])
    : "r"(da), "r"(db));
}
template<> __device__ __forceinline__ void wgmma_ss<128, 1>(float (&d)[96], uint32_t da, uint32_t db) {
  asm volatile("{\n.reg .pred p;\n.reg .b64 a, b;\nsetp.ne.b32 p, 1, 0;\nmov.b64 a, {%64, 0x40000080};\nmov.b64 b, {%65, 0x40000040};\nwgmma.mma_async.sync.aligned.m64n128k16.f32.bf16.bf16 {%0, %1, %2, %3, %4, %5, %6, %7, %8, %9, %10, %11, %12, %13, %14, %15, %16, %17, %18, %19, %20, %21, %22, %23, %24, %25, %26, %27, %28, %29, %30, %31, %32, %33, %34, %35, %36, %37, %38, %39, %40, %41, %42, %43, %44, %45, %46, %47, %48, %49, %50, %51, %52, %53, %54, %55, %56, %57, %58, %59, %60, %61, %62, %63}, a, b, p, 1, 1, 0, 1;\n}"
    : "+f"(d[0]), "+f"(d[1]), "+f"(d[2]), "+f"(d[3]), "+f"(d[4]), "+f"(d[5]), "+f"(d[6]), "+f"(d[7]), "+f"(d[8]), "+f"(d[9]), "+f"(d[10]), "+f"(d[11]), "+f"(d[12]), "+f"(d[13]), "+f"(d[14]), "+f"(d[15]), "+f"(d[16]), "+f"(d[17]), "+f"(d[18]), "+f"(d[19]), "+f"(d[20]), "+f"(d[21]), "+f"(d[22]), "+f"(d[23]), "+f"(d[24]), "+f"(d[25]), "+f"(d[26]), "+f"(d[27]), "+f"(d[28]), "+f"(d[29]), "+f"(d[30]), "+f"(d[31]), "+f"(d[32]), "+f"(d[33]), "+f"(d[34]), "+f"(d[35]), "+f"(d[36]), "+f"(d[37]), "+f"(d[38]), "+f"(d[39]), "+f"(d[40]), "+f"(d[41]), "+f"(d[42]), "+f"(d[43]), "+f"(d[44]), "+f"(d[45]), "+f"(d[46]), "+f"(d[47]), "+f"(d[48]), "+f"(d[49]), "+f"(d[50]), "+f"(d[51]), "+f"(d[52]), "+f"(d[53]), "+f"(d[54]), "+f"(d[55]), "+f"(d[56]), "+f"(d[57]), "+f"(d[58]), "+f"(d[59]), "+f"(d[60]), "+f"(d[61]), "+f"(d[62]), "+f"(d[63])
    : "r"(da), "r"(db));
}
template<> __device__ __forceinline__ void wgmma_ss<192, 0>(float (&d)[96], uint32_t da, uint32_t db) {
  asm volatile("{\n.reg .pred p;\n.reg .b64 a, b;\nsetp.ne.b32 p, 0, 0;\nmov.b64 a, {%96, 0x40000080};\nmov.b64 b, {%97, 0x40000040};\nwgmma.mma_async.sync.aligned.m64n192k16.f32.bf16.bf16 {%0, %1, %2, %3, %4, %5, %6, %7, %8, %9, %10, %11, %12, %13, %14, %15, %16, %17, %18, %19, %20, %21, %22, %23, %24, %25, %26, %27, %28, %29, %30, %31, %32, %33, %34, %35, %36, %37, %38, %39, %40, %41, %42, %43, %44, %45, %46, %47, %48, %49, %50, %51, %52, %53, %54, %55, %56, %57, %58, %59, %60, %61, %62, %63, %64, %65, %66, %67, %68, %69, %70, %71, %72, %73, %74, %75, %76, %77, %78, %79, %80, %81, %82, %83, %84, %85, %86, %87, %88, %89, %90, %91, %92, %93, %94, %95}, a, b, p, 1, 1, 0, 1;\n}"
    : "=f"(d[0]), "=f"(d[1]), "=f"(d[2]), "=f"(d[3]), "=f"(d[4]), "=f"(d[5]), "=f"(d[6]), "=f"(d[7]), "=f"(d[8]), "=f"(d[9]), "=f"(d[10]), "=f"(d[11]), "=f"(d[12]), "=f"(d[13]), "=f"(d[14]), "=f"(d[15]), "=f"(d[16]), "=f"(d[17]), "=f"(d[18]), "=f"(d[19]), "=f"(d[20]), "=f"(d[21]), "=f"(d[22]), "=f"(d[23]), "=f"(d[24]), "=f"(d[25]), "=f"(d[26]), "=f"(d[27]), "=f"(d[28]), "=f"(d[29]), "=f"(d[30]), "=f"(d[31]), "=f"(d[32]), "=f"(d[33]), "=f"(d[34]), "=f"(d[35]), "=f"(d[36]), "=f"(d[37]), "=f"(d[38]), "=f"(d[39]), "=f"(d[40]), "=f"(d[41]), "=f"(d[42]), "=f"(d[43]), "=f"(d[44]), "=f"(d[45]), "=f"(d[46]), "=f"(d[47]), "=f"(d[48]), "=f"(d[49]), "=f"(d[50]), "=f"(d[51]), "=f"(d[52]), "=f"(d[53]), "=f"(d[54]), "=f"(d[55]), "=f"(d[56]), "=f"(d[57]), "=f"(d[58]), "=f"(d[59]), "=f"(d[60]), "=f"(d[61]), "=f"(d[62]), "=f"(d[63]), "=f"(d[64]), "=f"(d[65]), "=f"(d[66]), "=f"(d[67]), "=f"(d[68]), "=f"(d[69]), "=f"(d[70]), "=f"(d[71]), "=f"(d[72]), "=f"(d[73]), "=f"(d[74]), "=f"(d[75]), "=f"(d[76]), "=f"(d[77]), "=f"(d[78]), "=f"(d[79]), "=f"(d[80]), "=f"(d[81]), "=f"(d[82]), "=f"(d[83]), "=f"(d[84]), "=f"(d[85]), "=f"(d[86]), "=f"(d[87]), "=f"(d[88]), "=f"(d[89]), "=f"(d[90]), "=f"(d[91]), "=f"(d[92]), "=f"(d[93]), "=f"(d[94]), "=f"(d[95])
    : "r"(da), "r"(db));
}
template<> __device__ __forceinline__ void wgmma_ss<192, 1>(float (&d)[96], uint32_t da, uint32_t db) {
  asm volatile("{\n.reg .pred p;\n.reg .b64 a, b;\nsetp.ne.b32 p, 1, 0;\nmov.b64 a, {%96, 0x40000080};\nmov.b64 b, {%97, 0x40000040};\nwgmma.mma_async.sync.aligned.m64n192k16.f32.bf16.bf16 {%0, %1, %2, %3, %4, %5, %6, %7, %8, %9, %10, %11, %12, %13, %14, %15, %16, %17, %18, %19, %20, %21, %22, %23, %24, %25, %26, %27, %28, %29, %30, %31, %32, %33, %34, %35, %36, %37, %38, %39, %40, %41, %42, %43, %44, %45, %46, %47, %48, %49, %50, %51, %52, %53, %54, %55, %56, %57, %58, %59, %60, %61, %62, %63, %64, %65, %66, %67, %68, %69, %70, %71, %72, %73, %74, %75, %76, %77, %78, %79, %80, %81, %82, %83, %84, %85, %86, %87, %88, %89, %90, %91, %92, %93, %94, %95}, a, b, p, 1, 1, 0, 1;\n}"
    : "+f"(d[0]), "+f"(d[1]), "+f"(d[2]), "+f"(d[3]), "+f"(d[4]), "+f"(d[5]), "+f"(d[6]), "+f"(d[7]), "+f"(d[8]), "+f"(d[9]), "+f"(d[10]), "+f"(d[11]), "+f"(d[12]), "+f"(d[13]), "+f"(d[14]), "+f"(d[15]), "+f"(d[16]), "+f"(d[17]), "+f"(d[18]), "+f"(d[19]), "+f"(d[20]), "+f"(d[21]), "+f"(d[22]), "+f"(d[23]), "+f"(d[24]), "+f"(d[25]), "+f"(d[26]), "+f"(d[27]), "+f"(d[28]), "+f"(d[29]), "+f"(d[30]), "+f"(d[31]), "+f"(d[32]), "+f"(d[33]), "+f"(d[34]), "+f"(d[35]), "+f"(d[36]), "+f"(d[37]), "+f"(d[38]), "+f"(d[39]), "+f"(d[40]), "+f"(d[41]), "+f"(d[42]), "+f"(d[43]), "+f"(d[44]), "+f"(d[45]), "+f"(d[46]), "+f"(d[47]), "+f"(d[48]), "+f"(d[49]), "+f"(d[50]), "+f"(d[51]), "+f"(d[52]), "+f"(d[53]), "+f"(d[54]), "+f"(d[55]), "+f"(d[56]), "+f"(d[57]), "+f"(d[58]), "+f"(d[59]), "+f"(d[60]), "+f"(d[61]), "+f"(d[62]), "+f"(d[63]), "+f"(d[64]), "+f"(d[65]), "+f"(d[66]), "+f"(d[67]), "+f"(d[68]), "+f"(d[69]), "+f"(d[70]), "+f"(d[71]), "+f"(d[72]), "+f"(d[73]), "+f"(d[74]), "+f"(d[75]), "+f"(d[76]), "+f"(d[77]), "+f"(d[78]), "+f"(d[79]), "+f"(d[80]), "+f"(d[81]), "+f"(d[82]), "+f"(d[83]), "+f"(d[84]), "+f"(d[85]), "+f"(d[86]), "+f"(d[87]), "+f"(d[88]), "+f"(d[89]), "+f"(d[90]), "+f"(d[91]), "+f"(d[92]), "+f"(d[93]), "+f"(d[94]), "+f"(d[95])
    : "r"(da), "r"(db));
}
template<> __device__ __forceinline__ void wgmma_ss<128, 2>(float (&d)[96], uint32_t da, uint32_t db) {
  asm volatile("{\n.reg .pred p;\n.reg .b64 a, b;\nsetp.ne.b32 p, 2, 0;\nmov.b64 a, {%64, 0x40000040};\nmov.b64 b, {%65, 0x40000040};\nwgmma.mma_async.sync.aligned.m64n128k16.f32.bf16.bf16 {%0, %1, %2, %3, %4, %5, %6, %7, %8, %9, %10, %11, %12, %13, %14, %15, %16, %17, %18, %19, %20, %21, %22, %23, %24, %25, %26, %27, %28, %29, %30, %31, %32, %33, %34, %35, %36, %37, %38, %39, %40, %41, %42, %43, %44, %45, %46, %47, %48, %49, %50, %51, %52, %53, %54, %55, %56, %57, %58, %59, %60, %61, %62, %63}, b, a, p, 1, 1, 1, 0;\n}"
    : "+f"(d[0]), "+f"(d[1]), "+f"(d[2]), "+f"(d[3]), "+f"(d[4]), "+f"(d[5]), "+f"(d[6]), "+f"(d[7]), "+f"(d[8]), "+f"(d[9]), "+f"(d[10]), "+f"(d[11]), "+f"(d[12]), "+f"(d[13]), "+f"(d[14]), "+f"(d[15]), "+f"(d[16]), "+f"(d[17]), "+f"(d[18]), "+f"(d[19]), "+f"(d[20]), "+f"(d[21]), "+f"(d[22]), "+f"(d[23]), "+f"(d[24]), "+f"(d[25]), "+f"(d[26]), "+f"(d[27]), "+f"(d[28]), "+f"(d[29]), "+f"(d[30]), "+f"(d[31]), "+f"(d[32]), "+f"(d[33]), "+f"(d[34]), "+f"(d[35]), "+f"(d[36]), "+f"(d[37]), "+f"(d[38]), "+f"(d[39]), "+f"(d[40]), "+f"(d[41]), "+f"(d[42]), "+f"(d[43]), "+f"(d[44]), "+f"(d[45]), "+f"(d[46]), "+f"(d[47]), "+f"(d[48]), "+f"(d[49]), "+f"(d[50]), "+f"(d[51]), "+f"(d[52]), "+f"(d[53]), "+f"(d[54]), "+f"(d[55]), "+f"(d[56]), "+f"(d[57]), "+f"(d[58]), "+f"(d[59]), "+f"(d[60]), "+f"(d[61]), "+f"(d[62]), "+f"(d[63])
    : "r"(da), "r"(db));
}

__device__ __forceinline__ uint32_t smem_u32(const void* p) { return (uint32_t)__cvta_generic_to_shared(p); }
__device__ __forceinline__ void mbar_arrive_cluster(uint32_t bar) { asm volatile("mbarrier.arrive.shared::cluster.b64 _, [%0];" :: "r"(bar) : "memory"); }
__device__ __forceinline__ void mbar_wait(uint32_t bar, uint32_t parity) {
  asm volatile(
    "{\n.reg .pred p;\n.reg .u32 n;\n"
    "mbarrier.try_wait.parity.shared::cta.b64 p, [%0], %1;\n"
    "@p bra.uni WAIT_DONE;\n"
    "mov.u32 n, 0;\n"
    "WAIT_LOOP:\n"
    "mbarrier.try_wait.parity.shared::cta.b64 p, [%0], %1;\n"
    "@p bra.uni WAIT_DONE;\n"
    "add.u32 n, n, 1;\n"
    "setp.lt.u32 p, n, 0x100000;\n"
    "@p bra.uni WAIT_LOOP;\n"
    "trap;\n"
    "WAIT_DONE:\n}" :: "r"(bar), "r"(parity) : "memory");
}
__device__ __forceinline__ void mbar_pace(uint32_t bar, uint32_t parity) {
  asm volatile(
    "{\n.reg .pred p;\n.reg .u32 n;\nmov.u32 n, 0;\n"
    "PACE_LOOP:\n"
    "mbarrier.try_wait.parity.shared::cta.b64 p, [%0], %1, 1000;\n"
    "add.u32 n, n, 1;\n"
    "setp.lt.and.u32 p, n, 16, !p;\n"
    "@p bra.uni PACE_LOOP;\n}" :: "r"(bar), "r"(parity) : "memory");
}
__device__ __forceinline__ uint32_t mbar_test(uint32_t bar, uint32_t parity) {
  uint32_t ok;
  asm volatile("{\n.reg .pred p;\nmbarrier.test_wait.parity.shared::cta.b64 p, [%1], %2;\nselp.u32 %0, 1, 0, p;\n}" : "=r"(ok) : "r"(bar), "r"(parity) : "memory");
  return ok;
}
#define ELECT "{\n.reg .pred p;\nelect.sync _|p, 0xffffffff;\n"
__device__ __forceinline__ void mbar_init_e(uint32_t bar, uint32_t cnt) { asm volatile(ELECT "@p mbarrier.init.shared::cta.b64 [%0], %1;\n}" :: "r"(bar), "r"(cnt) : "memory"); }
__device__ __forceinline__ void mbar_arrive_e(uint32_t bar) { asm volatile(ELECT "@p mbarrier.arrive.shared::cta.b64 _, [%0];\n}" :: "r"(bar) : "memory"); }
__device__ __forceinline__ void mbar_expect_e(uint32_t bar, uint32_t bytes) { asm volatile(ELECT "@p mbarrier.arrive.expect_tx.shared::cta.b64 _, [%0], %1;\n}" :: "r"(bar), "r"(bytes) : "memory"); }
__device__ __forceinline__ void tma_ld4_e(uint32_t dst, const CUtensorMap* m, uint32_t bar, int c0, int c3) {
  asm volatile(ELECT "@p cp.async.bulk.tensor.4d.shared::cluster.global.mbarrier::complete_tx::bytes [%0], [%1, {%3, %5, %5, %4}], [%2];\n}"
    :: "r"(dst), "l"(m), "r"(bar), "r"(c0), "r"(c3), "r"(0) : "memory");
}
__device__ __forceinline__ void tma_ld4_mc_e(uint32_t dst, const CUtensorMap* m, uint32_t bar, int c0, int c3, uint16_t mask = 3) {
  asm volatile(ELECT "@p cp.async.bulk.tensor.4d.shared::cluster.global.mbarrier::complete_tx::bytes.multicast::cluster [%0], [%1, {%3, %5, %5, %4}], [%2], %6;\n}"
    :: "r"(dst), "l"(m), "r"(bar), "r"(c0), "r"(c3), "r"(0), "h"(mask) : "memory");
}
__device__ __forceinline__ void tma_ld3_e(uint32_t dst, const CUtensorMap* m, uint32_t bar, int c0, int c1, int c2) {
  asm volatile(ELECT "@p cp.async.bulk.tensor.3d.shared::cluster.global.mbarrier::complete_tx::bytes [%0], [%1, {%3, %4, %5}], [%2];\n}"
    :: "r"(dst), "l"(m), "r"(bar), "r"(c0), "r"(c1), "r"(c2) : "memory");
}
__device__ __forceinline__ void tma_st4_e(const CUtensorMap* m, uint32_t src, int c0, int c3) {
  asm volatile(ELECT "@p cp.async.bulk.tensor.4d.global.shared::cta.bulk_group [%0, {%2, %4, %4, %3}], [%1];\n}"
    :: "l"(m), "r"(src), "r"(c0), "r"(c3), "r"(0) : "memory");
}
__device__ __forceinline__ void dsmem_copy_e(uint32_t dst, uint32_t src, uint32_t bar) {
  asm volatile(ELECT "@p cp.async.bulk.shared::cluster.shared::cta.mbarrier::complete_tx::bytes [%0], [%1], 16384, [%2];\n}"
    :: "r"(dst), "r"(src), "r"(bar) : "memory");
}
__device__ __forceinline__ void bulk_wait_read_e() { asm volatile(ELECT "@p cp.async.bulk.commit_group;\n@p cp.async.bulk.wait_group.read 0;\n}" ::: "memory"); __syncwarp(); }
__device__ __forceinline__ void publish_e(unsigned* flag, unsigned tag) {
  asm volatile(ELECT "@p fence.proxy.async;\n@p st.relaxed.gpu.global.u32 [%0], %1;\n}" :: "l"(flag), "r"(tag) : "memory");
  __syncwarp();
}
__device__ __forceinline__ void fence_async_smem() { asm volatile("fence.proxy.async.shared::cta;" ::: "memory"); }
__device__ __forceinline__ void wgmma_fence() { asm volatile("wgmma.fence.sync.aligned;" ::: "memory"); }
__device__ __forceinline__ void wgmma_commit() { asm volatile("wgmma.commit_group.sync.aligned;" ::: "memory"); }
template<int N> __device__ __forceinline__ void wgmma_wait() { asm volatile("wgmma.wait_group.sync.aligned %0;" :: "n"(N) : "memory"); }
__device__ __forceinline__ void bar_sync(int id, int n) { asm volatile("bar.sync %0, %1;" :: "r"(id), "r"(n) : "memory"); }
__device__ __forceinline__ void bar_arrive(int id, int n) { asm volatile("bar.arrive %0, %1;" :: "r"(id), "r"(n) : "memory"); }
__device__ __forceinline__ void bar_arrive_here(int id, float dep, float zero) {
  asm volatile("{\n.reg .pred p;\n.reg .u32 n;\nsetp.ne.u32 p, %2, 0;\nor.b32 n, %1, 256;\nmin.u32 n, n, 256;\nAGAIN:\nbar.arrive %0, n;\n@p bra.uni AGAIN;\n}"
    :: "r"(id), "r"(__float_as_uint(dep)), "r"(__float_as_uint(zero)) : "memory");
}
__device__ __forceinline__ void bar_sync_after(int id, uint32_t dep) {
  asm volatile("{\n.reg .u32 n;\nor.b32 n, %1, 256;\nmin.u32 n, n, 256;\nbar.sync %0, n;\n}" :: "r"(id), "r"(dep) : "memory");
}
__device__ __forceinline__ uint32_t mapa(uint32_t a, uint32_t r) { uint32_t d; asm("mapa.shared::cluster.u32 %0, %1, %2;" : "=r"(d) : "r"(a), "r"(r)); return d; }
__device__ __forceinline__ void st_tag128(uint4* p, uint32_t a, uint32_t b, uint32_t c, uint32_t tag) {
  asm volatile("{\n.reg .b64 lo, hi;\n.reg .b128 v;\nmov.b64 lo, {%1, %2};\nmov.b64 hi, {%3, %4};\nmov.b128 v, {lo, hi};\nst.relaxed.gpu.global.b128 [%0], v;\n}"
    :: "l"(p), "r"(a), "r"(b), "r"(c), "r"(tag) : "memory");
}
__device__ __forceinline__ void st_tag128_if(bool on, uint4* p, uint32_t a, uint32_t b, uint32_t c, uint32_t tag) {
  asm volatile("{\n.reg .pred q;\n.reg .b64 lo, hi;\n.reg .b128 v;\nsetp.ne.u32 q, %5, 0;\nmov.b64 lo, {%1, %2};\nmov.b64 hi, {%3, %4};\nmov.b128 v, {lo, hi};\n@q st.relaxed.gpu.global.b128 [%0], v;\n}"
    :: "l"(p), "r"(a), "r"(b), "r"(c), "r"(tag), "r"((uint32_t)on) : "memory");
}
__device__ __forceinline__ uint4 ld_tag128(const uint4* p) {
  uint4 v;
  asm volatile("{\n.reg .b64 lo, hi;\n.reg .b128 v;\nld.relaxed.gpu.global.b128 v, [%4];\nmov.b128 {lo, hi}, v;\nmov.b64 {%0, %1}, lo;\nmov.b64 {%2, %3}, hi;\n}"
    : "=r"(v.x), "=r"(v.y), "=r"(v.z), "=r"(v.w) : "l"(p) : "memory");
  return v;
}
__device__ __forceinline__ void st_tag64(uint2* p, float a, uint32_t tag) {
  asm volatile("{\n.reg .b64 v;\nmov.b64 v, {%1, %2};\nst.relaxed.gpu.global.b64 [%0], v;\n}" :: "l"(p), "r"(__float_as_uint(a)), "r"(tag) : "memory");
}
__device__ __forceinline__ uint2 ld_tag64(const uint2* p) {
  uint2 v;
  asm volatile("{\n.reg .b64 v;\nld.relaxed.gpu.global.b64 v, [%2];\nmov.b64 {%0, %1}, v;\n}" : "=r"(v.x), "=r"(v.y) : "l"(p) : "memory");
  return v;
}
__device__ __forceinline__ uint32_t pack_bf16(float lo, float hi) { uint32_t r; asm("cvt.rn.bf16x2.f32 %0, %1, %2;" : "=r"(r) : "f"(hi), "f"(lo)); return r; }
__device__ __forceinline__ uint32_t relu_sq_bf16(float lo, float hi) {
  uint32_t r; asm("{\n.reg .b32 t;\ncvt.rn.relu.bf16x2.f32 t, %1, %2;\nmul.rn.bf16x2 %0, t, t;\n}" : "=r"(r) : "f"(hi), "f"(lo)); return r;
}
__device__ __forceinline__ float bf_lo(uint32_t u) { return __uint_as_float(u << 16); }
__device__ __forceinline__ float bf_hi(uint32_t u) { return __uint_as_float(u & 0xffff0000u); }
__device__ __forceinline__ void stmatrix4(uint32_t addr, uint32_t r0, uint32_t r1, uint32_t r2, uint32_t r3) {
  asm volatile("stmatrix.sync.aligned.m8n8.x4.shared.b16 [%0], {%1, %2, %3, %4};" :: "r"(addr), "r"(r0), "r"(r1), "r"(r2), "r"(r3) : "memory");
}
__device__ __forceinline__ void ldmatrix4(uint32_t addr, uint32_t (&r)[4]) {
  asm volatile("ldmatrix.sync.aligned.m8n8.x4.shared.b16 {%0, %1, %2, %3}, [%4];" : "=r"(r[0]), "=r"(r[1]), "=r"(r[2]), "=r"(r[3]) : "r"(addr) : "memory");
}
__device__ __forceinline__ void stmatrix4_t(uint32_t addr, uint32_t r0, uint32_t r1, uint32_t r2, uint32_t r3) {
  asm volatile("stmatrix.sync.aligned.m8n8.x4.trans.shared.b16 [%0], {%1, %2, %3, %4};" :: "r"(addr), "r"(r0), "r"(r1), "r"(r2), "r"(r3) : "memory");
}
__device__ __forceinline__ void ldmatrix4_t(uint32_t addr, uint32_t (&r)[4]) {
  asm volatile("ldmatrix.sync.aligned.m8n8.x4.trans.shared.b16 {%0, %1, %2, %3}, [%4];" : "=r"(r[0]), "=r"(r[1]), "=r"(r[2]), "=r"(r[3]) : "r"(addr) : "memory");
}
__device__ __forceinline__ uint32_t movmatrix(uint32_t a) { uint32_t d; asm volatile("movmatrix.sync.aligned.m8n8.trans.b16 %0, %1;" : "=r"(d) : "r"(a)); return d; }
__device__ __forceinline__ void mma16816_z(float (&c)[4], uint32_t a0, uint32_t a1, uint32_t a2, uint32_t a3, uint32_t b0, uint32_t b1, const float4& z) {
  asm volatile("mma.sync.aligned.m16n8k16.row.col.f32.bf16.bf16.f32 {%0,%1,%2,%3}, {%4,%5,%6,%7}, {%8,%9}, {%10,%11,%12,%13};"
    : "=f"(c[0]), "=f"(c[1]), "=f"(c[2]), "=f"(c[3]) : "r"(a0), "r"(a1), "r"(a2), "r"(a3), "r"(b0), "r"(b1), "f"(z.x), "f"(z.y), "f"(z.z), "f"(z.w));
}
__device__ __forceinline__ float ex2(float x) { float y; asm("ex2.approx.ftz.f32 %0, %1;" : "=f"(y) : "f"(x)); return y; }
__device__ __forceinline__ float rcp(float x) { float y; asm("rcp.approx.ftz.f32 %0, %1;" : "=f"(y) : "f"(x)); return y; }
__device__ __forceinline__ void mma16816(float (&c)[4], uint32_t a0, uint32_t a1, uint32_t a2, uint32_t a3, uint32_t b0, uint32_t b1) {
  asm volatile("mma.sync.aligned.m16n8k16.row.col.f32.bf16.bf16.f32 {%0,%1,%2,%3}, {%4,%5,%6,%7}, {%8,%9}, {%0,%1,%2,%3};"
    : "+f"(c[0]), "+f"(c[1]), "+f"(c[2]), "+f"(c[3]) : "r"(a0), "r"(a1), "r"(a2), "r"(a3), "r"(b0), "r"(b1));
}
__device__ __forceinline__ void sts128(uint32_t a, uint32_t x, uint32_t y, uint32_t z, uint32_t w) { asm volatile("st.shared.v4.b32 [%0], {%1,%2,%3,%4};" :: "r"(a), "r"(x), "r"(y), "r"(z), "r"(w) : "memory"); }
__device__ __forceinline__ float2 lds64f(uint32_t a) { float2 v; asm volatile("ld.shared.v2.f32 {%0,%1}, [%2];" : "=f"(v.x), "=f"(v.y) : "r"(a) : "memory"); return v; }
__device__ __forceinline__ float4 lds128f(uint32_t a) { float4 v; asm volatile("ld.shared.v4.f32 {%0,%1,%2,%3}, [%4];" : "=f"(v.x), "=f"(v.y), "=f"(v.z), "=f"(v.w) : "r"(a) : "memory"); return v; }
__device__ __forceinline__ void sts32f(uint32_t a, float v) { asm volatile("st.shared.f32 [%0], %1;" :: "r"(a), "f"(v) : "memory"); }
__device__ __forceinline__ void sts64f(uint32_t a, float x, float y) { asm volatile("st.shared.v2.f32 [%0], {%1,%2};" :: "r"(a), "f"(x), "f"(y) : "memory"); }
__device__ __forceinline__ uint32_t lds32(uint32_t a) { uint32_t v; asm volatile("ld.shared.u32 %0, [%1];" : "=r"(v) : "r"(a) : "memory"); return v; }
__device__ __forceinline__ float after(float x, uint32_t d, uint32_t zero) { return __uint_as_float(__float_as_uint(x) | (d & zero)); }
template<int R> __device__ __forceinline__ void reg_alloc() { asm volatile("setmaxnreg.inc.sync.aligned.u32 %0;" :: "n"(R)); }
template<int R> __device__ __forceinline__ void reg_dealloc() { asm volatile("setmaxnreg.dec.sync.aligned.u32 %0;" :: "n"(R)); }

struct Ctx {
  uint32_t sb;
  int m, j, b, rank, wg, w, lane;
};

__device__ __forceinline__ unsigned smem_tag(const Ctx& c) { return lds32(c.sb + OFF_TAG); }
__device__ __forceinline__ int smem_block(const Ctx& c) { return lds32(c.sb + OFF_TAG + 8); }

struct WTile { int map, c0, c2; };
__host__ __device__ constexpr WTile wtile(int type, int j) {
  return WTile{128 * (type < 2 ? 5 : type < 5 ? type + 4 : type + 3), type < 2 ? (j + 8 * type) * 64 : 0,
               type < 2 ? 0 : type == 3 ? 3 * j : type == 4 ? 24 + 2 * j : type == 5 ? 40 + 2 * j : 2 * j};
}
__host__ __device__ constexpr int first_stage(int type, int part) { return ((part == 0 ? 0x2000422 : part == 1 ? 0x2 : 0x2002) >> (4 * type)) & 7; }

enum { A_NEW = 1 << 9, A_QUIET = 1 << 10, A_NONE = 1 << 11, A_PAIR = 2 << 11, A_COPY = 3 << 11 };
struct Plan {
  unsigned epoch[256];
  uint32_t v[8][PLAN_BYTES / 4];
};
constexpr Plan make_plan() {
  Plan plan{};
  for (int j = 0; j < 8; j++)
    for (int g = 4; g < 2 * KB_LAYER; g++) {
      const int layer = g >= KB_LAYER, r = g - layer * KB_LAYER;
      const bool split = (r >= 48 && r < 80) || (layer && r < 32);
      const int q = r - (r >= 48 ? 48 : 0);
      const bool head = split && q < 4, second = split && (head ? q >= 2 : q >= 18), lead = split && !second;
      const int type = split ? (r >= 48 ? 3 : 0) + second : r < 96 ? r >> 4 : 6, t = layer * 7 + type;
      const int step = !split ? r - 16 * type : head ? q & 1 : q - (second ? 16 : 2), n = step - (split && !head ? 2 : 0);
      const bool wide = type < 2 || type == 3;
      const int ns = wide || head ? 4 : 5, lag = type == 2 ? 3 : 4;
      const int e = g - (split && q && q < (r < 48 ? 4 : 6) ? 5 + (r >= 48 && q > 1) : n + 1 > ns ? ns : n + 1 > lag ? n + 1 : lag);
      const int v = (int)(0xfb7d95ea6c842310ull >> (4 * (step & 15))) & 15;
      const int kb = split ? (v < 4 ? (j * 2) ^ v : ((j >> 1) * 4 + v) & 15) : type != 2 || step < 8 ? step : step < 10 ? j ^ step : 8 + (((j & 6) + step) & 7);
      const uint32_t x = kb * 64 + (first_stage(type, head ? 1 : 2 * split) + n) % ns * (163840 / ns);
      const bool local = type == 2 && (step >> 1) == 4;
      const int act = split && step < 4 ? (head || lead ? A_NONE : A_PAIR) : local ? (step == 8 ? A_NONE : A_COPY) : 0;
      const uint32_t piece = type == 6 ? (step < 24 ? step / 3 : (step >> 1) - 4) : (type == 2 ? !local : lead ? step >= 4 : second && step == 2) ? kb : 31;
      const int ea = split && act == A_NONE ? g - 8 - (step == 3) : e;
      const WTile w = wtile(type, j);
      uint32_t* d = plan.v[j] + (g - 4) * 4;
      d[0] = x + ((ea >> 3) & 1) + (ea & 7) * 8 + (act ? 0 : (j & 1) * 8192) + (piece << 27);
      d[1] = (!head ? A_BYTES : lead ? 4 : 0) + (type == 2 || type == 6 ? 256 : t < 2 ? 0 : 128) + act + (n == 0 && !second ? A_NEW : 0) +
             (local && step == 8 ? A_QUIET : 0) + ((uint32_t)(t - second) << 27);
      d[2] = x + ((e >> 3) & 1) + (e & 7) * 8 + (!head || !type ? A_BYTES : wide ? 0 : 24576) + ((uint32_t)w.c2 << 26);
      d[3] = w.c0 + (wide ? 24576 : 16384) + (w.map << 16);
    }
  return plan;
}
__device__ __align__(128) Plan g_plan = make_plan();

template<int NL>
__device__ __forceinline__ void row_stats(const Ctx& c, int t) {
  const int ln = t / 3;
  const unsigned tag = smem_tag(c);
  const int row = c.w * 32 + c.lane + lds32(c.sb + OFF_ZERO);
  float s = 0.f, q = 0.f;
  const uint32_t xr = c.sb + OFF_X + row * 128 + (row & 7) * 16;
#pragma unroll 1
  for (int i = 0; i < 128; i += 16) {
    const float4 v = lds128f(xr ^ i), w = lds128f((xr ^ i) + A_BYTES);
    const float u[8] = {v.x, v.y, v.z, v.w, w.x, w.y, w.z, w.w};
#pragma unroll
    for (int z = 0; z < 16; z++) { const float x = z & 1 ? bf_hi(__float_as_uint(u[z >> 1])) : bf_lo(__float_as_uint(u[z >> 1])); s += x; q = fmaf(x, x, q); }
  }
  if (NL == 8) TL(-1, 6);
  if (NL == 4) mbar_pace(c.sb + OFF_FULL + 8 * SA, ln >> 1);
  const int b = smem_block(c);
  st_tag128(g_stats + (ln * 128 + b) * 128 + row, __float_as_uint(s), __float_as_uint(q), 0u, tag);
  mbar_pace(c.sb + (NL == 4 ? OFF_FULL + 8 * (SB & 7) : OFF_EMPTY + 16), (ln >> 1) ^ 1);
  const uint4* p = g_stats + (ln * 128 + (b & ~7)) * 128 + row;
  for (unsigned it = 0;; it++) {
    bool ok = true;
    s = 0.f; q = 0.f;
#pragma unroll 1
    for (int h = 0; h < 8; h += NL) {
      uint4 v[NL];
#pragma unroll
      for (int i = 0; i < NL; i++) v[i] = ld_tag128(p + (h + i) * 128);
#pragma unroll
      for (int i = 0; i < NL; i++) { ok = ok && v[i].w == tag; s += __uint_as_float(v[i].x); q += __uint_as_float(v[i].y); }
    }
    if (__all_sync(0xffffffffu, ok) || it > SPIN_LIMIT) break;
    __nanosleep(NL == 4 ? 400 : 100);
  }
  const float mean = s * (1.0f / D_);
  const float var = fmaxf(q * (1.0f / D_) - mean * mean, 0.0f);
  sts64f(c.sb + OFF_RST + row * 8, rsqrtf(var + 1e-5f), -mean);
  if ((EXP & 256) && NL == 8) sts32f(c.sb + OFF_TAG + 12, __int_as_float(row + 77));
  if ((EXP & 512) && NL == 4) sts32f(c.sb + OFF_TAG + 12, __int_as_float(row + 77));
  bar_arrive(BAR_EPI + (c.wg ^ 1), 256);
  TL(t - 2, 5);
}

__device__ __forceinline__ uint32_t res_addr(const Ctx& c) {
  return c.sb + OFF_X + ((c.lane >> 4) * 8 + (c.lane & 7)) * 128 + (((2 * c.w + ((c.lane >> 3) & 1)) ^ (c.lane & 7)) << 4);
}

template<int BN, int RES>
__device__ __forceinline__ void mainloop(const Ctx& c, float (&acc)[2][96], int t, int type, int g, int nkb) {
  constexpr int NS = BN == 192 ? 4 : 5, STR = BN == 192 ? 40960 : 32768;
  const bool split = !RES && (BN == 192 ? t > 1 : type == 4), second = BN == 128 || type == 1;
  int st = first_stage(type, split);
  if (split && second) g -= 14;
  const uint32_t rel = mapa(c.sb + OFF_EMPTY, c.lane & 1);
  const uint32_t sb = (c.sb & 0x3ffffu) >> 4;
  const uint32_t hb = BN == 192 && split && type ? 1024 : 0;
  uint32_t da = DESC_A + sb + (split ? OFF_X / 16 : st * (STR / 16)), db = DESC_B + sb + (BN == 128 && split ? 512 : st * (STR / 16) - hb);
  TL(t, 0);
  bar_sync(BAR_START + c.wg, 256);
  if (RES && type == 2) bar_sync(BAR_P1, 256);
  TL(t, 1);
  mbar_wait(c.sb + OFF_FULL + 8 * (g & 7), (g >> 3) & 1);
  TL(t, 2);
  wgmma_fence();
#define MMA(i, k, keep) wgmma_ss<BN, RES ? 2 : keep>(acc[i], da + (k) * 2 + (RES ? 0 : 64 * (i)), db + (k) * 128 + (RES ? 512 * (i) : 0))
  MMA(0, 0, 0); MMA(1, 0, 0); MMA(0, 1, 1); MMA(1, 1, 1);
  wgmma_commit();
  wgmma_fence();
  MMA(0, 2, 1); MMA(1, 2, 1); MMA(0, 3, 1); MMA(1, 3, 1);
  wgmma_commit();
  const int pause = BN == 192 && type == 1 ? (split ? PAUSE2 : PAUSE1) : nkb;
  int kb = 1, lim = split ? 2 : pause, pass = split ? 2 : !RES && type != 1 ? nkb : 0;
  const uint32_t other = BAR_START + (c.wg ^ 1);
  uint32_t prev = 8 * (g & 7);
  if (++st == NS) st = 0;
  g++;
  da = DESC_A + sb + (split ? (OFF_X + A_BYTES) / 16 : st * (STR / 16));
  db = DESC_B + sb + (BN == 128 && split ? 3072 : st * (STR / 16) - hb);
#pragma unroll 1
  for (;;) {
    mbar_wait(c.sb + OFF_FULL + 8 * (g & 7), (g >> 3) & 1);
    bool more;
#pragma unroll 1
    do {
      wgmma_fence();
      MMA(0, 0, 1); MMA(1, 0, 1); MMA(0, 1, 1); MMA(1, 1, 1);
      wgmma_commit();
      wgmma_wait<1>();
      if (c.lane < 2) mbar_arrive_cluster(rel + prev);
      TK(t, kb);
      prev = 8 * (g & 7);
      kb++; g++;
      if (++st == NS) st = 0;
      wgmma_fence();
      if (BN == 128 && !RES && kb == pass) bar_arrive(other, 256);
      MMA(0, 2, 1); MMA(1, 2, 1);
      if (BN == 192 && kb == pass) bar_arrive(other, 256);
      const uint32_t ok = mbar_test(c.sb + OFF_FULL + 8 * (g & 7), (g >> 3) & 1);
      MMA(0, 3, 1); MMA(1, 3, 1);
      wgmma_commit();
      more = ok && kb != lim;
      da = DESC_A + sb + (RES && type == 2 && kb == 8 ? OFF_STG / 16 : st * (STR / 16));
      db = DESC_B + sb + st * (STR / 16);
    } while (more);
    if (kb != lim) continue;
    if (RES || kb == nkb) break;
    if (BN == 128 || kb == 2) {
      wgmma_wait<0>();
      if (c.lane < 2) mbar_arrive_cluster(rel + prev);
      TK(t, 16);
      if (second) row_stats<4>(c, t);
      g += second ? 14 : 2;
      st = first_stage(type, 2);
      da = DESC_A + sb + st * (STR / 16); db = DESC_B + sb + st * (STR / 16);
      lim = pause; pass = type != 1 ? nkb : 0; prev = OFF_IDLE - OFF_EMPTY;
      bar_sync(BAR_START + c.wg, 256);
    } else {
      bar_sync(BAR_P0, 256); bar_sync(BAR_P1, 256);
      lim = kb == pause ? pause + 2 : nkb;
    }
  }
  if (!RES) return;
#define PAIR(i, n) wgmma_ss<128, 2>(acc[i], da + ((n) >> 2) * 2048 + ((n) & 3) * 2, db + ((n) >> 2) * 2048 + ((n) & 3) * 128 + 512 * (i))
#define PUT(z) do { const float* a = acc[(z) >> 3] + ((z) & 7) * 8; \
    stmatrix4_t(xw + (z) * 2048, pack_bf16(a[0], a[1]), pack_bf16(a[2], a[3]), pack_bf16(a[4], a[5]), pack_bf16(a[6], a[7])); } while (0)
  const uint32_t xw = res_addr(c);
  const int nrel = t == 13 ? 0 : 2;
  if (t == 13) asm volatile("barrier.cluster.arrive.relaxed.aligned;" ::: "memory");
#pragma unroll
  for (int n = 0; n < 4 * SK; n++) {
    if (!(n & 3)) { mbar_wait(c.sb + OFF_FULL + 8 * (8 - SK + n / 4), (g >> 3) & 1); wgmma_fence(); }
    PAIR(0, n);
    if (n == 3) { wgmma_commit(); wgmma_wait<1>(); if (c.lane < nrel) mbar_arrive_cluster(rel + prev); wgmma_fence(); }
  }
  wgmma_commit();
#pragma unroll
  for (int n = 0; n < 4 * SK; n++) {
    if (n == 4 * SK - 2 && t < 13) bar_arrive(other, 256);
    PAIR(1, n);
    wgmma_commit();
#pragma unroll
    for (int z = 0; z < 8; z++) if (z / 4 + 2 == n) PUT(z);
    if (n == 3) bar_arrive(BAR_RES, 160);
    if (n && n < 4 * SK - 1) wgmma_wait<2>();
    if (n > 4 && (n & 3) == 1 && c.lane < nrel) mbar_arrive_cluster(rel + 8 * (7 - SK + n / 4));
  }
  wgmma_wait<0>();
  if (c.lane < nrel) mbar_arrive_cluster(rel + 56);
  TL(t, 3);
#pragma unroll
  for (int nt = 8; nt < 16; nt++) {
    PUT(nt);
    if ((nt & 3) == 3 && t == 13) bar_arrive(nt == 11 ? BAR_START : BAR_EPI, 256);
    if ((nt & 3) == 1 && t == 13) bar_arrive(nt == 9 ? BAR_P0 : BAR_P1, 256);
  }
  if (t == 13) return;
  fence_async_smem();
  __syncwarp();
  asm volatile(ELECT "@p mbarrier.complete_tx.relaxed.cta.shared::cta.b64 [%0], 1;\n}" :: "r"(c.sb + OFF_FULL + 8) : "memory");
  bar_arrive(BAR_RES2, 160);
#undef MMA
#undef PAIR
#undef PUT
}
__device__ __forceinline__ void release(const Ctx& c, int slot, int lanes = 2) {
  if (c.lane < lanes) mbar_arrive_cluster(mapa(c.sb + OFF_EMPTY, c.lane & 1) + 8 * slot);
}
__device__ __forceinline__ void finish(const Ctx& c, int t, int slot) {
  wgmma_wait<0>();
  release(c, slot);
  TL(t, 3);
}

__device__ __forceinline__ void put_halo(uint32_t addr, bool last, uint32_t a, uint32_t b, uint32_t c, uint32_t d) {
  if (!last) stmatrix4(addr, a, b, c, d);
  else asm volatile("stmatrix.sync.aligned.m8n8.x2.shared.b16 [%0], {%1, %2};\nstmatrix.sync.aligned.m8n8.x1.shared.b16 [%0 + 256], {%3};" :: "r"(addr), "r"(a), "r"(b), "r"(c) : "memory");
}

__device__ __forceinline__ void fetch_halo(const Ctx& c, unsigned tag, int tile) {
  const int v = c.w & 1;
  const uint4* src = g_halo + (tile * 128 + c.b - 8) * 352 + v * 160 + c.lane;
  uint4 G[6];
#pragma unroll
  for (int z = 0; z < 6; z++) G[z] = make_uint4(0u, 0u, 0u, 0u);
  bar_sync(BAR_HGO + v, 64);
  for (unsigned it = 0; c.m > 0; it++) {
    bool ok = true;
    if (it && !(tile & 1)) __nanosleep(200);
#pragma unroll
    for (int z = 0; z < 6; z++) { G[z] = ld_tag128(src + z * 32); ok = ok && G[z].w == tag; }
    if (__all_sync(0xffffffffu, ok) || it > SPIN_LIMIT) break;
  }
#pragma unroll
  for (int z = 0; z < 6; z++) put_halo(c.sb + OFF_STG + c.lane * 16 + (z ? (v * 5 + z) * 384 - 128 : v * 1792), z == 5, G[z].x, G[z].y, G[z].z, G[z].w);
  if (!v) sts32f(c.sb + OFF_RST - 256 + c.lane * 8, __uint_as_float(G[0].z));
  __syncwarp();
  mbar_arrive_e(c.sb + OFF_HALO + 8 * v);
}

template<int SKEW>
__device__ __forceinline__ void conv_qkv(const Ctx& c, float (&acc)[2][96], uint32_t (&P)[3][2][4][4], int t) {
  const int lane = c.lane, w = c.w, g = lane >> 2, cc = lane & 3;
  const int layer = t >= 7;
  const uint32_t sb = (c.sb & 0x3ffffu) >> 4, par = layer ^ 1;
  uint32_t da = DESC_A + sb + 7680 + 64, db = DESC_B + sb + 7680;
#define MMA(i, n) if (SKEW) do { wgmma_ss<192, 1>(acc[i], da, db); \
    asm volatile("add.s32 %0, %0, %2;\nadd.s32 %1, %1, %3;" : "+r"(da), "+r"(db) : "r"((n) == 11 ? 5050 : (n) == 7 ? 2554 : (n) == 3 ? -7686 : 2), "r"((n) == 11 ? 4736 : (n) == 7 ? 2176 : (n) == 3 ? -8064 : 128)); } while (0)
  const uint32_t rst = c.sb + OFF_RST + w * 256, csb = c.sb + OFF_CSQ + SKEW * 768 + cc * 16, stg = c.sb + OFF_STG + w * 4096;
  float mu[4];
  uint32_t tag, rs_l;
  uint4* halo;
  bool send;
#define SETUP do { _Pragma("unroll") for (int r = 0; r < 4; r++) mu[r] = __uint_as_float(lds32(rst + (8 * r + g) * 8 + 4)); \
    tag = smem_tag(c); rs_l = lds32(rst + lane * 8); \
    const int b = smem_block(c); \
    halo = g_halo + ((layer * 2 + SKEW) * 128 + b) * 352 + lane; send = w == 3 && b < 120; \
    if (SKEW) asm volatile("" : "+l"(halo)); } while (0)
  if (SKEW) {
    mbar_wait(c.sb + OFF_FULL + 40, par);
    wgmma_fence();
    MMA(1, 0); MMA(1, 1); MMA(1, 2); MMA(1, 3);
    wgmma_commit();
    wgmma_wait<1>();
    release(c, 4);
    SETUP;
    mbar_wait(c.sb + OFF_FULL + 48, par);
  } else finish(c, t, layer ? 1 : 7);
  MMA(1, 4); MMA(1, 5);
  bar_sync(BAR_EPI + c.wg, 256);
  MMA(1, 6);
  mbar_wait(c.sb + OFF_TBL + 8 * SKEW, 0);
  MMA(1, 7);
  if (SKEW) mbar_wait(c.sb + OFF_FULL + 56, par);
  MMA(1, 8);
  bar_sync(BAR_FREE, 160);
  MMA(1, 9);
  if (!SKEW) SETUP;
  float4 cs = lds128f(csb + 4 * 64);
  if (SKEW) {
    MMA(1, 10); MMA(1, 11);
    wgmma_commit();
    MMA(0, 0);
    wgmma_commit();
    MMA(0, 1);
    wgmma_commit();
    wgmma_wait<2>();
  }
#define CONV(i, np) do { _Pragma("unroll") for (int z = 0; z < 4; z++) { const int nt = 2 * (np) + (z >> 1), h = z & 1; \
    const float m = mu[2 * h + (i)]; \
    P[nt >> 3][(nt >> 2) & 1][2 * h + (i)][nt & 3] = pack_bf16(fmaf(z >> 1 ? cs.z : cs.x, m, acc[i][4 * nt + 2 * h]), \
                                                                     fmaf(z >> 1 ? cs.w : cs.y, m, acc[i][4 * nt + 2 * h + 1])); } } while (0)
#define HM(u) P[1 + (((u) >> 4) & 1)][((u) >> 3) & 1][((u) & 2) + 1][(((u) >> 1) & 2) + ((u) & 1)]
#define HW(u) ((u) == 2 ? rs_l : HM((u) - ((u) > 2)))
#pragma unroll
  for (int n = 0; n < 12; n++) {
    const int np = (n + 4) % 12;
    if (SKEW && n == HGK && w == 0) bar_arrive(BAR_HGO, 64);
    if (SKEW && n == HGO && w == 0) bar_arrive(BAR_HGO + 1, 64);
    if (SKEW && n == 8) bar_arrive(BAR_START + (c.wg ^ 1), 256);
    if (SKEW && n < 10) { MMA(0, n + 2); wgmma_commit(); }
    CONV(1, np);
    cs = lds128f(csb + (n < 11 ? (n + 5) % 12 : 0) * 64);
#pragma unroll
    for (int z = 0; z < 11; z++)
      if ((3 * z + 1) / 4 == n) {
        st_tag128_if(send, halo + z * 32, HW(3 * z), HW(3 * z + 1), HW(3 * z + 2), tag);
        put_halo(stg + 4096 + lane * 16 + (z ? z * 384 - 128 : 0), z == 10, HW(3 * z), HW(3 * z + 1), HW(3 * z + 2), tag);
      }
    if (SKEW && n < 10) wgmma_wait<2>();
    if (SKEW && (n == 3 || n == 7)) release(c, 5 + (n >> 2));
  }
#undef MMA
#undef HW
#undef SETUP
#undef HM
  if (SKEW) {
    wgmma_wait<0>();
    release(c, 7, w ? 2 : 0);
    TL(t, 3);
  }
#pragma unroll
  for (int np = 0; np < 12; np++) {
    CONV(0, np);
    if (!SKEW && np == HG1 && w == 0) { bar_arrive(BAR_HGO, 64); bar_arrive(BAR_HGO + 1, 64); }
    if (np < 11) cs = lds128f(csb + (np + 1) * 64);
  }
#undef CONV
}

__device__ __forceinline__ void epi_qkv(const Ctx& c, float (&acc)[2][96], int t, int q) {
  const int lane = c.lane, w = c.w, g = lane >> 2, cc = lane & 3;
  uint32_t P[3][2][4][4];
  if (q) conv_qkv<1>(c, acc, P, t); else conv_qkv<0>(c, acc, P, t);
  const uint32_t rst = c.sb + OFF_RST + w * 256, stg = c.sb + OFF_STG + w * 4096;
  const bool nohalo = w == 0 && smem_block(c) < 8;
#pragma unroll
  for (int z = 0; z < 16; z++) P[2][z >> 3][(z >> 1) & 2][z & 3] = movmatrix(P[2][z >> 3][(z >> 1) & 2][z & 3]);
  uint32_t K1[4][4], V1[4][4];
  const uint32_t hl = stg + (lane & 15) * 16 + (lane >> 4) * 512;
#define HZ(z) (((z) >> 1) * 1024 + ((z) & 1) * 256)
  __syncwarp();
#pragma unroll
  for (int z = 0; z < 4; z++) { ldmatrix4(hl + 4096 + HZ(z), K1[z]); ldmatrix4_t(hl + 4096 + 2048 + HZ(z), V1[z]); }
  TL(t, 9);
  bar_sync(BAR_WG + c.wg, 128);
  if (w == 0) { TL(t, 8); mbar_wait(c.sb + OFF_HALO, q); release(c, 7, 2 * q); }
  uint32_t HK[4][4], HV[4][4];
#pragma unroll
  for (int z = 0; z < 4; z++) ldmatrix4(hl + HZ(z), HK[z]);
  const bool far0 = 2 * cc > g, far1 = 2 * cc + 1 > g;
  float rk[4][2], sc[4][2];
#pragma unroll
  for (int r = 0; r < 4; r++) {
    const float rq = __uint_as_float(lds32(rst + (8 * r + g) * 8)) * (0.17677669529663687f * 1.4426950408889634f);
    const int back = r & 1 ? 64 : 192;
    rk[r][0] = __uint_as_float(lds32(rst + r * 64 + cc * 16 - (far0 ? back : 0)));
    rk[r][1] = __uint_as_float(lds32(rst + r * 64 + cc * 16 + 8 - (far1 ? back : 0)));
    sc[r][0] = rq * rk[r][0]; sc[r][1] = rq * rk[r][1];
  }
  TL(t, 4);
  float S[4][3][4];
  if (q == 0) bar_sync(BAR_P0, 256);
  float4 zero = lds128f(c.sb + OFF_ZERO);
#pragma unroll
  for (int k = 0; k < 2; k++)
#pragma unroll
    for (int z = 0; z < 4; z++) {
      const uint32_t* qa = P[0][z >> 1][2 * (z & 1)]; const uint32_t* qb = P[0][z >> 1][2 * (z & 1) + 1];
      const uint32_t* kk[3] = {HK[z], P[1][z >> 1][2 * (z & 1)], K1[z]};
#pragma unroll
      for (int n = 0; n < 3; n++) {
        if (k == 0) mma16816_z(S[z][n], qa[0], qb[0], qa[1], qb[1], kk[n][0], kk[n][1], zero);
        else mma16816(S[z][n], qa[2], qb[2], qa[3], qb[3], kk[n][2], kk[n][3]);
        if (q == 0 && k * 12 + z * 3 + n + 1 == NS) bar_arrive_here(BAR_P1, S[0][0][0], zero.x);
      }
    }
  TL(t, 10);
  const uint32_t fmask = (far0 ? 0xffffu : 0u) | (far1 ? 0xffff0000u : 0u);
  uint32_t pf[4][2], pn[4][2];
#pragma unroll
  for (int z = 0; z < 4; z++)
#pragma unroll
    for (int i = 0; i < 2; i++) {
      const int r = 2 * (z & 1) + i;
      float l0 = (far0 ? S[z][i][2 * i] : S[z][i + 1][2 * i]) * sc[r][0];
      float l1 = (far1 ? S[z][i][2 * i + 1] : S[z][i + 1][2 * i + 1]) * sc[r][1];
      if (i == 0 && nohalo) { const float neg = -1e9f * 1.4426950408889634f; if (far0) l0 = neg; if (far1) l1 = neg; }
      float mx = fmaxf(l0, l1);
      mx = fmaxf(mx, __shfl_xor_sync(0xffffffffu, mx, 1));
      mx = fmaxf(mx, __shfl_xor_sync(0xffffffffu, mx, 2));
      l0 = ex2(l0 - mx); l1 = ex2(l1 - mx);
      float sum = l0 + l1;
      l0 *= rk[r][0]; l1 *= rk[r][1];
      sum += __shfl_xor_sync(0xffffffffu, sum, 1);
      sum += __shfl_xor_sync(0xffffffffu, sum, 2);
      sum = rcp(sum);
      const uint32_t u = pack_bf16(l0 * sum, l1 * sum);
      pf[z][i] = u & fmask; pn[z][i] = u & ~fmask;
    }
  float O[4][2][2][4];
  TL(t, 11);
  if (w == 0) { mbar_wait(c.sb + OFF_HALO + 8, q); TL(t, 12); }
#pragma unroll
  for (int z = 0; z < 4; z++) ldmatrix4_t(hl + 2048 + HZ(z), HV[z]);
#undef HZ
  if (q == 0) bar_sync_after(BAR_P0, (pn[0][0] | pn[0][1] | pn[1][0]) | (pn[1][1] | pn[2][0] | pn[2][1]) | (pn[3][0] | pn[3][1]));
  zero = lds128f(c.sb + OFF_ZERO);
#pragma unroll
  for (int z = 0; z < 4; z++)
#pragma unroll
    for (int d = 0; d < 2; d++) {
      const uint32_t* v0 = P[2][z >> 1][2 * (z & 1)] + 2 * d;
      mma16816_z(O[z][0][d], HV[z][2 * d], HV[z][2 * d + 1], v0[0], v0[1], pf[z][0], pn[z][0], zero);
      mma16816_z(O[z][1][d], v0[0], v0[1], V1[z][2 * d], V1[z][2 * d + 1], pf[z][1], pn[z][1], zero);
      if (z * 4 + d * 2 + 2 == NP) bar_arrive_here(BAR_P1, O[0][0][0][0], zero.x);
    }
  TL(t, 5);
#pragma unroll
  for (int nt = 0; nt < 8; nt++) {
    uint32_t u[4];
#pragma unroll
    for (int r = 0; r < 4; r++) { const float* o = O[2 * (nt >> 2) + (r >> 1)][r & 1][(nt >> 1) & 1] + 2 * (nt & 1); u[r] = pack_bf16(o[0], o[1]); }
    stmatrix4_t(stg + lane * 128 + ((nt ^ (lane & 7)) << 4), u[0], u[1], u[2], u[3]);
  }
  bar_arrive(BAR_READY, 160);
  TL(t, 13);
}

template<int CH>
__device__ __forceinline__ void epi_up(const Ctx& c, float (&acc)[2][96], int type) {
  const int lane = c.lane, w = c.w, g = lane >> 2, cc = lane & 3;
  float rs[4], nm[4];
#pragma unroll
  for (int r = 0; r < 4; r++) { const float2 v = lds64f(c.sb + OFF_RST + (w * 32 + 8 * r + g) * 8); rs[r] = v.x; nm[r] = v.x * v.y; }
  const int loc0 = type == 3 ? 0 : (type == 4 ? 192 : 320);
  const uint32_t cb = c.sb + OFF_UP + loc0 * 8 + cc * 16;
  const uint32_t zero = lds32(c.sb + OFF_ZERO);
  uint32_t d[2] = {0u, 0u};
  const uint32_t stg = c.sb + OFF_STG + w * 4096;
#pragma unroll
  for (int ch = CH; ch < (CH ? 3 : 2); ch++) {
    uint32_t P[8][4];
#pragma unroll
    for (int n8 = 0; n8 < 8; n8++) {
      const int nt = ch * 8 + n8;
      const float4 cv = lds128f(cb + nt * 64);
#pragma unroll
      for (int r = 0; r < 4; r++) {
        const float m = after(nm[r], d[r & 1], zero);
        d[r & 1] = P[n8][r] = relu_sq_bf16(fmaf(acc[r & 1][4 * nt + 2 * (r >> 1)], rs[r], fmaf(cv.x, m, cv.z)),
                                           fmaf(acc[r & 1][4 * nt + 2 * (r >> 1) + 1], rs[r], fmaf(cv.y, m, cv.w)));
      }
    }
    bar_sync(BAR_FREE, 160);
#pragma unroll
    for (int n8 = 0; n8 < 8; n8++)
      stmatrix4(stg + lane * 128 + ((n8 ^ (lane & 7)) << 4), P[n8][0], P[n8][1], P[n8][2], P[n8][3]);
    bar_arrive(BAR_READY, 160);
  }
}

__device__ __forceinline__ void init_res(const Ctx& c, float (&acc)[2][96], int t, bool bias) {
  if (t == 2) mbar_wait(c.sb + OFF_XBAR, 0);
  uint32_t xb = res_addr(c);
  const uint32_t zero = lds32(c.sb + OFF_ZERO);
  float b[4];
#pragma unroll
  for (int r = 0; r < 4; r++) b[r] = bias ? __uint_as_float(lds32(c.sb + OFF_B2 + (r >> 1) * 256 + c.w * 64 + (r & 1) * 32 + (c.lane >> 2) * 4)) : 0.f;
#pragma unroll
  for (int z = 0; z < 16; z++) {
    uint32_t u[4];
    asm volatile("{\n.reg .pred p;\nSTAY:\nldmatrix.sync.aligned.m8n8.x4.trans.shared.b16 {%0, %1, %2, %3}, [%4];\nsetp.lt.u32 p, %0, %5;\n@p bra.uni STAY;\n}"
      : "=r"(u[0]), "=r"(u[1]), "=r"(u[2]), "=r"(u[3]) : "r"(xb + z * 2048), "r"(zero) : "memory");
#pragma unroll
    for (int r = 0; r < 4; r++) {
      float* a = acc[z >> 3] + (z & 7) * 8 + 2 * r;
      a[0] = bf_lo(u[r]) + b[(z >> 3) * 2 + (r & 1)];
      a[1] = bf_hi(u[r]) + b[(z >> 3) * 2 + (r & 1)];
      asm volatile("" : "+f"(a[0]), "+f"(a[1]));
    }
  }
}

__device__ __forceinline__ void load_table(const Ctx& c, const Params& p, int part, unsigned tag) {
  const int i0 = (part < 4 ? part * 192 : 704) + c.lane, n = part < 3 ? 6 : 4;
  const uint2* src = g_cs + c.j * NCS + i0;
  const uint32_t dst = c.sb + OFF_CSQ + (i0 & 1) * 4 + (part < 2 ? (i0 >> 4) * 64 + (i0 & 6) * 8 + (i0 & 8) : 1536 + ((i0 - 384) >> 1) * 16);
  const __nv_bfloat16* bias = p.b1 + (part == 2 ? c.j * 192 : (part == 3 ? 1536 : 2560) + c.j * 128) + c.lane;
  float v[6];
  if (part >= 2) {
#pragma unroll
    for (int k = 0; k < 6; k++) if (k < n) sts32f(dst + k * 256 + 8, __bfloat162float(bias[k * 32]));
  }
  for (unsigned it = 0;; it++) {
    bool ok = true;
#pragma unroll
    for (int k = 0; k < 6; k++) { const uint2 a = ld_tag64(src + (k < n ? k * 32 : 0)); ok = ok && a.y == tag; v[k] = __uint_as_float(a.x); }
    if (__all_sync(0xffffffffu, ok) || it > SPIN_LIMIT) break;
    __nanosleep(200);
  }
#pragma unroll
  for (int k = 0; k < 6; k++) if (k < n) sts32f(dst + k * (part < 2 ? 128 : 256), v[k]);
  __syncwarp();
}

__device__ __forceinline__ void colsum_cta(const Ctx& c, const Params& p, unsigned* epoch) {
  if (c.wg < 2) mbar_init_e(c.sb + OFF_FULL + 32 * c.wg + 8 * c.w, 1);
  sts32f(c.sb + OFF_STG + threadIdx.x * 4, __uint_as_float(0x3f803f80u));
  fence_async_smem();
  __syncthreads();
  if (c.wg == 2) return;
  const unsigned tag = *(volatile unsigned*)epoch + 1;
  const int j = (blockIdx.x - 128) * 2 + c.wg;
  const uint32_t ring = c.sb + c.wg * 98304, full = c.sb + OFF_FULL + 32 * c.wg;
  const uint64_t ones = (uint64_t)(((c.sb + OFF_STG) & 0x3ffffu) >> 4) | (8u << 16) | ((uint64_t)16u << 32);
  float d[3][4];
#pragma unroll 1
  for (int n = -4; n < 80; n++) {
    if (n >= 0) {
      mbar_wait(full + 8 * (n & 3), (n >> 2) & 1);
      const uint64_t da = (uint64_t)(((ring + (n & 3) * 24576) & 0x3ffffu) >> 4) | (64u << 16) | ((uint64_t)(64u | (1u << 30)) << 32);
      wgmma_fence();
#pragma unroll
      for (int k = 0; k < 4; k++)
#pragma unroll
        for (int z = 0; z < 3; z++)
          asm volatile("{\n.reg .pred p;\nsetp.ne.b32 p, %6, 0;\nwgmma.mma_async.sync.aligned.m64n8k16.f32.bf16.bf16 {%0,%1,%2,%3}, %4, %5, p, 1, 1, 1, 0;\n}"
            : "+f"(d[z][0]), "+f"(d[z][1]), "+f"(d[z][2]), "+f"(d[z][3]) : "l"(da + z * 512 + k * 128), "l"(ones), "r"((n & 15) | k));
      wgmma_commit();
      wgmma_wait<0>();
      bar_sync(BAR_WG + c.wg, 128);
      if ((n & 15) == 15 && (c.lane & 3) < 2) {
        const int u = n >> 4;
        uint2* out = g_cs + j * NCS + (u < 4 ? u * 192 : 704) + c.w * 16 + (c.lane >> 2) + (c.lane & 1) * 8;
#pragma unroll
        for (int z = 0; z < 3; z++) if (z < 2 || u < 3) st_tag64(out + z * 64, (c.lane & 1) ? d[z][2] : d[z][0], tag);
      }
      __syncwarp();
    }
    if (c.w == 0 && n < 76) {
      const int u = (n + 4) >> 4;
      const WTile w = wtile(u + (u >= 2), j);
      mbar_expect_e(full + 8 * (n & 3), u < 3 ? 24576 : 16384);
      tma_ld3_e(ring + (n & 3) * 24576, (const CUtensorMap*)((const char*)&p + w.map), full + 8 * (n & 3), w.c0, ((n + 4) & 15) * 64, w.c2);
    }
  }
  bar_sync(BAR_START, 256);
  if (threadIdx.x == 0) *epoch = tag;
}

__device__ __forceinline__ void place(Ctx& c, uint32_t slot) {
  const int row = slot < 32 ? slot >> 3 : slot < 60 ? ((slot - 4) * 37) >> 8 : slot - 56;
  const int gpc = slot < 60 ? slot - row * (slot < 32 ? 8 : 7) - (slot < 32 ? 0 : 3) : 0;
  c.m = (gpc & 1) * 8 + row;
  c.j = (gpc & 6) + c.rank; c.b = c.m * 8 + c.j;
}

__global__ void __cluster_dims__(2, 1, 1) __launch_bounds__(384, 1) fused_kernel(unsigned* const epochs, const char* const x0, const char* const w0, const __grid_constant__ Params p) {
  extern __shared__ uint8_t smem_raw[];
  const int tid = threadIdx.x;
  Ctx c;
  c.sb = (smem_u32(smem_raw) + 1023) & ~1023u;
  const int k = __shfl_sync(0xffffffffu, tid >> 5, 0);
  c.wg = k >> 2; c.w = k & 3; c.lane = tid & 31;
  c.rank = blockIdx.x & 1;
  if (blockIdx.x >= 128) { colsum_cta(c, p, epochs + blockIdx.x); return; }
  uint32_t slot; asm volatile("mov.u32 %0, %%smid;" : "=r"(slot));
  slot = __shfl_sync(0xffffffffu, slot < 120 ? slot >> 1 : 60 + ((slot >> 1) & 3), 0);
  if (c.wg == 2) {
    const bool claim = tid == 320 && c.rank == 0;
    unsigned epoch, old;
    asm volatile("{\n.reg .pred p;\nsetp.ne.u32 p, %4, 0;\nmov.u32 %0, 0;\nmov.u32 %1, 0;\n@p atom.relaxed.gpu.global.add.u32 %0, [%2], 1;\n@p ld.relaxed.gpu.global.u32 %1, [%3];\n}"
      : "=r"(old), "=r"(epoch) : "l"(epochs + 132 + slot + c.lane), "l"(epochs + blockIdx.x), "r"((uint32_t)claim) : "memory");
    reg_dealloc<40>();
#pragma unroll 1
    for (int pass = 0;; pass++) {
      place(c, slot);
      if (c.w == 1) {
        asm volatile(ELECT "@p mbarrier.init.shared::cta.b64 [%0], 2;\n@p mbarrier.init.shared::cta.b64 [%0 + 8], 2;\n"
          "@p mbarrier.init.shared::cta.b64 [%0 + 16], 2;\n@p mbarrier.init.shared::cta.b64 [%0 + 24], 2;\n}" :: "r"(c.sb + OFF_FULL) : "memory");
        fence_async_smem();
        if (!pass) asm volatile("fence.mbarrier_init.release.cluster;\nbarrier.cluster.arrive.relaxed.aligned;" ::: "memory");
#pragma unroll 1
        for (int s = pass ? 0 : 2; s < 4; s++) {
          const uint32_t full = c.sb + OFF_FULL + 8 * s, dst = c.sb + (s ^ 2) * 40960;
          mbar_expect_e(full, 40960);
          tma_ld4_e(dst, &p.ld_x, full, s * 64, c.m * 4);
          tma_ld4_e(dst + 8192, &p.ld_x, full, s * 64, c.m * 4 + 2);
          tma_ld3_e(dst + A_BYTES, &p.w_qkv, full, c.j * 64, s * 64, 0);
          mbar_arrive_e(full);
        }
      } else if (!pass) {
        if (c.w == 2) { mbar_init_e(c.sb + OFF_SLOT, 1); mbar_expect_e(c.sb + OFF_SLOT, 8); }
        asm volatile("fence.mbarrier_init.release.cluster;\nbarrier.cluster.arrive.relaxed.aligned;" ::: "memory");
      }
      if (c.w == 0) {
        asm volatile("cp.async.wait_all;" ::: "memory");
#pragma unroll
        for (int i = 0; i < PLAN_BYTES; i += 512)
          asm volatile("cp.async.cg.shared.global [%0], [%1], 16;" :: "r"(c.sb + OFF_PLAN + c.lane * 16 + i), "l"(epochs + 256 + c.j * (PLAN_BYTES / 4) + c.lane * 4 + i / 4) : "memory");
      }
      if (c.w == 3) sts32f(c.sb + OFF_TAG + 8, __int_as_float(c.b));
      if (pass) { bar_sync(BAR_START, 256); break; }
      asm volatile("barrier.cluster.wait.aligned;" ::: "memory");
      if (claim) {
        uint32_t s = slot;
        for (int it = 0; old != epoch && it < 64; it++) { atomicSub(epochs + 132 + s, 1u); s = (s + 1) & 63; old = atomicAdd(epochs + 132 + s, 1u); }
#pragma unroll
        for (int r = 0; r < 2; r++)
          asm volatile("{\n.reg .u32 t;\nadd.u32 t, %1, 1;\nst.async.weak.shared::cluster.mbarrier::complete_tx::bytes.v2.b32 [%0], {t, %2}, [%3];\n}"
            :: "r"(mapa(c.sb + OFF_TAG, r)), "r"(old), "r"(s), "r"(mapa(c.sb + OFF_SLOT, r)) : "memory");
      }
      __syncwarp();
      mbar_wait(c.sb + OFF_SLOT, 0);
      const uint32_t got = __shfl_sync(0xffffffffu, lds32(c.sb + OFF_TAG + 4), 0);
      if (got == slot) {
        bar_arrive(BAR_START, 256);
#pragma unroll 1
        for (int s = 0; s < 16 && c.w == 3; s += 8) {
          mbar_wait(c.sb + OFF_PRE + s, 0);
          PTL(12, 12 + s / 8);
          fence_async_smem();
          if (c.lane < 2) asm volatile("mbarrier.arrive.shared::cta.b64 _, [%0];" :: "r"(c.sb + OFF_FULL + s) : "memory");
        }
        break;
      }
      slot = got;
      if (c.w == 1)
#pragma unroll 1
        for (int s = 0; s < 4; s++) { mbar_wait(c.sb + (s < 2 ? OFF_PRE : OFF_FULL) + 8 * s, 0); asm volatile(ELECT "@p mbarrier.inval.shared::cta.b64 [%0];\n}" :: "r"(c.sb + OFF_FULL + 8 * s) : "memory"); }
    }
    const unsigned tag = smem_tag(c);
    if (c.w < 2) { asm volatile("cp.async.wait_all;" ::: "memory"); bar_sync(BAR_COPY, 64); PTL(14, 13); }
    if (c.w == 0) {
      const char* fp = (const char*)(g_flags + c.m * 32 + c.lane);
      unsigned ready = 1u << 31;
      float2 nx = lds64f(c.sb + OFF_PLAN);
#pragma unroll 1
      for (int g = 4; g < 2 * KB_LAYER; g++) {
        const uint32_t x = __float_as_uint(nx.x), y = __float_as_uint(nx.y);
        nx = lds64f(c.sb + OFF_PLAN + g * 16 - 48);
        if (y & A_NEW) ready = 1u << 31;
        for (unsigned it = 0; !((ready >> (x >> 27)) & 1) && it < SPIN_LIMIT; it++) {
          unsigned v; asm volatile("ld.relaxed.gpu.global.u32 %0, [%1];" : "=r"(v) : "l"(fp + (y >> 16)) : "memory");
          ready |= __ballot_sync(0xffffffffu, v == tag);
          asm volatile("fence.proxy.async.global;" ::: "memory");
        }
        mbar_wait(c.sb + OFF_EMPTY + (x & 0x38), x & 1);
        const uint32_t full = c.sb + OFF_FULL + 8 * (g & 7), dst = c.sb + (x & 0x3e000);
        const CUtensorMap* mp = (const CUtensorMap*)((const char*)&p + (y & 0x180));
        if (!(y & A_QUIET)) mbar_expect_e(full, y & 0x4004);
        if (!(y & A_COPY)) tma_ld4_mc_e(dst, mp, full, x & 0xfc0, c.m * 4 + c.rank * 2);
        else if (!(y & A_NONE)) { tma_ld4_e(dst, mp, full, x & 0xfc0, c.m * 4); tma_ld4_e(dst + 8192, mp, full, x & 0xfc0, c.m * 4 + 2); }
        else if (y & A_PAIR) {
          const uint32_t peer = mapa(c.sb, c.rank ^ 1);
          mbar_wait(c.sb + OFF_FULL, g < KB_LAYER);
          dsmem_copy_e(peer + 3 * 32768, c.sb + OFF_STG, peer + OFF_FULL + 8);
        }
      }
    } else if (c.w == 1) {
      float2 nx = lds64f(c.sb + OFF_PLAN + 8);
#pragma unroll 1
      for (int g = 4; g < 2 * KB_LAYER; g++) {
        const uint32_t x = __float_as_uint(nx.x), y = __float_as_uint(nx.y);
        nx = lds64f(c.sb + OFF_PLAN + g * 16 - 40);
        mbar_wait(c.sb + OFF_EMPTY + (x & 0x38), x & 1);
        const uint32_t full = c.sb + OFF_FULL + 8 * (g & 7);
        mbar_expect_e(full, y & 0x6000);
        tma_ld3_e(c.sb + (x & 0x3e000), (const CUtensorMap*)((const char*)&p + (y >> 16)), full, y & 0x3c0, x & 0xfc0, x >> 26);
      }
    } else if (c.w == 2) {
      if (c.lane == 0) epochs[blockIdx.x] = tag;
      mbar_pace(c.sb + OFF_EMPTY + 56, 0);
#pragma unroll 1
      for (int z = 0; z < 44; z++) st_tag128(g_halo + ((z & 3) * 128 + c.b) * 352 + (z >> 2) * 32 + c.lane, 0u, 0u, 0u, 0u);
      bar_arrive(BAR_FREE, 160);
#pragma unroll 1
      for (int t = 0; t < 14; t++) {
        const int layer = t >= 7, type = t - layer * 7;
        const int slab = c.m * 4;
        unsigned* flag = g_flags + c.m * 32 + c.j;
        if (type == 2 || type == 6) {
          flag += (t + 1) * 512 + c.j;
          bar_sync(BAR_RES, 160);
          fence_async_smem();
          asm volatile(ELECT "@p mbarrier.complete_tx.relaxed.cta.shared::cta.b64 [%0], 4;\n}" :: "r"(c.sb + OFF_FULL) : "memory");
          tma_st4_e(&p.st_out, c.sb + OFF_X, c.j * 128, slab);
          if (t < 13) {
            bulk_wait_read_e();
            PTL(t, 8);
            publish_e(flag++, tag);
            PTL(t, 9);
            mbar_wait(c.sb + OFF_FULL + 8, t != 2);
            mbar_wait(c.sb + OFF_EMPTY + 56, t == 2);
#pragma unroll
            for (int h = 0; h < 2; h++) tma_ld4_mc_e(c.sb + 3 * 40960 + h * 8192, &p.ld_out, c.sb + OFF_FULL + 40, c.j * 128, slab + 2 * h, 2 - c.rank);
          }
          if (t == 13) { bulk_wait_read_e(); break; }
          tma_st4_e(&p.ld_out, c.sb + OFF_X + A_BYTES, c.j * 128 + 64, slab);
          if (t < 13) mbar_pace(c.sb + OFF_FULL + 48, t != 2);
          tma_st4_e(&p.ld_out, c.sb + OFF_X + A_BYTES + 8192, c.j * 128 + 64, slab + 2);
          bulk_wait_read_e();
          PTL(t, 11);
        } else {
          flag += (layer * 7 + (type < 2 ? 2 : 6)) * 512 + (type < 2 ? type : type - 3) * 8;
          const int col = type < 2 ? (c.j + 8 * type) * 64 : type == 3 ? c.j * 192 : (type == 4 ? 1536 : 2560) + c.j * 128;
#pragma unroll 1
          for (int ch = type == 3 ? -1 : 0; ch < (type < 2 ? 1 : 2); ch++) {
            if (type < 2) fetch_halo(c, tag, layer * 2 + type);
            bar_sync(BAR_READY, 160);
            fence_async_smem();
#pragma unroll 1
            for (int z = 0; z < 4; z++) {
              if (z && type != 1) bulk_wait_read_e();
              tma_st4_e(&p.st_h, c.sb + OFF_STG + z * 4096, col + (ch < 0 ? 128 : ch * 64), slab + z);
            }
            if (type == 1) { mbar_wait(c.sb + OFF_FULL, layer); mbar_arrive_e(c.sb + OFF_FULL); }
            bulk_wait_read_e();
            if (t < 12 || ch == 0) bar_arrive(BAR_FREE, 160);
          }
          PTL(t, 14);
        }
        if (t < 13) publish_e(flag, tag);
        PTL(t, 6);
      }
    } else {
      mbar_pace(c.sb + OFF_EMPTY + 8 * (c.m & 3), 0);
      PTL(14, 14);
      mbar_expect_e(c.sb + OFF_XBAR, 32768);
#pragma unroll
      for (int i = 0; i < 4; i++) tma_ld4_e(c.sb + OFF_X + i * 8192, &p.ld_x, c.sb + OFF_XBAR, c.j * 128 + (i >> 1) * 64, c.m * 4 + (i & 1) * 2);
#pragma unroll
      for (int i = 0; i < 4; i++) sts32f(c.sb + OFF_B2 + i * 128 + c.lane * 4, __bfloat162float(p.b2[c.j * 128 + i * 32 + c.lane]));
#pragma unroll 1
      for (int part = 0; part < 7; part++) {
        if (part < 5) {
          load_table(c, p, part, tag);
          mbar_arrive_e(c.sb + OFF_TBL + 8 * part);
          PTL(part, 7);
        }
        if (part < 2 || part > 4) fetch_halo(c, tag, part < 2 ? part : part - 3);
        if ((0x52 >> part) & 1) {
          const uint32_t peer = mapa(c.sb, c.rank ^ 1);
          bar_sync(BAR_RES2, 160);
          mbar_wait(c.sb + OFF_EMPTY + 56, part == 1);
          dsmem_copy_e(peer + 2 * 40960, c.sb + OFF_X + A_BYTES, peer + OFF_FULL + 32);
        }
      }
    }
  } else {
    place(c, slot);
    const int r = tid >> 3;
    const uint32_t dst = c.sb + 2 * 40960 + r * 128 + ((tid ^ r) & 7) * 16;
    const char* ga = x0 + (c.m * 128 + (r & 15) * 2 + c.wg) * 2048 + (tid & 7) * 16;
    const char* gb = w0 + r * 6144 + c.j * 128 + (tid & 7) * 16;
#pragma unroll
    for (int s = 0; s < 2; s++) {
#pragma unroll
      for (int i = 0; i < 10; i++)
        asm volatile("cp.async.cg.shared.global [%0], [%1], 16;" :: "r"(dst + s * 40960 + i * 4096),
          "l"(i < 4 ? ga + i * 65536 + s * 128 : gb + (2 * s + (i & 1)) * (32 * 6144) + (i / 2 - 2) * 2048) : "memory");
      if (!s) {
        mbar_init_e(c.sb + OFF_EMPTY + 8 * k, 8);
        mbar_init_e(c.sb + (k < 4 ? OFF_XBAR : OFF_FULL) + 8 * k, k < 4 ? 1 : 2);
        if (k < 7) mbar_init_e(c.sb + OFF_XBAR + 32 + 8 * k, k > 4 ? 256 : 1);
        else sts128(c.sb + OFF_ZERO, 0u, 0u, 0u, 0u);
        asm volatile("fence.mbarrier_init.release.cluster;\nbarrier.cluster.arrive.relaxed.aligned;" ::: "memory");
        bar_sync(BAR_EPI, 256);
      }
      asm volatile("cp.async.mbarrier.arrive.noinc.shared::cta.b64 [%0];" :: "r"(c.sb + OFF_PRE + 8 * s) : "memory");
    }
    asm volatile("barrier.cluster.wait.aligned;" ::: "memory");
    reg_alloc<232>();
    if (c.wg) { mbar_wait(c.sb + OFF_XBAR, 0); TL(-1, 4); row_stats<8>(c, 1); }
#pragma unroll 1
    for (int t = c.wg; t < 14; t += 2) {
      const int layer = t >= 7, type = t - layer * 7;
      const int g0 = layer * KB_LAYER + type * 16;
      float acc[2][96];
      if (type == 2 || type == 6) {
        init_res(c, acc, t, type == 6);
        mainloop<128, 1>(c, acc, t, type, g0, (type == 6 ? 56 : 16) - SK);
        TL(t, 4);
        continue;
      }
      if (type < 4) {
        mainloop<192, 0>(c, acc, t, type, g0, type == 1 ? 13 : 16);
        if (type < 2) { epi_qkv(c, acc, t, type); goto done; }
        finish(c, t, 1);
        bar_sync(BAR_EPI + c.wg, 256);
        mbar_wait(c.sb + OFF_TBL + 16, 0);
        epi_up<2>(c, acc, type);
      } else {
        mainloop<128, 0>(c, acc, t, type, g0, 16);
        finish(c, t, 7);
        bar_sync(BAR_EPI + c.wg, 256);
        mbar_wait(c.sb + OFF_TBL + 8 * (type - 1), 0);
      }
      epi_up<0>(c, acc, type);
      TL(t, 4);
    done:
      if (type != 1 && type != 5) bar_arrive(BAR_EPI + (c.wg ^ 1), 256);
    }
    if (c.wg == 1) {
      asm volatile("barrier.cluster.wait.aligned;" ::: "memory");
    } else {
      const int b = smem_block(c), r = tid >> 3;
      char* dst = p.out + ((b >> 3) * 128 + r * 2) * 2048 + (b & 7) * 256 + 128 + (tid & 7) * 16;
      const uint32_t src = c.sb + OFF_X + A_BYTES + r * 128 + ((tid ^ r) & 7) * 16;
      asm volatile("barrier.cluster.arrive.relaxed.aligned;" ::: "memory");
#pragma unroll
      for (int h = 0; h < 4; h++) {
        bar_sync(h == 3 ? BAR_EPI : h == 1 ? BAR_START : h ? BAR_P1 : BAR_P0, 256);
        const float4 v0 = lds128f(src + h * 4096), v1 = lds128f(src + h * 4096 + 2048);
        *(float4*)(dst + h * 65536) = v0; *(float4*)(dst + h * 65536 + 2048) = v1;
      }
      asm volatile("barrier.cluster.wait.aligned;" ::: "memory");
    }
  }
}

typedef CUresult (*EncodeFn)(CUtensorMap*, CUtensorMapDataType, cuuint32_t, void*, const cuuint64_t*, const cuuint64_t*,
                             const cuuint32_t*, const cuuint32_t*, CUtensorMapInterleave, CUtensorMapSwizzle,
                             CUtensorMapL2promotion, CUtensorMapFloatOOBfill);

void make_map(EncodeFn fn, CUtensorMap* m, const void* ptr, int rank, const cuuint64_t* dims, const cuuint64_t* strides, const cuuint32_t* box) {
  const cuuint32_t es[4] = {1, 1, 1, 1};
  fn(m, CU_TENSOR_MAP_DATA_TYPE_BFLOAT16, rank, const_cast<void*>(ptr), dims, strides, box, es, CU_TENSOR_MAP_INTERLEAVE_NONE,
     CU_TENSOR_MAP_SWIZZLE_128B, CU_TENSOR_MAP_L2_PROMOTION_L2_128B, CU_TENSOR_MAP_FLOAT_OOB_FILL_NONE);
}
void map_rows(EncodeFn fn, CUtensorMap* m, const void* ptr, int cols, int rows, int box_slabs, bool tokens) {
  const cuuint64_t rb = (cuuint64_t)cols * 2;
  const cuuint64_t dims[4] = {(cuuint64_t)cols, 16, 2, (cuuint64_t)(rows / 32)};
  const cuuint64_t st[3] = {tokens ? 2 * rb : rb, tokens ? rb : 16 * rb, 32 * rb};
  const cuuint32_t box[4] = {64, 16, 2, (cuuint32_t)box_slabs};
  make_map(fn, m, ptr, 4, dims, st, box);
}
void map_w(EncodeFn fn, CUtensorMap* m, const void* ptr, int K, int N, int inner, int nch) {
  const cuuint64_t dims[3] = {(cuuint64_t)inner, (cuuint64_t)K, (cuuint64_t)(N / inner)}, st[2] = {(cuuint64_t)N * 2, (cuuint64_t)inner * 2};
  const cuuint32_t box[3] = {64, 64, (cuuint32_t)nch};
  make_map(fn, m, ptr, 3, dims, st, box);
}

}

extern "C" void kernel_launch(void* const* d_in, const int* in_sizes, int n_in, void* d_out, int out_size) {
  (void)in_sizes; (void)n_in; (void)out_size;
  Params p;
  p.b1 = (const __nv_bfloat16*)d_in[5]; p.b2 = (const __nv_bfloat16*)d_in[7]; p.out = (char*)d_out;
  void* fnp = nullptr; cudaDriverEntryPointQueryResult qr;
  cudaGetDriverEntryPoint("cuTensorMapEncodeTiled", &fnp, cudaEnableDefault, &qr);
  EncodeFn fn = (EncodeFn)fnp;
  void *h, *epochs;
  cudaGetSymbolAddress(&h, g_h);
  cudaGetSymbolAddress(&epochs, g_plan);
  map_rows(fn, &p.ld_x, d_in[0], D_, S_, 2, true);
  map_rows(fn, &p.ld_out, d_out, D_, S_, 2, true);
  map_rows(fn, &p.ld_h, h, F_, S_, 2, false);
  map_rows(fn, &p.st_h, h, F_, S_, 1, false);
  map_rows(fn, &p.st_out, d_out, D_, S_, 4, true);
  map_w(fn, &p.w_qkv, d_in[1], D_, 3 * D_, D_, 3);
  map_w(fn, &p.w_o, d_in[2], D_, D_, 64, 2);
  map_w(fn, &p.w_1a, d_in[4], D_, F_, 64, 3);
  map_w(fn, &p.w_1b, d_in[4], D_, F_, 64, 2);
  map_w(fn, &p.w_2, d_in[6], F_, D_, 64, 2);
  cudaFuncSetAttribute(fused_kernel, cudaFuncAttributeMaxDynamicSharedMemorySize, SMEM_BYTES);
  fused_kernel<<<132, 384, SMEM_BYTES>>>((unsigned*)epochs, (const char*)d_in[0], (const char*)d_in[1], p);
}
```
